```python
import torch

def _softmax(x, axis=-1):
    return torch.softmax(x, dim=axis)
def _gelu(x):
    return torch.nn.functional.gelu(x, approximate="tanh")
def _silu(x):
    return torch.nn.functional.silu(x)
def _sigmoid(x):
    return torch.sigmoid(x)
def _layernorm(x, axis=-1, eps=1e-5):
    m = x.mean(dim=axis, keepdim=True)
    v = x.var(dim=axis, keepdim=True, unbiased=False)
    return (x - m) / torch.sqrt(v + eps)
def _scatter_add(tgt, idx, src, axis=0):
    return tgt.clone().index_add_(axis, idx, src)
def _segment_sum(src, seg, n):
    out = torch.zeros((n,) + src.shape[1:], dtype=src.dtype)
    return out.index_add_(0, seg, src)
def _pad(x, pw):
    flat = tuple(v for pair in reversed(pw) for v in pair)
    return torch.nn.functional.pad(x, flat)

kernel_name = 'sequential_preLN__linear_attn_block__moe_arch_mod__prompt'

def setup_inputs():

    _w = (lambda a: (lambda t: t.to(torch.bfloat16) if t.is_floating_point() else t)(torch.as_tensor(a)))
    def _A_setup():
        B, S, D = 1, 2048, 1024
        return {
            "x": _w((lambda *s: torch.randn(*s, dtype=torch.bfloat16) * 0.05)(B, S, D)),
            "wqkv": _w((lambda *s: torch.randn(*s, dtype=torch.bfloat16) * 0.05)(D, 3 * D)),
            "wo": _w((lambda *s: torch.randn(*s, dtype=torch.bfloat16) * 0.05)(D, D)),
        }
    _A_in = _A_setup()

    def _B_setup():
        B, S, D, F, C = 1, 2048, 1024, 3584, 2
        return {
            "x": _w((lambda *s: torch.randn(*s, dtype=torch.bfloat16) * 0.05)(B, S, D)),
            "w_r": _w((lambda *s: torch.randn(*s, dtype=torch.bfloat16) * 0.05)(D)),
            "w_gate": _w((lambda *s: torch.randn(*s, dtype=torch.bfloat16) * 0.05)(D, F)),
            "w_up": _w((lambda *s: torch.randn(*s, dtype=torch.bfloat16) * 0.05)(D, F)),
            "w_down": _w((lambda *s: torch.randn(*s, dtype=torch.bfloat16) * 0.05)(F, D)),
        }
    _B_in = _B_setup()

    return {
        "A_x": _A_in["x"],
        "A_wqkv": _A_in["wqkv"],
        "A_wo": _A_in["wo"],
        "B_x": _B_in["x"],
        "B_w_r": _B_in["w_r"],
        "B_w_gate": _B_in["w_gate"],
        "B_w_up": _B_in["w_up"],
        "B_w_down": _B_in["w_down"],
    }

def reference(A_x, A_wqkv, A_wo, B_x, B_w_r, B_w_gate, B_w_up, B_w_down):
    def _A_ref(x, wqkv, wo):
        B, S, D = x.shape
        H = 32; Dh = D // H
        qkv = (lambda x, *d: x.permute(*d))((x @ wqkv).reshape(B, S, 3, H, Dh), 2, 0, 3, 1, 4)
        q, k, v = qkv[0], qkv[1], qkv[2]
        phi = lambda t: torch.where(t > 0, t + 1, torch.exp(t)) + 1e-6
        pq, pk = phi(q), phi(k)
        kv = torch.einsum("bhsd,bhse->bhde", pk, v)
        z = torch.einsum("bhsd->bhd", pk)
        num = torch.einsum("bhqd,bhde->bhqe", pq, kv)
        den = torch.einsum("bhqd,bhd->bhq", pq, z)[..., None] + 1e-6
        o = num / den
        return (lambda x, *d: x.permute(*d))(o, 0, 2, 1, 3).reshape(B, S, D) @ wo

    def _B_ref(x, w_r, w_gate, w_up, w_down):
        B, S, D = x.shape
        C = 2
        r = x @ w_r
        idx = torch.argsort(-r, axis=-1)[:, :C]
        idx_e = (lambda x, n, axis: torch.repeat_interleave(x, n, dim=axis))(idx.reshape(B, C, 1), D, axis=2)
        x_sel = (lambda x, i, axis: torch.take_along_dim(x, i, dim=axis))(x, idx_e, axis=1)
        g = _silu(x_sel @ w_gate)
        u = x_sel @ w_up
        y = (g * u) @ w_down
        r_sel = _sigmoid((lambda x, i, axis: torch.take_along_dim(x, i, dim=axis))(r, idx, axis=1))
        y = y * r_sel.reshape(B, C, 1)
        b_off = (torch.arange(B) * S).reshape(B, 1)
        flat_idx = (idx + b_off).reshape(B * C)
        zero = (x * 0.0).reshape(B * S, D)
        upd = _scatter_add(zero, flat_idx, y.reshape(B * C, D), axis=0)
        return x + upd.reshape(B, S, D)

    x = A_x
    h = x + _A_ref(_layernorm(x, axis=-1), A_wqkv, A_wo)
    h2 = h + _B_ref(_layernorm(h, axis=-1), B_w_r, B_w_gate, B_w_up, B_w_down)
    return h2
```

```cpp
#include <cuda_runtime.h>
#include <cuda.h>
#include <cuda_bf16.h>
#include <stdint.h>
#include <type_traits>

namespace {

constexpr int S_ = 2048, D_ = 1024, F_ = 3584;
constexpr int NCTA = 128, NFFN = 112;
constexpr uint32_t SENT = 0xFFFFFFFFu;
constexpr int SPIN_LIMIT = 1 << 20;

#define ADELAY 700
#define PFA 1
#define NOPF 0
#define QHOLD 1
#define NPULL 12
#define CDELAY 0
#define NOUTW 3
#define YDELAY 500
#define EFX 0
#define EFW 1
#define EFF 1
#define KLEAD 13
#define GPACE 12
#define NDIR 4
#define PULL0 5
#define DMASK 0x2490
#define PFST 1
#define W0OFF 2
#define XWPF 0
constexpr uint32_t STAGE_B = 57344;
__host__ __device__ constexpr uint32_t xoff(int s) { return s < 2 ? s * 57344 : 98304 + s * 32768; }
__host__ __device__ constexpr uint32_t woff(int s) { return s < 1 ? 32768 : 65536 + s * 24576; }
constexpr uint32_t OFF_STATS = 229376;
constexpr uint32_t OFF_COLSUM = 231424;
constexpr uint32_t OFF_BARS = 232192;
constexpr uint32_t SMEM_BYTES = 232448;
constexpr uint32_t B_FULL = 0, B_EMPTY = 32, B_AUX = 64, B_EV0 = 72, B_EV1 = 80, B_FULL3 = 88, B_SW = 216, B_OUT = 224, B_LATE = 232, B_SEL = B_FULL + 8, B_FFN = 240;
constexpr uint32_t OFF_EBAR = OFF_STATS + 912;
constexpr uint32_t SLOT_B = 16384;
constexpr uint32_t sb = 1024;
constexpr uint32_t bars = sb + OFF_BARS;
constexpr uint32_t GU_SLOTS = 0xB1A09876u;
constexpr uint32_t OFF_LNP = OFF_STATS + 1024;
constexpr uint32_t OFF_KVB = 13 * SLOT_B + 8192;

__device__ unsigned g_epoch;
__device__ uint4 g_st1[S_ / 2];
__device__ uint4 g_csp[16 * 8 * 48];
__device__ uint4 g_kvp[16 * 8 * 272];
__device__ uint4 g_obuf[32 * 64 * 128];
__device__ uint4 g_st2[S_];
__device__ uint4 g_hsel[32 * 256];
__device__ uint32_t g_cand[8 * 32];
__device__ uint4 g_ybuf[NCTA * NFFN * 4];
#define TS_DECL
#define TS(i)
#define TSG(i)
#define TSV(i, v)
#define TS_DUMP(slot)
#define PTS(i)

__device__ __forceinline__ uint32_t smem_u32(const void* p) { return (uint32_t)__cvta_generic_to_shared(p); }
__device__ __forceinline__ void mbar_init(uint32_t bar, uint32_t cnt) { asm volatile("mbarrier.init.shared::cta.b64 [%0], %1;" :: "r"(bar), "r"(cnt) : "memory"); }
__device__ __forceinline__ void mbar_expect_tx(uint32_t bar, uint32_t bytes) { asm volatile("mbarrier.arrive.expect_tx.shared::cta.b64 _, [%0], %1;" :: "r"(bar), "r"(bytes) : "memory"); }
__device__ __forceinline__ void mbar_arrive(uint32_t bar) { asm volatile("mbarrier.arrive.shared::cta.b64 _, [%0];" :: "r"(bar) : "memory"); }
#define SPINCHK(it, code) if ((it) > SPIN_LIMIT) break
__device__ __forceinline__ void mbar_wait(uint32_t bar, uint32_t parity) {
  asm volatile("{\n.reg .pred p;\n.reg .u32 c;\nmov.u32 c, 0;\n"
               "WL:\nmbarrier.try_wait.parity.shared::cta.b64 p, [%0], %1;\n@p bra WD;\n"
               "add.u32 c, c, 1;\nsetp.lt.u32 p, c, 1048576;\n@p bra WL;\nWD:\n}" :: "r"(bar), "r"(parity) : "memory");
}
__device__ __forceinline__ uint64_t l2_stream() { uint64_t p; asm("createpolicy.fractional.L2::evict_first.b64 %0, 1.0;" : "=l"(p)); return p; }
__device__ __forceinline__ void tma_2d(uint32_t dst, const CUtensorMap* tm, int c0, int c1, uint32_t bar, bool stream) {
  if (stream) asm volatile("cp.async.bulk.tensor.2d.shared::cluster.global.mbarrier::complete_tx::bytes.L2::cache_hint [%0], [%1, {%3, %4}], [%2], %5;"
                           :: "r"(dst), "l"(tm), "r"(bar), "r"(c0), "r"(c1), "l"(l2_stream()) : "memory");
  else asm volatile("cp.async.bulk.tensor.2d.shared::cluster.global.mbarrier::complete_tx::bytes [%0], [%1, {%3, %4}], [%2];"
                    :: "r"(dst), "l"(tm), "r"(bar), "r"(c0), "r"(c1) : "memory");
}
__device__ __forceinline__ void tma_3d(uint32_t dst, const CUtensorMap* tm, int c0, int c1, int c2, uint32_t bar, bool stream) {
  if (stream) asm volatile("cp.async.bulk.tensor.3d.shared::cluster.global.mbarrier::complete_tx::bytes.L2::cache_hint [%0], [%1, {%3, %4, %5}], [%2], %6;"
                           :: "r"(dst), "l"(tm), "r"(bar), "r"(c0), "r"(c1), "r"(c2), "l"(l2_stream()) : "memory");
  else asm volatile("cp.async.bulk.tensor.3d.shared::cluster.global.mbarrier::complete_tx::bytes [%0], [%1, {%3, %4, %5}], [%2];"
                    :: "r"(dst), "l"(tm), "r"(bar), "r"(c0), "r"(c1), "r"(c2) : "memory");
}
__device__ __forceinline__ void tma_2d_mc(uint32_t dst, const CUtensorMap* tm, int c0, int c1, uint32_t bar, bool stream) {
  if (stream) asm volatile("cp.async.bulk.tensor.2d.shared::cluster.global.mbarrier::complete_tx::bytes.multicast::cluster.L2::cache_hint [%0], [%1, {%3, %4}], [%2], %5, %6;"
                           :: "r"(dst), "l"(tm), "r"(bar), "r"(c0), "r"(c1), "h"((uint16_t)3), "l"(l2_stream()) : "memory");
  else asm volatile("cp.async.bulk.tensor.2d.shared::cluster.global.mbarrier::complete_tx::bytes.multicast::cluster [%0], [%1, {%3, %4}], [%2], %5;"
                    :: "r"(dst), "l"(tm), "r"(bar), "r"(c0), "r"(c1), "h"((uint16_t)3) : "memory");
}
__device__ __forceinline__ bool elect_one() {
  uint32_t p;
  asm volatile("{\n.reg .pred q;\nelect.sync _|q, 0xFFFFFFFF;\nselp.u32 %0, 1, 0, q;\n}" : "=r"(p));
  return p;
}
__device__ __forceinline__ void bulk_load_mc(uint32_t dst, const void* src, uint32_t bytes, uint32_t bar) {
  asm volatile("{\n.reg .pred q;\nelect.sync _|q, 0xFFFFFFFF;\n"
               "@q cp.async.bulk.shared::cluster.global.mbarrier::complete_tx::bytes.multicast::cluster [%0], [%1], %2, [%3], %4;\n}"
               :: "r"(dst), "l"(src), "r"(bytes), "r"(bar), "h"((uint16_t)3) : "memory");
}
__device__ __forceinline__ void bulk_store(void* dst, uint32_t src, uint32_t bytes) {
  asm volatile("cp.async.bulk.global.shared::cta.bulk_group [%0], [%1], %2;" :: "l"(dst), "r"(src), "r"(bytes) : "memory");
}
__device__ __forceinline__ void mbar_arrive_rem(uint32_t bar) { asm volatile("mbarrier.arrive.shared::cluster.b64 _, [%0];" :: "r"(bar) : "memory"); }
__device__ __forceinline__ void st_async4(uint32_t addr, const uint4& v, uint32_t bar) {
  asm volatile("st.async.shared::cluster.mbarrier::complete_tx::bytes.v4.b32 [%0], {%1,%2,%3,%4}, [%5];" :: "r"(addr), "r"(v.x), "r"(v.y), "r"(v.z), "r"(v.w), "r"(bar) : "memory");
}
template <uint32_t O> __device__ __forceinline__ void ldsm4_o(uint32_t addr, uint32_t& a, uint32_t& b, uint32_t& c, uint32_t& d) {
  asm volatile("ldmatrix.sync.aligned.m8n8.x4.shared.b16 {%0,%1,%2,%3}, [%4+%5];" : "=r"(a), "=r"(b), "=r"(c), "=r"(d) : "r"(addr), "n"(O) : "memory");
}
template <uint32_t O> __device__ __forceinline__ void ldsm4t_o(uint32_t addr, uint32_t (&r)[4]) {
  asm volatile("ldmatrix.sync.aligned.m8n8.x4.trans.shared.b16 {%0,%1,%2,%3}, [%4+%5];" : "=r"(r[0]), "=r"(r[1]), "=r"(r[2]), "=r"(r[3]) : "r"(addr), "n"(O) : "memory");
}
__device__ __forceinline__ void mma16816(float (&c)[4], const uint32_t (&a)[4], uint32_t b0, uint32_t b1) {
  asm("mma.sync.aligned.m16n8k16.row.col.f32.bf16.bf16.f32 {%0,%1,%2,%3}, {%4,%5,%6,%7}, {%8,%9}, {%0,%1,%2,%3};"
      : "+f"(c[0]), "+f"(c[1]), "+f"(c[2]), "+f"(c[3]) : "r"(a[0]), "r"(a[1]), "r"(a[2]), "r"(a[3]), "r"(b0), "r"(b1));
}
__device__ __forceinline__ void l2_prefetch(const void* p) { asm volatile("prefetch.global.L2 [%0];" :: "l"(p) : "memory"); }
__device__ __forceinline__ uint32_t ld_line(const void* p) { uint32_t v; asm volatile("ld.global.cg.L2::128B.u32 %0, [%1];" : "=r"(v) : "l"(p) : "memory"); return v; }
__device__ __forceinline__ void tmap_prefetch(const CUtensorMap* tm) { asm volatile("prefetch.tensormap [%0];" :: "l"(tm) : "memory"); }
__device__ __forceinline__ void wg_fence() { asm volatile("wgmma.fence.sync.aligned;" ::: "memory"); }
__device__ __forceinline__ void wg_commit() { asm volatile("wgmma.commit_group.sync.aligned;" ::: "memory"); }
template <int N> __device__ __forceinline__ void wg_wait() { asm volatile("wgmma.wait_group.sync.aligned %0;" :: "n"(N) : "memory"); }
template <int N> __device__ __forceinline__ void pin(float (&d)[N]) {
#pragma unroll
  for (int i = 0; i < N; i++) asm volatile("" : "+f"(d[i]) :: "memory");
}
__device__ __forceinline__ void pin4(uint4& v) { asm volatile("" : "+r"(v.x), "+r"(v.y), "+r"(v.z), "+r"(v.w) :: "memory"); }
template <uint32_t SBO, uint32_t SWZ> __device__ __forceinline__ uint64_t dsc(uint32_t lo) { return ((uint64_t)((SBO >> 4) | (SWZ << 30)) << 32) | lo; }
__host__ __device__ constexpr uint32_t dlo(uint32_t addr, uint32_t lbo) { return (addr >> 4) | ((lbo >> 4) << 16); }
__device__ __forceinline__ void bar_sync(int id, int n) { asm volatile("bar.sync %0, %1;" :: "r"(id), "r"(n) : "memory"); }
__device__ __forceinline__ void bar_arrive(int id, int n) { asm volatile("bar.arrive %0, %1;" :: "r"(id), "r"(n) : "memory"); }
__device__ __forceinline__ void fence_async_smem() { asm volatile("fence.proxy.async.shared::cta;" ::: "memory"); }
__device__ __forceinline__ void fence_gpu() { asm volatile("fence.acq_rel.gpu;" ::: "memory"); }
__device__ __forceinline__ uint4 ld_cg4(const void* p) { uint4 v; asm volatile("ld.global.cg.v4.u32 {%0,%1,%2,%3}, [%4];" : "=r"(v.x), "=r"(v.y), "=r"(v.z), "=r"(v.w) : "l"(p) : "memory"); return v; }
__device__ __forceinline__ uint4 ld_rlx4(const void* p) { uint4 v; asm volatile("ld.relaxed.gpu.global.v4.u32 {%0,%1,%2,%3}, [%4];" : "=r"(v.x), "=r"(v.y), "=r"(v.z), "=r"(v.w) : "l"(p) : "memory"); return v; }
__device__ __forceinline__ uint32_t ld_rlx(const void* p) { uint32_t v; asm volatile("ld.relaxed.gpu.global.u32 %0, [%1];" : "=r"(v) : "l"(p) : "memory"); return v; }
__device__ __forceinline__ void st_rlx4(void* p, uint4 v) { asm volatile("st.relaxed.gpu.global.v4.u32 [%0], {%1,%2,%3,%4};" :: "l"(p), "r"(v.x), "r"(v.y), "r"(v.z), "r"(v.w) : "memory"); }
__device__ __forceinline__ void st_rlx2(void* p, uint32_t a, uint32_t b) { asm volatile("st.relaxed.gpu.global.v2.u32 [%0], {%1,%2};" :: "l"(p), "r"(a), "r"(b) : "memory"); }
__device__ __forceinline__ void st_rlx(void* p, uint32_t a) { asm volatile("st.relaxed.gpu.global.u32 [%0], %1;" :: "l"(p), "r"(a) : "memory"); }
__device__ __forceinline__ void red4(void* p, float a, float b, float c, float d) { asm volatile("red.relaxed.gpu.global.add.v4.f32 [%0], {%1,%2,%3,%4};" :: "l"(p), "f"(a), "f"(b), "f"(c), "f"(d) : "memory"); }
__device__ __forceinline__ uint32_t pack2(float lo, float hi) { uint32_t r; asm("cvt.rn.bf16x2.f32 %0, %1, %2;" : "=r"(r) : "f"(hi), "f"(lo)); return r; }
__device__ __forceinline__ float bf_lo(uint32_t v) { return __uint_as_float(v << 16); }
__device__ __forceinline__ float bf_hi(uint32_t v) { return __uint_as_float(v & 0xFFFF0000u); }
__device__ __forceinline__ void stsm4(uint32_t addr, uint32_t a, uint32_t b, uint32_t c, uint32_t d) {
  asm volatile("stmatrix.sync.aligned.m8n8.x4.shared.b16 [%0], {%1,%2,%3,%4};" :: "r"(addr), "r"(a), "r"(b), "r"(c), "r"(d) : "memory");
}
template <uint32_t O> __device__ __forceinline__ void stsm4_o(uint32_t addr, uint32_t a, uint32_t b, uint32_t c, uint32_t d) {
  asm volatile("stmatrix.sync.aligned.m8n8.x4.shared.b16 [%0+%5], {%1,%2,%3,%4};" :: "r"(addr), "r"(a), "r"(b), "r"(c), "r"(d), "n"(O) : "memory");
}
__device__ __forceinline__ void sts4(uint32_t addr, uint32_t a, uint32_t b, uint32_t c, uint32_t d) { asm volatile("st.shared.v4.u32 [%0], {%1,%2,%3,%4};" :: "r"(addr), "r"(a), "r"(b), "r"(c), "r"(d) : "memory"); }
__device__ __forceinline__ void sts2f(uint32_t addr, float a, float b) { asm volatile("st.shared.v2.f32 [%0], {%1,%2};" :: "r"(addr), "f"(a), "f"(b) : "memory"); }
__device__ __forceinline__ void sts1(uint32_t addr, uint32_t a) { asm volatile("st.shared.u32 [%0], %1;" :: "r"(addr), "r"(a) : "memory"); }
__device__ __forceinline__ float2 lds2f(uint32_t addr) { float2 v; asm volatile("ld.shared.v2.f32 {%0,%1}, [%2];" : "=f"(v.x), "=f"(v.y) : "r"(addr) : "memory"); return v; }
template <uint32_t O> __device__ __forceinline__ float2 lds2f_o(uint32_t addr) { float2 v; asm volatile("ld.shared.v2.f32 {%0,%1}, [%2+%3];" : "=f"(v.x), "=f"(v.y) : "r"(addr), "n"(O) : "memory"); return v; }
template <int I, int N, class F> __device__ __forceinline__ void static_for(F&& f) { if constexpr (I < N) { f(std::integral_constant<int, I>{}); static_for<I + 1, N>(f); } }
__device__ __forceinline__ uint4 lds4(uint32_t addr) { uint4 v; asm volatile("ld.shared.v4.u32 {%0,%1,%2,%3}, [%4];" : "=r"(v.x), "=r"(v.y), "=r"(v.z), "=r"(v.w) : "r"(addr) : "memory"); return v; }
__device__ __forceinline__ uint32_t lds1(uint32_t addr) { uint32_t v; asm volatile("ld.shared.u32 %0, [%1];" : "=r"(v) : "r"(addr) : "memory"); return v; }
__device__ __forceinline__ float ex2(float x) { float y; asm("ex2.approx.ftz.f32 %0, %1;" : "=f"(y) : "f"(x)); return y; }
__device__ __forceinline__ uint32_t max4(uint32_t m, const uint4& v) { return __vimax3_u32(__vimax3_u32(m, v.x, v.y), v.z, v.w); }
__device__ __forceinline__ float rsq(float x) { float y; asm("rsqrt.approx.ftz.f32 %0, %1;" : "=f"(y) : "f"(x)); return y; }
__device__ __forceinline__ float rcp(float x) { float y; asm("rcp.approx.ftz.f32 %0, %1;" : "=f"(y) : "f"(x)); return y; }
__device__ __forceinline__ uint2 ld_rlx2(const void* p) { uint2 v; asm volatile("ld.relaxed.gpu.global.v2.u32 {%0,%1}, [%2];" : "=r"(v.x), "=r"(v.y) : "l"(p) : "memory"); return v; }
template <uint32_t O> __device__ __forceinline__ uint4 lds4_o(uint32_t addr) { uint4 v; asm volatile("ld.shared.v4.u32 {%0,%1,%2,%3}, [%4+%5];" : "=r"(v.x), "=r"(v.y), "=r"(v.z), "=r"(v.w) : "r"(addr), "n"(O) : "memory"); return v; }
__device__ __forceinline__ float phi(float u, float rstd, float rl) { return fmaf(fmaxf(u, 0.f), rstd, __saturatef(ex2(u * rl) + 1e-6f)); }

template<int TA, int TB, int OFF, int SZ> __device__ __forceinline__ void wgmma_n192_ss(float (&d)[SZ], uint64_t da, uint64_t db, int scale_d) {
  asm volatile("{\n.reg .pred p;\nsetp.ne.b32 p, %98, 0;\n"
    "wgmma.mma_async.sync.aligned.m64n192k16.f32.bf16.bf16 {%0,%1,%2,%3,%4,%5,%6,%7,%8,%9,%10,%11,%12,%13,%14,%15,%16,%17,%18,%19,%20,%21,%22,%23,%24,%25,%26,%27,%28,%29,%30,%31,%32,%33,%34,%35,%36,%37,%38,%39,%40,%41,%42,%43,%44,%45,%46,%47,%48,%49,%50,%51,%52,%53,%54,%55,%56,%57,%58,%59,%60,%61,%62,%63,%64,%65,%66,%67,%68,%69,%70,%71,%72,%73,%74,%75,%76,%77,%78,%79,%80,%81,%82,%83,%84,%85,%86,%87,%88,%89,%90,%91,%92,%93,%94,%95}, %96, %97, p, 1, 1, %99, %100;\n}\n"
    : "+f"(d[OFF+0]), "+f"(d[OFF+1]), "+f"(d[OFF+2]), "+f"(d[OFF+3]), "+f"(d[OFF+4]), "+f"(d[OFF+5]), "+f"(d[OFF+6]), "+f"(d[OFF+7]),
      "+f"(d[OFF+8]), "+f"(d[OFF+9]), "+f"(d[OFF+10]), "+f"(d[OFF+11]), "+f"(d[OFF+12]), "+f"(d[OFF+13]), "+f"(d[OFF+14]), "+f"(d[OFF+15]),
      "+f"(d[OFF+16]), "+f"(d[OFF+17]), "+f"(d[OFF+18]), "+f"(d[OFF+19]), "+f"(d[OFF+20]), "+f"(d[OFF+21]), "+f"(d[OFF+22]), "+f"(d[OFF+23]),
      "+f"(d[OFF+24]), "+f"(d[OFF+25]), "+f"(d[OFF+26]), "+f"(d[OFF+27]), "+f"(d[OFF+28]), "+f"(d[OFF+29]), "+f"(d[OFF+30]), "+f"(d[OFF+31]),
      "+f"(d[OFF+32]), "+f"(d[OFF+33]), "+f"(d[OFF+34]), "+f"(d[OFF+35]), "+f"(d[OFF+36]), "+f"(d[OFF+37]), "+f"(d[OFF+38]), "+f"(d[OFF+39]),
      "+f"(d[OFF+40]), "+f"(d[OFF+41]), "+f"(d[OFF+42]), "+f"(d[OFF+43]), "+f"(d[OFF+44]), "+f"(d[OFF+45]), "+f"(d[OFF+46]), "+f"(d[OFF+47]),
      "+f"(d[OFF+48]), "+f"(d[OFF+49]), "+f"(d[OFF+50]), "+f"(d[OFF+51]), "+f"(d[OFF+52]), "+f"(d[OFF+53]), "+f"(d[OFF+54]), "+f"(d[OFF+55]),
      "+f"(d[OFF+56]), "+f"(d[OFF+57]), "+f"(d[OFF+58]), "+f"(d[OFF+59]), "+f"(d[OFF+60]), "+f"(d[OFF+61]), "+f"(d[OFF+62]), "+f"(d[OFF+63]),
      "+f"(d[OFF+64]), "+f"(d[OFF+65]), "+f"(d[OFF+66]), "+f"(d[OFF+67]), "+f"(d[OFF+68]), "+f"(d[OFF+69]), "+f"(d[OFF+70]), "+f"(d[OFF+71]),
      "+f"(d[OFF+72]), "+f"(d[OFF+73]), "+f"(d[OFF+74]), "+f"(d[OFF+75]), "+f"(d[OFF+76]), "+f"(d[OFF+77]), "+f"(d[OFF+78]), "+f"(d[OFF+79]),
      "+f"(d[OFF+80]), "+f"(d[OFF+81]), "+f"(d[OFF+82]), "+f"(d[OFF+83]), "+f"(d[OFF+84]), "+f"(d[OFF+85]), "+f"(d[OFF+86]), "+f"(d[OFF+87]),
      "+f"(d[OFF+88]), "+f"(d[OFF+89]), "+f"(d[OFF+90]), "+f"(d[OFF+91]), "+f"(d[OFF+92]), "+f"(d[OFF+93]), "+f"(d[OFF+94]), "+f"(d[OFF+95])
    : "l"(da), "l"(db), "r"(scale_d), "n"(TA), "n"(TB));
}
template<int TA, int TB, int OFF, int SZ> __device__ __forceinline__ void wgmma_n72_ss(float (&d)[SZ], uint64_t da, uint64_t db, int scale_d) {
  asm volatile("{\n.reg .pred p;\nsetp.ne.b32 p, %38, 0;\n"
    "wgmma.mma_async.sync.aligned.m64n72k16.f32.bf16.bf16 {%0,%1,%2,%3,%4,%5,%6,%7,%8,%9,%10,%11,%12,%13,%14,%15,%16,%17,%18,%19,%20,%21,%22,%23,%24,%25,%26,%27,%28,%29,%30,%31,%32,%33,%34,%35}, %36, %37, p, 1, 1, %39, %40;\n}\n"
    : "+f"(d[OFF+0]), "+f"(d[OFF+1]), "+f"(d[OFF+2]), "+f"(d[OFF+3]), "+f"(d[OFF+4]), "+f"(d[OFF+5]), "+f"(d[OFF+6]), "+f"(d[OFF+7]),
      "+f"(d[OFF+8]), "+f"(d[OFF+9]), "+f"(d[OFF+10]), "+f"(d[OFF+11]), "+f"(d[OFF+12]), "+f"(d[OFF+13]), "+f"(d[OFF+14]), "+f"(d[OFF+15]),
      "+f"(d[OFF+16]), "+f"(d[OFF+17]), "+f"(d[OFF+18]), "+f"(d[OFF+19]), "+f"(d[OFF+20]), "+f"(d[OFF+21]), "+f"(d[OFF+22]), "+f"(d[OFF+23]),
      "+f"(d[OFF+24]), "+f"(d[OFF+25]), "+f"(d[OFF+26]), "+f"(d[OFF+27]), "+f"(d[OFF+28]), "+f"(d[OFF+29]), "+f"(d[OFF+30]), "+f"(d[OFF+31]),
      "+f"(d[OFF+32]), "+f"(d[OFF+33]), "+f"(d[OFF+34]), "+f"(d[OFF+35])
    : "l"(da), "l"(db), "r"(scale_d), "n"(TA), "n"(TB));
}
template<int TB, int OFF, int SZ> __device__ __forceinline__ void wgmma_n40_rs(float (&d)[SZ], uint32_t a0, uint32_t a1, uint32_t a2, uint32_t a3, uint64_t db, int scale_d) {
  asm volatile("{\n.reg .pred p;\nsetp.ne.b32 p, %25, 0;\n"
    "wgmma.mma_async.sync.aligned.m64n40k16.f32.bf16.bf16 {%0,%1,%2,%3,%4,%5,%6,%7,%8,%9,%10,%11,%12,%13,%14,%15,%16,%17,%18,%19}, {%20,%21,%22,%23}, %24, p, 1, 1, %26;\n}\n"
    : "+f"(d[OFF+0]), "+f"(d[OFF+1]), "+f"(d[OFF+2]), "+f"(d[OFF+3]), "+f"(d[OFF+4]), "+f"(d[OFF+5]), "+f"(d[OFF+6]), "+f"(d[OFF+7]),
      "+f"(d[OFF+8]), "+f"(d[OFF+9]), "+f"(d[OFF+10]), "+f"(d[OFF+11]), "+f"(d[OFF+12]), "+f"(d[OFF+13]), "+f"(d[OFF+14]), "+f"(d[OFF+15]),
      "+f"(d[OFF+16]), "+f"(d[OFF+17]), "+f"(d[OFF+18]), "+f"(d[OFF+19])
    : "r"(a0), "r"(a1), "r"(a2), "r"(a3), "l"(db), "r"(scale_d), "n"(TB));
}
template<int TB, int OFF, int SZ> __device__ __forceinline__ void wgmma_n128_rs(float (&d)[SZ], uint32_t a0, uint32_t a1, uint32_t a2, uint32_t a3, uint64_t db, int scale_d) {
  asm volatile("{\n.reg .pred p;\nsetp.ne.b32 p, %69, 0;\n"
    "wgmma.mma_async.sync.aligned.m64n128k16.f32.bf16.bf16 {%0,%1,%2,%3,%4,%5,%6,%7,%8,%9,%10,%11,%12,%13,%14,%15,%16,%17,%18,%19,%20,%21,%22,%23,%24,%25,%26,%27,%28,%29,%30,%31,%32,%33,%34,%35,%36,%37,%38,%39,%40,%41,%42,%43,%44,%45,%46,%47,%48,%49,%50,%51,%52,%53,%54,%55,%56,%57,%58,%59,%60,%61,%62,%63}, {%64,%65,%66,%67}, %68, p, 1, 1, %70;\n}\n"
    : "+f"(d[OFF+0]), "+f"(d[OFF+1]), "+f"(d[OFF+2]), "+f"(d[OFF+3]), "+f"(d[OFF+4]), "+f"(d[OFF+5]), "+f"(d[OFF+6]), "+f"(d[OFF+7]),
      "+f"(d[OFF+8]), "+f"(d[OFF+9]), "+f"(d[OFF+10]), "+f"(d[OFF+11]), "+f"(d[OFF+12]), "+f"(d[OFF+13]), "+f"(d[OFF+14]), "+f"(d[OFF+15]),
      "+f"(d[OFF+16]), "+f"(d[OFF+17]), "+f"(d[OFF+18]), "+f"(d[OFF+19]), "+f"(d[OFF+20]), "+f"(d[OFF+21]), "+f"(d[OFF+22]), "+f"(d[OFF+23]),
      "+f"(d[OFF+24]), "+f"(d[OFF+25]), "+f"(d[OFF+26]), "+f"(d[OFF+27]), "+f"(d[OFF+28]), "+f"(d[OFF+29]), "+f"(d[OFF+30]), "+f"(d[OFF+31]),
      "+f"(d[OFF+32]), "+f"(d[OFF+33]), "+f"(d[OFF+34]), "+f"(d[OFF+35]), "+f"(d[OFF+36]), "+f"(d[OFF+37]), "+f"(d[OFF+38]), "+f"(d[OFF+39]),
      "+f"(d[OFF+40]), "+f"(d[OFF+41]), "+f"(d[OFF+42]), "+f"(d[OFF+43]), "+f"(d[OFF+44]), "+f"(d[OFF+45]), "+f"(d[OFF+46]), "+f"(d[OFF+47]),
      "+f"(d[OFF+48]), "+f"(d[OFF+49]), "+f"(d[OFF+50]), "+f"(d[OFF+51]), "+f"(d[OFF+52]), "+f"(d[OFF+53]), "+f"(d[OFF+54]), "+f"(d[OFF+55]),
      "+f"(d[OFF+56]), "+f"(d[OFF+57]), "+f"(d[OFF+58]), "+f"(d[OFF+59]), "+f"(d[OFF+60]), "+f"(d[OFF+61]), "+f"(d[OFF+62]), "+f"(d[OFF+63])
    : "r"(a0), "r"(a1), "r"(a2), "r"(a3), "l"(db), "r"(scale_d), "n"(TB));
}

struct Ptrs { const __nv_bfloat16 *x, *wqkv, *wo, *wr, *wg, *wu, *wd; __nv_bfloat16* out; };

__global__ void __cluster_dims__(2, 1, 1) __launch_bounds__(384, 1) fused_kernel(const __grid_constant__ CUtensorMap tmX, const __grid_constant__ CUtensorMap tmW,
                                                       const __grid_constant__ CUtensorMap tmO, const __grid_constant__ CUtensorMap tmG,
                                                       const __grid_constant__ CUtensorMap tmU, const __grid_constant__ CUtensorMap tmD,
                                                       const __grid_constant__ CUtensorMap tmR,
                                                       const Ptrs P) {
  extern __shared__ __align__(1024) uint8_t smem_raw[];
  const int tid = threadIdx.x, wid = __shfl_sync(~0u, tid >> 5, 0), wg = wid >> 2, lane = tid & 31;
#define MAPV 1
  const int pj = blockIdx.x >> 1, pi = pj - 36;
  const int gi = pj < 4 ? 0 : pj < 36 ? (pj - 4) & 7 : 1 + pi % 7, gk = pj < 4 ? 4 + pj : pj < 36 ? (pj - 4) >> 3 : 4 + pi / 7;
  const int b = MAPV == 0 ? blockIdx.x : MAPV == 1 ? gk * 16 + gi * 2 + (blockIdx.x & 1) : MAPV == 2 ? gi * 16 + gk * 2 + (blockIdx.x & 1)
              : ((gi >> 2) * 4 + (gk & 3)) * 16 + ((gi & 3) + (gk & 4)) * 2 + (blockIdx.x & 1);
  const int rb = b >> 4, cg = b & 15, hf = cg >> 3, c3 = cg & 7;
  const int jp = cg >> 1;
  const int fidx = jp == rb ? -1 : b - 2 * rb - (jp > rb ? 2 : 0);
  const uint32_t rank = b & 1, own = rank << 24, peer = own ^ (1u << 24);
  const uint32_t sm = own + sb, mb = own + bars;
  auto chunk_of = [&](int p) { const int q = p >> 1; return q == 0 ? cg ^ p : ((q < 5 ? ((jp & 4) ^ 4) + q - 1 : jp ^ (q - 4)) << 1) + (p & 1); };
  TS_DECL; TS(0); TSG(30);
  if (wid == 8) {
    if (elect_one()) {
      if (smem_u32(smem_raw) != sm) asm volatile("trap;");
#pragma unroll
      for (int s = 0; s < 4; s++) mbar_init(mb + B_FULL + 8 * s, 1);
      asm volatile("fence.mbarrier_init.release.cluster;" ::: "memory");
      fence_async_smem();
      mbar_expect_tx(mb + B_FULL, STAGE_B);
      tma_3d(sm + woff(0), &tmW, cg * 64, 0, 0, mb + B_FULL, EFW);
      tma_2d(sm, &tmX, 0, rb * 256, mb + B_FULL, EFX);
      tma_2d(sm + 16384, &tmX, 0, rb * 256 + 128, mb + B_FULL, EFX);
#pragma unroll
      for (int kb = 1; kb < 4; kb++) {
        mbar_expect_tx(mb + B_FULL + 8 * kb, STAGE_B);
        tma_3d(sm + woff(kb), &tmW, cg * 64, kb * 64, 0, mb + B_FULL + 8 * kb, EFW);
      }
    }
  } else if (wid == 9) {
    if (elect_one()) {
#pragma unroll
      for (int i = 4; i < 32; i++)
        if (i != 27) mbar_init(mb + 8 * i, i < 8 ? 8 : i == 8 ? 64 : i == 9 ? 4 : i == 10 ? 16 : i == 26 ? 2 : 1);
      asm volatile("fence.mbarrier_init.release.cluster;" ::: "memory");
      fence_async_smem();
    }
  } else if (wid == 11) {
#pragma unroll
    for (int i = 0; i < 4; i++) sts4(sm + OFF_STATS + i * 512 + lane * 16, SENT, SENT, SENT, SENT);
    fence_async_smem();
  }
  __syncthreads();
  asm volatile("barrier.cluster.arrive.relaxed.aligned;\nbarrier.cluster.wait.aligned;" ::: "memory");

  if (wg == 2) {
    asm volatile("setmaxnreg.dec.sync.aligned.u32 56;");
    auto wait_e = [&](int p) { mbar_wait(sm + OFF_EBAR + (p >> 3) * 1024 + (p & 7) * 8, 0); };
    auto load_b = [&](int p, int slot) {
      mbar_expect_tx(mb + B_FULL3 + 8 * p, (p & ~2) ? 2 * SLOT_B : SLOT_B);
      tma_3d(sm + slot * SLOT_B, &tmO, 0, chunk_of(p) * 64, c3 * 2, mb + B_FULL3 + 8 * p, false);
    };
    auto load_f = [&](int f, int slot) {
      if (f < 8) {
        tma_2d(sm + slot * SLOT_B, &tmG, fidx * 32, f * 128, mb + B_FFN, EFF);
        tma_2d(sm + slot * SLOT_B + 8192, &tmU, fidx * 32, f * 128, mb + B_FFN, EFF);
      } else tma_3d(sm + slot * SLOT_B, &tmD, 0, fidx * 32, (f - 8) * 4, mb + B_FFN + 8, EFF);
    };
    if (wid == 8) {
      if (elect_one()) {
#pragma unroll
        for (int kb = 1; kb < 4; kb++) tma_2d_mc(sm + xoff(kb) + rank * 16384, &tmX, kb * 64, rb * 256 + rank * 128, mb + B_FULL + 8 * kb, EFX);
#pragma unroll 1
        for (int kb = 4; kb < 16; kb++) {
          const uint32_t fb = mb + B_FULL + 8 * (kb & 3);
          mbar_wait(fb + B_EMPTY, ((kb >> 2) & 1) ^ 1);
          mbar_expect_tx(fb, STAGE_B);
          tma_2d_mc(sm + xoff(kb & 3) + rank * 16384, &tmX, kb * 64, rb * 256 + rank * 128, fb, EFX);
          tma_3d(sm + woff(kb & 3), &tmW, cg * 64, kb * 64, 0, fb, EFW);
          if (kb >= 16 - NDIR) asm volatile("mbarrier.arrive.shared::cta.b64 _, [%0], 4;" :: "r"(fb + B_EMPTY) : "memory");
        }
        if (fidx >= 0) { mbar_expect_tx(mb + B_FFN, 131072); mbar_expect_tx(mb + B_FFN + 8, 65536); }
#pragma unroll 1
        for (int p = 0; p < 10; p++) {
          if (p == 0 || p == 3 || p == 7 || p == 8) mbar_wait(mb + B_EMPTY + 8 * ((p + 1) / 3), 1);
          load_b(p, p);
        }
        mbar_wait(mb + B_EV0, 0);
#pragma unroll
        for (int p = 0; p < 16; p++) mbar_init(sm + OFF_EBAR + (p >> 3) * 1024 + (p & 7) * 8, (p == 3 || p == 6) ? 17 : 16);
        asm volatile("fence.mbarrier_init.release.cluster;" ::: "memory");
        mbar_arrive(mb + B_FULL + 16);
        mbar_expect_tx(mb + B_FULL, 32768);
        tma_3d(sm + 10 * SLOT_B, &tmR, 0, (rb * 4 + hf) * 64, c3 * 2, mb + B_FULL, true);
        tma_3d(sm + 12 * SLOT_B, &tmR, 0, (rb * 4 + 2 + hf) * 64, c3 * 2, mb + B_FULL, true);
      }
      __syncwarp();
      const uint4* src = &g_obuf[(rb * 4 + rank * 2 + hf) * 64 * 128];
      mbar_wait(mb + B_EV1, 0);
      { const long long t0 = clock64(); while (clock64() - t0 < ADELAY) {} }
      {
        const uint32_t* probe = &src[chunk_of(3 + ((lane >> 2) & 3)) * 512 + 384 + (lane & 3) * 32 + 31].w;
        uint32_t v = ld_rlx(probe);
#pragma unroll
        for (int p = 3; p < 7; p++) {
          if (p == 4) wait_e(0);
          for (int it = 0; __ballot_sync(~0u, v == SENT) & (15 << (4 * (p - 3))); it++) { v = ld_rlx(probe); SPINCHK(it, 10); }
          bulk_load_mc(sm + (10 + (p & 3)) * SLOT_B + rank * 8192, src + chunk_of(p) * 512, 8192, mb + B_FULL3 + 8 * p);
        }
      }
      PTS(6);
#pragma unroll 1
      for (int p = 7; p < 16; p++) {
        const uint4* q = src + chunk_of(p) * 512;
        wait_e(p - 4);
        bulk_load_mc(sm + (10 + (p & 3)) * SLOT_B + rank * 8192, q, 8192, mb + B_FULL3 + 8 * p);
      }
      PTS(15);
      if (fidx >= 0 && elect_one()) {
#pragma unroll 1
        for (int i = 0; i < 4; i++) { wait_e(12 + i); load_f(5 + 2 * i, 10 + i); }
      }
    } else {
      const int r4 = lane >> 3, c8 = lane & 7;
      const uint32_t eb = (lane << 24) + bars + B_EMPTY;
      auto tagged = [](float v, uint32_t tag) { return ((__float_as_uint(v) + 128) & ~255u) | tag; };
      auto gather = [&](uint32_t tag) {
        const int L = tid - 288, q = (L >> 5) * 24 + min(lane, 23);
        const uint4* cp = &g_csp[cg * 8 * 48 + q];
        const uint4* sp = &g_st1[rb * 128 + L];
        uint4 v[10];
        mbar_wait(mb + B_FULL + 8 * (GPACE & 3), (GPACE >> 2) & 1);
#pragma unroll 1
        for (int it = 0;; it++) {
#pragma unroll
          for (int i = 0; i < 8; i++) v[i] = ld_rlx4(cp + i * 48);
          v[8] = ld_rlx4(sp); v[9] = ld_rlx4(sp + 64);
          uint32_t x = 0;
#pragma unroll
          for (int i = 0; i < 10; i++) { v[i].x ^= tag; v[i].y ^= tag; v[i].z ^= tag; v[i].w ^= tag; x |= v[i].x | v[i].y | v[i].z | v[i].w; }
          if (!__any_sync(~0u, (x & 255) != 0)) break;
          SPINCHK(it, 3);
        }
        sts4(sm + OFF_STATS + L * 16, v[8].x, v[8].y, v[8].z, v[8].w);
        sts4(sm + OFF_STATS + 1024 + L * 16, v[9].x, v[9].y, v[9].z, v[9].w);
        float c[4] = {0.f, 0.f, 0.f, 0.f};
#pragma unroll
        for (int i = 0; i < 8; i++) { c[0] += __uint_as_float(v[i].x); c[1] += __uint_as_float(v[i].y); c[2] += __uint_as_float(v[i].z); c[3] += __uint_as_float(v[i].w); }
        sts4(sm + OFF_COLSUM + q * 16, __float_as_uint(c[0]), __float_as_uint(c[1]), __float_as_uint(c[2]), __float_as_uint(c[3]));
        mbar_arrive(mb + B_AUX);
      };
      if (wid == 9) {
        float a[12];
#pragma unroll
        for (int i = 0; i < 12; i++) a[i] = 0.f;
        const int r2 = lane >> 4, c16 = lane & 15;
        const uint32_t a0 = sm + rb * 1024 + r2 * 128 + (((c16 >> 1) ^ r2) << 4) + (c16 & 1) * 8;
        const uint2* gw = (const uint2*)(P.wqkv + ((16 - NDIR) * 64 + rb * 8 + r2) * 3072 + cg * 64) + c16;
#pragma unroll 1
        for (int it = 0; it < 16; it++) {
          uint2 w[12];
          const int kb = it - __popc(DMASK & ((1 << it) - 1));
          const bool direct = (DMASK >> it) & 1;
          if (it == 1) {
#pragma unroll
            for (int i = 0; i < NDIR; i++) if (lane < 24) l2_prefetch(P.wqkv + ((16 - NDIR + i) * 64 + rb * 8 + (lane & 7)) * 3072 + (lane >> 3) * 1024 + cg * 64);
          }
          if (direct) {
#pragma unroll
            for (int i = 0; i < 12; i++) w[i] = ld_rlx2(gw + (i >> 2) * 256 + (i & 3) * 1536);
            gw += 64 * 768;
          } else {
            const uint32_t so = a0 + woff(kb & 3);
            mbar_wait(mb + B_FULL + 8 * (kb & 3), (kb >> 2) & 1);
            static_for<0, 12>([&](auto ic) { constexpr int i = decltype(ic)::value;
              const float2 v = lds2f_o<(i >> 2) * 8192 + (i & 3) * 256>(so ^ ((i & 3) << 5)); w[i] = make_uint2(__float_as_uint(v.x), __float_as_uint(v.y)); });
          }
#pragma unroll
          for (int i = 0; i < 12; i++) {
            float* q = a + (i >> 2) * 4;
            q[0] += bf_lo(w[i].x); q[1] += bf_hi(w[i].x); q[2] += bf_lo(w[i].y); q[3] += bf_hi(w[i].y);
          }
          __syncwarp();
          if (lane < 2 && !direct) mbar_arrive_rem(eb + 8 * (kb & 3));
        }
        float c[6];
#pragma unroll
        for (int i = 0; i < 6; i++) {
          const int o = (i >> 1) * 4 + (i & 1);
          c[i] = (r2 ? a[o + 2] : a[o]) + __shfl_xor_sync(~0u, r2 ? a[o] : a[o + 2], 16);
        }
        bar_sync(5, 96);
        TS(6);
        const uint32_t tag = lds1(mb + B_SW + 4) & 255;
#pragma unroll
        for (int sg = 0; sg < 3; sg++) st_rlx2((uint2*)&g_csp[(cg * 8 + rb) * 48] + sg * 32 + c16 * 2 + r2, tagged(c[sg * 2], tag), tagged(c[sg * 2 + 1], tag));
        gather(tag);
        TS(2);
        {
          const uint4 sv = make_uint4(SENT, SENT, SENT, SENT);
          uint4* y = &g_ybuf[b * NFFN * 4 + lane];
#pragma unroll
          for (int i = 0; i < 14; i++) y[i * 32] = sv;
          if (lane < 16) g_st2[b * 16 + lane] = make_uint4(0, 0, 0, 0);
          g_hsel[b * 64 + lane] = sv; g_hsel[b * 64 + 32 + lane] = sv;
          if (b < 8) g_cand[b * 32 + lane] = SENT;
          fence_gpu();
          __syncwarp();
          if (lane == 0) mbar_arrive(mb + B_LATE);
        }
        TS(3);
        TS_DUMP(2);
        if (elect_one()) {
#pragma unroll 1
          for (int p = 1; p < 15; p++) {
            if (p == 1) mbar_wait(mb + B_EV1, 0);
            wait_e(p + 1);
            PTS(16 + p);
            if (p < 7) load_b(p + 9, p - 1);
            else if (fidx >= 0) load_f(p < 11 ? p - 7 : 2 * p - 18, p < 11 ? p - 1 : p - 11);
          }
        }
      } else if (wid == 10) {
        float sx[4], qx[4], piv[4];
        const uint32_t xa = sm + (cg * 16 + r4) * 128;
        mbar_wait(mb + B_FULL, 0);
#pragma unroll
        for (int i = 0; i < 4; i++) { sx[i] = 0.f; qx[i] = 0.f; piv[i] = bf_lo(lds1(xa + i * 512)); }
        const uint4* gx = (const uint4*)(P.x + (b * 16 + r4) * D_ + (16 - NDIR) * 64) + c8;
#pragma unroll 1
        for (int it = 0; it < 16; it++) {
          uint4 xv[4];
          const int kb = it - __popc(DMASK & ((1 << it) - 1));
          const bool direct = (DMASK >> it) & 1;
          if (it == 1) {
#pragma unroll
            for (int i = 0; i < NDIR; i++) if (lane < 16) l2_prefetch(P.x + (b * 16 + lane) * D_ + (16 - NDIR + i) * 64);
          }
          if (direct) {
#pragma unroll
            for (int i = 0; i < 4; i++) xv[i] = ld_cg4(gx + i * 512);
            gx += 8;
          } else {
            const uint32_t so = xa + c8 * 16 + xoff(kb & 3);
            mbar_wait(mb + B_FULL + 8 * (kb & 3), (kb >> 2) & 1);
            xv[0] = lds4_o<0>(so); xv[1] = lds4_o<512>(so); xv[2] = lds4_o<1024>(so); xv[3] = lds4_o<1536>(so);
          }
#pragma unroll
          for (int i = 0; i < 4; i++) {
            const uint32_t e[4] = {xv[i].x, xv[i].y, xv[i].z, xv[i].w};
#pragma unroll
            for (int j = 0; j < 4; j++) {
              const float d0 = bf_lo(e[j]) - piv[i], d1 = bf_hi(e[j]) - piv[i];
              sx[i] += d0 + d1; qx[i] = fmaf(d0, d0, fmaf(d1, d1, qx[i]));
            }
          }
          __syncwarp();
          if (lane < 2 && !direct) mbar_arrive_rem(eb + 8 * (kb & 3));
        }
#pragma unroll
        for (int o = 1; o < 8; o <<= 1)
#pragma unroll
          for (int i = 0; i < 4; i++) { sx[i] += __shfl_xor_sync(~0u, sx[i], o); qx[i] += __shfl_xor_sync(~0u, qx[i], o); }
        const float m = (c8 == 0 ? sx[0] : c8 == 1 ? sx[1] : c8 == 2 ? sx[2] : sx[3]) * (1.f / D_);
        const float var = fmaxf(fmaf(-m, m, (c8 == 0 ? qx[0] : c8 == 1 ? qx[1] : c8 == 2 ? qx[2] : qx[3]) * (1.f / D_)), 0.f);
        const float mean = m + (c8 == 0 ? piv[0] : c8 == 1 ? piv[1] : c8 == 2 ? piv[2] : piv[3]);
        bar_sync(5, 96);
        const uint32_t tag = lds1(mb + B_SW + 4) & 255;
        if (c8 < 4) st_rlx2((uint2*)g_st1 + b * 16 + r4 + 4 * c8, tagged(-mean, tag), tagged(rsqrtf(var + 1e-5f), tag));
        gather(tag);
        uint32_t sink = 0;
#pragma unroll 1
        for (int i = 0; i < 4; i++) {
          const __nv_bfloat16* q = P.x + ((rb * 4 + hf) * 64 + i * 16 + (lane >> 1)) * D_ + c3 * 128 + (lane & 1) * 64;
          sink ^= ld_line(q) ^ ld_line(q + 128 * D_);
        }
        const uint2 w = ld_rlx2((const uint2*)(P.wr + c3 * 128) + lane);
        if (sink == 0x9E3779B9u && tag == 256) sts1(mb + B_SW + 4, sink);
        mbar_wait(mb + B_EV1, 0);
        sts4(sm + OFF_COLSUM + lane * 16, w.x << 16, w.x & 0xFFFF0000u, w.y << 16, w.y & 0xFFFF0000u);
        __syncwarp();
        if (lane == 0) mbar_arrive(mb + B_FULL3 + 8 * 15);
#pragma unroll 1
        for (int h = 0; h < 2; h++) {
          const uint32_t* probe = &g_obuf[(rb * 4 + rank * 2 + hf) * 64 * 128 + chunk_of(min(7 + 3 * h + (lane >> 2), 9 + 6 * h)) * 512 + 384 + (lane & 3) * 32 + 31].w;
          wait_e(2 + 2 * h);
          for (int it = 0; __any_sync(~0u, ld_rlx(probe) == SENT); it++) SPINCHK(it, 11);
          if (lane == 0) mbar_arrive(sm + OFF_EBAR + 24 + 24 * h);
        }
      } else {
        mbar_wait(mb + B_FULL + 8 * PFST, 0);
        if (elect_one()) {
#pragma unroll 1
          for (int i = 0; i < 16; i++) bulk_store(&g_obuf[((rb * 4 + (i >> 2)) * 64 + cg * 4 + (i & 3)) * 128], sm + OFF_STATS, 2048);
          bulk_store(&g_kvp[(cg * 8 + rb) * 272], sm + OFF_STATS, 2048); bulk_store(&g_kvp[(cg * 8 + rb) * 272 + 128], sm + OFF_STATS, 2048);
          bulk_store(&g_kvp[(cg * 8 + rb) * 272 + 256], sm + OFF_STATS, 256);
          asm volatile("cp.async.bulk.commit_group;" ::: "memory");
          tmap_prefetch(&tmO); tmap_prefetch(&tmG); tmap_prefetch(&tmU); tmap_prefetch(&tmD); tmap_prefetch(&tmR);
        }
        __syncwarp();
        const char* pg = (const char*)P.wg + (size_t)(rank * 32 + lane) * (F_ * 2) + (fidx >> 1) * 128;
        const char* pu = (const char*)P.wu + (size_t)(rank * 32 + lane) * (F_ * 2) + (fidx >> 1) * 128;
        const char* pd = (const char*)P.wd + (size_t)fidx * 65536 + lane * 128;
        uint32_t sink = 0;
        auto line = [&](int r, int h) { return r < 8 ? ((h & 1) ? pu : pg) + (size_t)(2 * r + (h >> 1)) * (64 * F_ * 2) : pd + (4 * r + h - 32) * 4096; };
#pragma unroll 1
        for (int r = -PFA; r < 12; r++) {
          uint32_t v[4] = {0, 0, 0, 0};
          if (r == 0) mbar_wait(mb + B_FULL + 8 * (PULL0 & 3), (PULL0 >> 2) & 1);
          if (fidx >= 0) {
            if (r >= 0 && r < NPULL) {
#pragma unroll
              for (int h = 0; h < 4; h++) v[h] = ld_line(line(r, h));
            }
            if (!NOPF && r + PFA < 12) {
#pragma unroll
              for (int h = 0; h < 4; h++) l2_prefetch(line(r + PFA, h));
            }
          }
          if (r == -1) {
            const uint32_t ep = ld_rlx(&g_epoch);
            float s = 0.f;
#pragma unroll
            for (int i = 0; i < 4; i++) {
              const uint4 v = ld_cg4((const uint4*)P.wr + lane + i * 32);
              s += (bf_lo(v.x) + bf_hi(v.x)) + (bf_lo(v.y) + bf_hi(v.y)) + (bf_lo(v.z) + bf_hi(v.z)) + (bf_lo(v.w) + bf_hi(v.w));
            }
#pragma unroll
            for (int o = 16; o; o >>= 1) s += __shfl_xor_sync(~0u, s, o);
            if (lane == 0) sts2f(mb + B_SW, s, __uint_as_float(ep + 1));
            asm volatile("cp.async.bulk.wait_group 0;\nfence.proxy.async;" ::: "memory");
            fence_gpu(); bar_arrive(5, 96); PTS(0);
          }
          if (r >= 3 && r < 7) l2_prefetch((const char*)P.wo + (size_t)b * 16384 + (r - 3) * 4096 + lane * 128);
          sink ^= v[0] ^ v[1] ^ v[2] ^ v[3];
          asm volatile("" : "+r"(sink));
        }
        PTS(1);
        if (sink == 0x9E3779B9u && P.out == nullptr) sts1(mb + B_SW + 4, sink);
      }
    }
    __syncwarp();
    mbar_wait(mb + B_OUT, 0);
    const float2 cf = lds2f(sm + OFF_STATS + 64);
    const int cand0 = 2047 - (__float_as_int(cf.x) & 2047), cand1 = 2047 - (__float_as_int(cf.y) & 2047), rr = lane >> 4;
    auto store_rows = [&](int tr, bool on) {
      const uint4 v = lds4(sm + 4 * SLOT_B + tr * 256 + (((lane & 15) ^ (tr & 7)) << 4));
      const float2 pr = lds2f(sm + OFF_LNP + (tr + (tr & 64)) * 8);
      const float f = 1.f + pr.x, n = pr.y;
      if (on) *(uint4*)(P.out + (size_t)(rb * 256 + hf * 64 + tr + (tr & 64)) * D_ + c3 * 128 + (lane & 15) * 8) =
          make_uint4(pack2(fmaf(bf_lo(v.x), f, n), fmaf(bf_hi(v.x), f, n)), pack2(fmaf(bf_lo(v.y), f, n), fmaf(bf_hi(v.y), f, n)),
                     pack2(fmaf(bf_lo(v.z), f, n), fmaf(bf_hi(v.z), f, n)), pack2(fmaf(bf_lo(v.w), f, n), fmaf(bf_hi(v.w), f, n)));
    };
    if (wid == 8) {
      { const long long t0 = clock64(); while (clock64() - t0 < CDELAY) {} }
      uint32_t k;
      for (int it = 0;; it++) { k = ld_rlx(&g_cand[c3 * 32 + lane]); if (!__any_sync(~0u, k == SENT)) break; SPINCHK(it, 12); }
      const uint32_t m1 = __reduce_max_sync(~0u, k), m2 = __reduce_max_sync(~0u, k == m1 ? 0 : k);
      if (k == m1 || k == m2) sts2f(sm + OFF_STATS + 80 + (k == m2) * 8, __uint_as_float(k), __int_as_float(lane));
      __syncwarp();
      if (lane == 0) { mbar_arrive(mb + B_SEL); PTS(16); }
      const uint32_t kc = __float_as_uint(rr ? cf.y : cf.x);
      const int c = rr ? cand1 : cand0;
      store_rows(((c >> 1) & 64) + (c & 63), kc != m1 && kc != m2);
    } else if (wid < 9 + NOUTW) {
#pragma unroll 2
      for (int tr = (wid - 9) * 2 + rr; tr < 128; tr += 2 * NOUTW) {
        const int row = rb * 256 + hf * 64 + tr + (tr & 64);
        store_rows(tr, row != cand0 && row != cand1);
      }
      if (wid == 9 && lane == 0) PTS(31);
    }
  } else {
    asm volatile("setmaxnreg.inc.sync.aligned.u32 224;");
    const int t128 = tid & 127, warp = wid & 3, g = lane >> 2, t = lane & 3;
    const int mb3 = rb * 4 + wg * 2 + hf;
    const int row0 = mb3 * 64 + warp * 16 + g;
    uint32_t pq[2][16];
    {
      float acc0[96], acc1[96];
#pragma unroll
      for (int i = 0; i < 96; i++) { acc0[i] = 0.f; acc1[i] = 0.f; }
      const uint32_t xo0 = dlo(sb, 16) + (wg * 2 + hf) * 512, xo1 = dlo(sb, 16) + (wg * 2 + (hf ^ 1)) * 512;
      const int nwait = wg ? 16 : KLEAD;
      const uint32_t eb0 = (t128 << 24) + bars + B_EMPTY;
#pragma unroll 1
      for (int kb = 0; kb < 16; kb++) {
        const int s = kb & 3;
        if (kb < nwait) mbar_wait(mb + B_FULL + 8 * s, (kb >> 2) & 1);
        if (kb == 0) TS(1);
        const uint32_t xs = xoff(s) >> 4, ws = dlo(sb, 8192) + (woff(s) >> 4);
        pin(acc0); pin(acc1);
        wg_fence();
#pragma unroll
        for (int k = 0; k < 4; k++) {
          const uint64_t db = dsc<1024, 1>(ws + k * 128);
          wgmma_n192_ss<0, 1, 0>(acc0, dsc<1024, 1>(xs + xo0 + k * 2), db, 1);
          wgmma_n192_ss<0, 1, 0>(acc1, dsc<1024, 1>(xs + xo1 + k * 2), db, 1);
        }
        wg_commit();
        wg_wait<1>();
        pin(acc0); pin(acc1);
        if (kb > 0 && t128 < 2 && kb != nwait) mbar_arrive_rem(eb0 + 8 * ((kb - 1) & 3));
        if (kb == nwait - 1) {
          if (wg) bar_arrive(6, 256);
          else {
            wg_wait<0>();
            pin(acc0); pin(acc1);
            if (t128 < 2) mbar_arrive_rem(eb0 + 8 * s);
#pragma unroll
            for (int k2 = KLEAD; k2 < 16; k2++) mbar_wait(mb + B_FULL + 8 * (k2 & 3), 1);
            bar_sync(6, 256);
          }
        }
      }
      mbar_wait(mb + B_AUX, 0);
      float rs[2][2], nm[2][2];
#pragma unroll
      for (int m = 0; m < 2; m++)
#pragma unroll
        for (int h = 0; h < 2; h++) { const float2 v = lds2f(sm + OFF_STATS + ((wg * 2 + (m ^ hf)) * 64 + warp * 16 + h * 8 + g) * 8); nm[m][h] = v.x; rs[m][h] = v.y; }
      if (!wg) bar_arrive(7, 256);
      wg_wait<0>();
      pin(acc0); pin(acc1);
      if (t128 < 2) mbar_arrive_rem((t128 << 24) + bars + B_EMPTY + 24);
      TS(2);
      auto center = [&](auto jc) {
        constexpr int j = decltype(jc)::value;
        const float2 cs = lds2f_o<sb + OFF_COLSUM + j * 32>(own + t * 8);
        acc0[j * 4] = fmaf(nm[0][0], cs.x, acc0[j * 4]); acc0[j * 4 + 1] = fmaf(nm[0][0], cs.y, acc0[j * 4 + 1]);
        acc0[j * 4 + 2] = fmaf(nm[0][1], cs.x, acc0[j * 4 + 2]); acc0[j * 4 + 3] = fmaf(nm[0][1], cs.y, acc0[j * 4 + 3]);
        acc1[j * 4] = fmaf(nm[1][0], cs.x, acc1[j * 4]); acc1[j * 4 + 1] = fmaf(nm[1][0], cs.y, acc1[j * 4 + 1]);
        acc1[j * 4 + 2] = fmaf(nm[1][1], cs.x, acc1[j * 4 + 2]); acc1[j * 4 + 3] = fmaf(nm[1][1], cs.y, acc1[j * 4 + 3]);
      };
      static_for<16, 20>(center);
      bar_sync(2 + wg, 128);
      const uint32_t srow = sm + (10 + wg) * SLOT_B + (warp * 16 + (lane & 15)) * 128;
      const float L2E = 1.4426950408889634f;
      uint32_t sad[4];
#pragma unroll
      for (int j = 0; j < 4; j++) sad[j] = srow + (((2 * j + (lane >> 4)) ^ (lane & 7)) << 4);
#pragma unroll
      for (int j = 0; j < 4; j++) {
        const int v = 64 + j * 8;
        if (j == 2) { static_for<20, 24>(center); static_for<8, 16>(center); }
        stsm4_o<8192>(sad[j], pack2(acc0[v] * rs[0][0], acc0[v + 1] * rs[0][0]), pack2(acc0[v + 2] * rs[0][1], acc0[v + 3] * rs[0][1]),
                              pack2(acc0[v + 4] * rs[0][0], acc0[v + 5] * rs[0][0]), pack2(acc0[v + 6] * rs[0][1], acc0[v + 7] * rs[0][1]));
        stsm4_o<2 * SLOT_B + 8192>(sad[j], pack2(acc1[v] * rs[1][0], acc1[v + 1] * rs[1][0]), pack2(acc1[v + 2] * rs[1][1], acc1[v + 3] * rs[1][1]),
                                       pack2(acc1[v + 4] * rs[1][0], acc1[v + 5] * rs[1][0]), pack2(acc1[v + 6] * rs[1][1], acc1[v + 7] * rs[1][1]));
      }
      {
        const float rl00 = rs[0][0] * L2E, rl01 = rs[0][1] * L2E, rl10 = rs[1][0] * L2E, rl11 = rs[1][1] * L2E;
#pragma unroll
        for (int j = 0; j < 4; j++) {
          const int o = 32 + j * 8;
          stsm4_o<0>(sad[j], pack2(phi(acc0[o], rs[0][0], rl00), phi(acc0[o + 1], rs[0][0], rl00)), pack2(phi(acc0[o + 2], rs[0][1], rl01), phi(acc0[o + 3], rs[0][1], rl01)),
                             pack2(phi(acc0[o + 4], rs[0][0], rl00), phi(acc0[o + 5], rs[0][0], rl00)), pack2(phi(acc0[o + 6], rs[0][1], rl01), phi(acc0[o + 7], rs[0][1], rl01)));
          stsm4_o<2 * SLOT_B>(sad[j], pack2(phi(acc1[o], rs[1][0], rl10), phi(acc1[o + 1], rs[1][0], rl10)), pack2(phi(acc1[o + 2], rs[1][1], rl11), phi(acc1[o + 3], rs[1][1], rl11)),
                                  pack2(phi(acc1[o + 4], rs[1][0], rl10), phi(acc1[o + 5], rs[1][0], rl10)), pack2(phi(acc1[o + 6], rs[1][1], rl11), phi(acc1[o + 7], rs[1][1], rl11)));
        }
      }
      if (wg) {
        bar_sync(7, 256);
        if (t128 < 16) sts4(sm + OFF_STATS + t128 * 128 + ((t128 & 7) << 4), 0x3F803F80u, 0x3F803F80u, 0x3F803F80u, 0x3F803F80u);
      }
      fence_async_smem();
      if (wg) bar_sync(3, 128); else bar_sync(4, 256);
      TS(3);
      float ka[36];
#pragma unroll
      for (int i = 0; i < 36; i++) ka[i] = 0.f;
      pin(ka);
      wg_fence();
#pragma unroll
      for (int i = 0; i < 8; i++) {
        const uint32_t o = sb + 10 * SLOT_B + (i >> 2) * 2 * SLOT_B + (i & 3) * 2048;
        wgmma_n72_ss<1, 1, 0>(ka, dsc<1024, 1>(dlo(o, 8192) + wg * 1024), dsc<1024, 1>(dlo(o + 8192, sb + OFF_STATS - o - 8192) + wg * (1024u - (1024u << 16))), 1);
      }
      wg_commit();
      wg_wait<0>();
      pin(ka);
      if (t128 < 2) mbar_arrive_rem((t128 << 24) + bars + B_EV0);
      TS(4);
      float kvv[16];
#pragma unroll
      for (int i = 0; i < 16; i++) kvv[i] = (warp >> 1) ? ka[16 + i] : ka[i];
      const uint32_t xch = sm + 13 * SLOT_B + t128 * 16;
      const int d0 = warp * 16 + g, d1 = d0 + 8;
      const uint32_t za0 = sm + OFF_STATS + (d0 >> 2) * 128 + ((((d0 >> 2) + 1) & 7) << 4) + (d0 & 3) * 4;
      const uint32_t za1 = sm + OFF_STATS + (d1 >> 2) * 128 + ((((d1 >> 2) + 1) & 7) << 4) + (d1 & 3) * 4;
      if (wg == 1) {
#pragma unroll
        for (int q = 0; q < 4; q++) sts4(xch + q * 2048, __float_as_uint(kvv[q * 4]), __float_as_uint(kvv[q * 4 + 1]), __float_as_uint(kvv[q * 4 + 2]), __float_as_uint(kvv[q * 4 + 3]));
        if (t == 0) { sts1(za0, __float_as_uint(ka[32])); sts1(za1, __float_as_uint(ka[34])); }
        bar_arrive(4, 256);
      } else {
        mbar_wait(mb + B_LATE, 0);
#pragma unroll
        for (int q = 0; q < 4; q++) {
          const uint4 v = lds4(xch + q * 2048);
          kvv[q * 4] += __uint_as_float(v.x); kvv[q * 4 + 1] += __uint_as_float(v.y); kvv[q * 4 + 2] += __uint_as_float(v.z); kvv[q * 4 + 3] += __uint_as_float(v.w);
        }
        uint4* dst = &g_kvp[(cg * 8 + rb) * 272];
        st_rlx4(dst + warp * 64 + lane, make_uint4(pack2(kvv[0], kvv[1]), pack2(kvv[4], kvv[5]), pack2(kvv[8], kvv[9]), pack2(kvv[12], kvv[13])));
        st_rlx4(dst + warp * 64 + 32 + lane, make_uint4(pack2(kvv[2], kvv[3]), pack2(kvv[6], kvv[7]), pack2(kvv[10], kvv[11]), pack2(kvv[14], kvv[15])));
        if (t == 0) {
          st_rlx((uint32_t*)(dst + 256) + d0, __float_as_uint(ka[32] + __uint_as_float(lds1(za0))));
          st_rlx((uint32_t*)(dst + 256) + d1, __float_as_uint(ka[34] + __uint_as_float(lds1(za1))));
        }
      }
      if (QHOLD) { if (wg) bar_sync(8, 256); else bar_arrive(8, 256); }
      TS(5);
      auto q_epi = [&](float (&a)[96], const float r0, const float r1, uint32_t (&o)[16]) {
        const float rl0 = r0 * L2E, rl1 = r1 * L2E;
#pragma unroll
        for (int j = 0; j < 8; j++) {
          const int c = j * 4;
          o[j * 2] = pack2(phi(a[c], r0, rl0), phi(a[c + 1], r0, rl0));
          o[j * 2 + 1] = pack2(phi(a[c + 2], r1, rl1), phi(a[c + 3], r1, rl1));
        }
      };
      static_for<0, 8>(center);
      q_epi(acc0, rs[0][0], rs[0][1], pq[0]);
      q_epi(acc1, rs[1][0], rs[1][1], pq[1]);
#pragma unroll
      for (int i = 0; i < 16; i++) asm volatile("" : "+r"(pq[0][i]), "+r"(pq[1][i]) :: "memory");
    }
    TS(6);
    {
      uint4 v[8]; uint2 z;
      uint32_t dep = 0;
#pragma unroll
      for (int i = 0; i < 16; i++) dep = __vimax3_u32(dep, pq[0][i], pq[1][i]);
      asm volatile("bar.sync 1, %0;" :: "r"(dep == SENT ? 0 : 256) : "memory");
      const uint4* src = &g_kvp[cg * 8 * 272];
#pragma unroll
      for (int s = 0; s < 8; s++) v[s] = ld_rlx4(src + s * 272 + tid);
      z = ld_rlx2((const uint2*)(src + g * 272 + 256) + wid * 4 + t);
#pragma unroll 1
      for (int it = 0;; it++) {
        uint32_t m[8], mm = max(z.x, z.y);
#pragma unroll
        for (int s = 0; s < 8; s++) m[s] = max4(0, v[s]);
#pragma unroll
        for (int s = 0; s < 8; s += 2) mm = __vimax3_u32(mm, m[s], m[s + 1]);
        TSV(20, it + 1);
        if (!__any_sync(~0u, mm == SENT)) break;
        SPINCHK(it, 4);
#pragma unroll
        for (int s = 0; s < 8; s++) if (m[s] == SENT) v[s] = ld_rlx4(src + s * 272 + tid);
        z = ld_rlx2((const uint2*)(src + g * 272 + 256) + wid * 4 + t);
      }
      TS(23);
      float a[8], z0 = __uint_as_float(z.x), z1 = __uint_as_float(z.y);
#pragma unroll
      for (int o = 4; o < 32; o <<= 1) { z0 += __shfl_xor_sync(~0u, z0, o); z1 += __shfl_xor_sync(~0u, z1, o); }
#pragma unroll
      for (int i = 0; i < 8; i++) a[i] = 0.f;
#pragma unroll
      for (int s = 0; s < 8; s++) {
        a[0] += bf_lo(v[s].x); a[1] += bf_hi(v[s].x); a[2] += bf_lo(v[s].y); a[3] += bf_hi(v[s].y);
        a[4] += bf_lo(v[s].z); a[5] += bf_hi(v[s].z); a[6] += bf_lo(v[s].w); a[7] += bf_hi(v[s].w);
      }
      const uint32_t kb0 = sm + OFF_KVB + wid * 1024;
      stsm4(kb0 + (lane & 7) * 128 + (((lane >> 3) ^ (lane & 7)) << 4), pack2(a[0], a[1]), pack2(a[2], a[3]), pack2(a[4], a[5]), pack2(a[6], a[7]));
      if (lane < 8) {
        const int r = t * 2 + g;
        const float zs = g ? z1 : z0;
        const uint32_t zz = pack2(zs, zs);
        sts4(kb0 + r * 128 + ((4 ^ r) << 4), zz, zz, zz, zz);
      }
      fence_async_smem();
      bar_sync(1, 256);
    }
    TS(7);
    uint4 abuf[2][4], ost[2][4];
    uint4* const od0 = &g_obuf[(mb3 * 64 + cg * 4) * 128 + t128];
    uint4* const od1 = &g_obuf[((mb3 ^ 1) * 64 + cg * 4) * 128 + t128];
    {
      float oa[4][20];
#pragma unroll
      for (int i = 0; i < 4; i++)
#pragma unroll
        for (int j = 0; j < 20; j++) oa[i][j] = 0.f;
#pragma unroll
      for (int i = 0; i < 4; i++) pin(oa[i]);
      wg_fence();
#pragma unroll
      for (int m = 1; m >= 0; m--) {
#pragma unroll
        for (int ks = 0; ks < 4; ks++)
          wgmma_n40_rs<1, 0>(oa[m * 2 + (ks >> 1)], pq[m][ks * 4], pq[m][ks * 4 + 1], pq[m][ks * 4 + 2], pq[m][ks * 4 + 3], dsc<1024, 1>(dlo(sb + OFF_KVB + ks * 2048, 8192)), 1);
      }
      wg_commit();
      wg_wait<0>();
#pragma unroll
      for (int i = 0; i < 4; i++) pin(oa[i]);
      if (lane < 2) mbar_arrive_rem((lane << 24) + bars + B_EV1);
      mbar_wait(mb + B_FULL + 16, 0);
#pragma unroll
      for (int m = 1; m >= 0; m--) {
#pragma unroll
        for (int h = 0; h < 2; h++) {
          const float (&d)[20] = oa[m * 2 + h];
          const float i0 = rcp(d[16] + 1e-6f), i1 = rcp(d[18] + 1e-6f);
#pragma unroll
          for (int k2 = 0; k2 < 2; k2++) {
            const uint4 v = make_uint4(pack2(d[k2 * 8] * i0, d[k2 * 8 + 1] * i0), pack2(d[k2 * 8 + 2] * i1, d[k2 * 8 + 3] * i1),
                                       pack2(d[k2 * 8 + 4] * i0, d[k2 * 8 + 5] * i0), pack2(d[k2 * 8 + 6] * i1, d[k2 * 8 + 7] * i1));
            ost[m][h * 2 + k2] = v;
            if (m == 1) { if (!(jp & 2)) st_rlx4(od1 + (h * 2 + k2) * 128, v); }
            else {
              abuf[0][h * 2 + k2] = v; abuf[1][h * 2 + k2] = v;
              st_async4(peer + sb + 11 * SLOT_B + wg * 8192 + (h * 2 + k2) * 2048 + t128 * 16, v, peer + bars + B_FULL3 + 8);
            }
          }
        }
      }
    }
    TS(8);
    float acc[64];
#pragma unroll
    for (int i = 0; i < 64; i++) acc[i] = 0.f;
    {
      const uint32_t la = own + wg * 8192 + t128 * 16, eb = (lane << 24) + sb + OFF_EBAR;
      auto fetch = [&](int p, uint4 (&a)[4]) {
        const uint32_t ra = la + (p & 3) * SLOT_B;
        a[0] = lds4_o<sb + 10 * SLOT_B>(ra); a[1] = lds4_o<sb + 10 * SLOT_B + 2048>(ra);
        a[2] = lds4_o<sb + 10 * SLOT_B + 4096>(ra); a[3] = lds4_o<sb + 10 * SLOT_B + 6144>(ra);
      };
      mbar_wait(mb + B_FULL3, 0);
#pragma unroll 1
      for (int pp = 0; pp < 16; pp += 2) {
#pragma unroll
        for (int j = 0; j < 2; j++) {
          const int p = pp + j;
          uint4 (&a)[4] = abuf[j];
          if (__any_sync(~0u, max(max4(max4(0, a[0]), a[1]), max4(max4(0, a[2]), a[3])) == SENT)) {
            int pl = p; asm volatile("" : "+r"(pl));
            const uint4* q = &g_obuf[(mb3 * 64 + chunk_of(pl) * 4) * 128 + t128];
#pragma unroll 1
            for (int it = 0;; it++) {
#pragma unroll
              for (int i = 0; i < 4; i++) a[i] = ld_rlx4(q + i * 128);
              TSV(21, _ts + 1);
              if (!__any_sync(~0u, max(max4(max4(0, a[0]), a[1]), max4(max4(0, a[2]), a[3])) == SENT)) break;
              SPINCHK(it, 5);
            }
          }
          if (lane < 2 && (j == 1 || p > 0)) mbar_arrive_rem(eb + (p >> 3) * 1024 + (p & 7) * 8);
          const bool early = j == 0 ? pp > 2 : (pp > 0 && pp < 14);
          if (early) mbar_wait(mb + B_FULL3 + 8 * (p + 1), 0);
          wg_wait<0>();
          pin(acc);
#pragma unroll
          for (int i = 0; i < 4; i++) pin4(abuf[j ^ 1][i]);
          if (early) fetch(p + 1, abuf[j ^ 1]);
          if (p == 2) TS(9);
          const uint32_t bs = dlo(sb, 8192) + (p < 10 ? p : p - 10) * (SLOT_B >> 4);
          wg_fence();
#pragma unroll
          for (int k = 0; k < 4; k++) wgmma_n128_rs<1, 0>(acc, a[k].x, a[k].y, a[k].z, a[k].w, dsc<1024, 1>(bs + k * 128), 1);
          wg_commit();
          if (pp < 6) {
            if (j == 0 && p == 0 && (jp & 2)) {
#pragma unroll
              for (int k = 0; k < 4; k++) st_rlx4(od1 + k * 128, ost[1][k]);
            }
            if (p == ((jp >> 1) & 1) + W0OFF) {
#pragma unroll
              for (int k = 0; k < 4; k++) st_rlx4(od0 + k * 128, ost[0][k]);
            }
            if (!early) {
              mbar_wait(mb + B_FULL3 + 8 * (p + 1), 0);
              if (j == 0) fetch(p + 1, abuf[j ^ 1]);
              else {
                abuf[0][0].x = SENT;
                mbar_wait(mb + B_FULL, 0);
                const uint32_t xa = sm + (10 + wg * 2) * SLOT_B + (warp * 16 + (lane & 15)) * 128;
                uint32_t r[8][4];
#pragma unroll
                for (int q = 0; q < 4; q++) {
                  const uint32_t ad = xa + (((2 * q + (lane >> 4)) ^ (lane & 7)) << 4);
                  ldsm4_o<0>(ad, r[q][0], r[q][1], r[q][2], r[q][3]); ldsm4_o<8192>(ad, r[4 + q][0], r[4 + q][1], r[4 + q][2], r[4 + q][3]);
                }
                wg_wait<0>();
                pin(acc);
                if (lane < 2) mbar_arrive_rem(eb);
#pragma unroll
                for (int q = 0; q < 32; q++) { acc[q * 2] += bf_lo(r[q >> 2][q & 3]); acc[q * 2 + 1] += bf_hi(r[q >> 2][q & 3]); }
                TS(28);
              }
            }
          }
        }
      }
    }
    float wf[32];
    static_for<0, 16>([&](auto jc) { constexpr int j = decltype(jc)::value; const float2 v = lds2f_o<sb + OFF_COLSUM + j * 32>(own + t * 8); wf[j * 2] = v.x; wf[j * 2 + 1] = v.y; });
    pin(wf);
    wg_wait<0>();
    pin(acc);
#pragma unroll
    for (int i = 0; i < 4; i++) pin4(abuf[1][i]);
    TS(10);
    {
      float s0 = 0.f, q0 = 0.f, e0 = 0.f, s1 = 0.f, q1 = 0.f, e1 = 0.f;
#pragma unroll
      for (int j = 0; j < 16; j++) {
        const float a = acc[j * 4], c = acc[j * 4 + 1], d = acc[j * 4 + 2], e = acc[j * 4 + 3];
        s0 += a + c; q0 = fmaf(a, a, fmaf(c, c, q0)); e0 = fmaf(a, wf[j * 2], fmaf(c, wf[j * 2 + 1], e0));
        s1 += d + e; q1 = fmaf(d, d, fmaf(e, e, q1)); e1 = fmaf(d, wf[j * 2], fmaf(e, wf[j * 2 + 1], e1));
      }
      const bool od = t & 1;
      float s = (od ? s1 : s0) + __shfl_xor_sync(~0u, od ? s0 : s1, 1);
      float q = (od ? q1 : q0) + __shfl_xor_sync(~0u, od ? q0 : q1, 1);
      float e = (od ? e1 : e0) + __shfl_xor_sync(~0u, od ? e0 : e1, 1);
      s += __shfl_xor_sync(~0u, s, 2); q += __shfl_xor_sync(~0u, q, 2); e += __shfl_xor_sync(~0u, e, 2);
      if (t < 2) red4(&g_st2[row0 + t * 8], s, q, e, 1.f);
    }
    TS(11);
    const uint32_t msc = sm + OFF_STATS;
    const uint32_t hst = sm + 4 * SLOT_B + wid * 4096, myslot = sm + ((GU_SLOTS >> (4 * wid)) & 15) * SLOT_B;
    bar_sync(1, 256);
#pragma unroll
    for (int j = 0; j < 8; j++)
      stsm4(hst + (lane & 15) * 256 + (((2 * j + (lane >> 4)) ^ (lane & 7)) << 4), pack2(acc[j * 8], acc[j * 8 + 1]), pack2(acc[j * 8 + 2], acc[j * 8 + 3]),
            pack2(acc[j * 8 + 4], acc[j * 8 + 5]), pack2(acc[j * 8 + 6], acc[j * 8 + 7]));
    uint32_t wa[8][4][4], wd[8][2][4];
    const uint32_t a0 = myslot + ((lane >> 4) * 8 + (lane & 7)) * 64 + ((((lane >> 3) & 1) ^ ((lane >> 1) & 3)) << 4);
    auto load_gu = [&](auto ic) { constexpr int i = decltype(ic)::value; ldsm4t_o<(i >> 2) * 1024 + ((i >> 1) & 1) * 8192>(a0 ^ ((i & 1) << 5), wa[i >> 2][i & 3]); };
    {
      const int row = mb3 * 64 + warp * 16 + (lane & 15);
      uint4 v;
#pragma unroll 1
      for (int it = 0;; it++) {
        v = ld_rlx4(&g_st2[row]);
        TSV(22, it + 1);
        if (!__any_sync(~0u, v.w != 0x41000000u)) break;
        SPINCHK(it, 6);
      }
      TS(12);
      const float sw = __uint_as_float(lds1(mb + B_SW));
      const float mean = __uint_as_float(v.x) * (1.f / D_);
      const float rstd = rsq(fmaxf(fmaf(-mean, mean, __uint_as_float(v.y) * (1.f / D_)), 0.f) + 1e-5f);
      const uint32_t u = __float_as_uint(rstd * fmaf(-mean, sw, __uint_as_float(v.z)));
      uint32_t k = min(((u ^ ((uint32_t)((int)u >> 31) | 0x80000000u)) & ~2047u), 0xFFFFF000u) | (2047 - row);
      uint32_t m1 = __reduce_max_sync(~0u, k), m2 = __reduce_max_sync(~0u, k == m1 ? 0 : k);
      if (lane < 16) sts2f(sm + OFF_LNP + (wg * 128 + warp * 16 + lane) * 8, rstd, -mean * rstd);
      if (lane == 0) sts2f(msc + wid * 8, __uint_as_float(m1), __uint_as_float(m2));
      bar_sync(1, 256);
      k = lds1(msc + (lane & 15) * 4);
      m1 = __reduce_max_sync(~0u, k); m2 = __reduce_max_sync(~0u, k == m1 ? 0 : k);
      const int grp = rb * 2 + hf, c0 = 2047 - (m1 & 2047), c1 = 2047 - (m2 & 2047);
      if (tid == 0) {
        st_rlx2(&g_cand[c3 * 32 + grp * 2], m1, m2);
        sts2f(msc + 64, __uint_as_float(m1), __uint_as_float(m2));
        mbar_arrive(mb + B_OUT);
      }
      if ((c0 >> 4) == mb3 * 4 + warp || (c1 >> 4) == mb3 * 4 + warp) {
        const int ra = (lane & 4) ? c1 : c0, rd = (lane & 16) ? c1 : c0;
        uint32_t h0, h1, h2, h3;
        ldsm4_o<0>(hst + (ra & 15) * 256 + ((((lane & 3) * 4 + (lane >> 3)) ^ (ra & 7)) << 4), h0, h1, h2, h3);
        const float2 pr = lds2f(sm + OFF_LNP + (wg * 128 + warp * 16 + (rd & 15)) * 8);
        if ((rd >> 4) == mb3 * 4 + warp) {
          uint4* d = &g_hsel[(grp * 2 + (lane >> 4)) * 256 + c3 * 32 + t * 4 + (g & 3)];
          st_rlx4(d, make_uint4(pack2(fmaf(bf_lo(h0), pr.x, pr.y), fmaf(bf_hi(h0), pr.x, pr.y)), pack2(fmaf(bf_lo(h1), pr.x, pr.y), fmaf(bf_hi(h1), pr.x, pr.y)),
                                pack2(fmaf(bf_lo(h2), pr.x, pr.y), fmaf(bf_hi(h2), pr.x, pr.y)), pack2(fmaf(bf_lo(h3), pr.x, pr.y), fmaf(bf_hi(h3), pr.x, pr.y))));
          st_rlx4(d + 16, make_uint4(h0, h1, h2, h3));
        }
      }
    }
    TS(13);
    if (fidx >= 0) mbar_wait(mb + B_FFN, 0);
    static_for<0, 32>(load_gu);
    const uint32_t da = sm + (2 + (wid >> 2) + (wid & 2) * 5) * SLOT_B + (wid & 1) * 8192 + ((lane >> 4) * 8 + (lane & 7)) * 128 + ((((lane >> 3) & 1) ^ (lane & 7)) << 4);
    TS(15);
    mbar_wait(mb + B_SEL, 0);
    const uint4 sel = lds4(msc + 80);
    TS(26);
    float gu[2][4][4];
    uint32_t fh = 0, fn = 0;
    const uint32_t* fq = (const uint32_t*)g_hsel + ((tid & 1) ? sel.w : sel.y) * 1024 + (b >> 4) * 128 + ((tid >> 2) & 3) * 16 + (b & 15);
    {
      uint4 xb[4];
      const uint4* xp = &g_hsel[((lane & 16) ? sel.w : sel.y) * 256 + wid * 32 + (lane & 15)];
      uint4 xv = ld_rlx4(xp);
      if (tid < 16) { fn = ld_rlx(fq); fh = ld_rlx(fq + 64); }
      if (fidx >= 0) mbar_wait(mb + B_FFN + 8, 0);
      static_for<0, 8>([&](auto ic) { constexpr int i = decltype(ic)::value; ldsm4t_o<(i & 1) * 2048>(da ^ ((i >> 1) << 5), wd[i >> 1][i & 1]); });
#pragma unroll 1
      for (int it = 0; __any_sync(~0u, max4(0, xv) == SENT); it++) { xv = ld_rlx4(xp); TSV(24, it + 1); SPINCHK(it, 7); }
      sts4(myslot + 2048 + ((lane & 3) * 8 + (lane >> 2)) * 16, xv.x, xv.y, xv.z, xv.w);
      __syncwarp();
#pragma unroll
      for (int i = 0; i < 4; i++) xb[i] = lds4(myslot + 2048 + (i * 8 + (lane & 7)) * 16);
      TS(14);
#pragma unroll
      for (int i = 0; i < 32; i++) gu[i >> 4][(i >> 2) & 3][i & 3] = 0.f;
#pragma unroll
      for (int ks = 0; ks < 8; ks++) {
#pragma unroll
        for (int i = 0; i < 4; i++) mma16816(gu[ks & 1][i], wa[ks][i], (ks & 1) ? xb[ks >> 1].z : xb[ks >> 1].x, (ks & 1) ? xb[ks >> 1].w : xb[ks >> 1].y);
        if (ks == 3) {
          uint32_t dd = da; asm volatile("" : "+r"(dd) : "f"(gu[0][0][0]));
          static_for<0, 8>([&](auto ic) { constexpr int i = decltype(ic)::value; ldsm4t_o<4096 + (i & 1) * 2048>(dd ^ ((i >> 1) << 5), wd[4 + (i >> 1)][i & 1]); });
        }
      }
    }
    {
      float o[4];
#pragma unroll
      for (int j = 0; j < 4; j++) {
        const float s0 = gu[0][0][j] + gu[1][0][j], s1 = gu[0][1][j] + gu[1][1][j], s2 = gu[0][2][j] + gu[1][2][j], s3 = gu[0][3][j] + gu[1][3][j];
        o[j] = t == 0 ? s0 : t == 1 ? s1 : t == 2 ? s2 : s3;
      }
      sts2f(myslot + 1024 + (t * 16 + g) * 8, o[0], o[1]);
      sts2f(myslot + 1024 + (t * 16 + g + 8) * 8, o[2], o[3]);
    }
    TS(25);
    bar_sync(1, 256);
    {
      float g0 = 0.f, g1 = 0.f, u0 = 0.f, u1 = 0.f;
      static_for<0, 8>([&](auto wc) { constexpr int w = decltype(wc)::value;
        const float2 a = lds2f_o<sb + ((GU_SLOTS >> (4 * w)) & 15) * SLOT_B + 1024>(own + lane * 8), c = lds2f_o<sb + ((GU_SLOTS >> (4 * w)) & 15) * SLOT_B + 1280>(own + lane * 8);
        g0 += a.x; g1 += a.y; u0 += c.x; u1 += c.y; });
      const uint32_t act = pack2(g0 * rcp(1.f + ex2(-1.4426950408889634f * g0)) * u0, g1 * rcp(1.f + ex2(-1.4426950408889634f * g1)) * u1);
      uint32_t bq[4];
#pragma unroll
      for (int i = 0; i < 4; i++) {
        const uint32_t lo = __shfl_sync(~0u, act, i * 8 + 2 * t), hi = __shfl_sync(~0u, act, i * 8 + 2 * t + 1);
        bq[i] = __byte_perm(lo, hi, (g & 1) ? 0x7632 : 0x5410);
      }
      TS(16);
      float ya[8][4];
#pragma unroll
      for (int i = 0; i < 8; i++) { ya[i][0] = 0.f; ya[i][1] = 0.f; ya[i][2] = 0.f; ya[i][3] = 0.f; }
#pragma unroll
      for (int ks = 0; ks < 2; ks++)
#pragma unroll
        for (int i = 0; i < 8; i++) mma16816(ya[i], wd[i][ks], bq[ks * 2], bq[ks * 2 + 1]);
      if (fidx >= 0) {
        uint2* yp = (uint2*)&g_ybuf[((wid * 16 + t * 2) * NFFN + fidx) * 4] + g;
#pragma unroll
        for (int h = 0; h < 2; h++) {
          float o[4];
#pragma unroll
          for (int j = 0; j < 4; j++) o[j] = t == 0 ? ya[h * 4][j] : t == 1 ? ya[h * 4 + 1][j] : t == 2 ? ya[h * 4 + 2][j] : ya[h * 4 + 3][j];
          st_rlx2(yp + h * (8 * NFFN * 8), __float_as_uint(o[0]), __float_as_uint(o[1]));
          st_rlx2(yp + h * (8 * NFFN * 8) + NFFN * 8, __float_as_uint(o[2]), __float_as_uint(o[3]));
        }
      }
    }
    TS(17);
    const long long ty = clock64();
    {
      while (clock64() - ty < YDELAY) {}
      uint4 v0, v1 = make_uint4(0, 0, 0, 0);
#pragma unroll 1
      for (int it = 0;; it++) {
        v0 = ld_rlx4(&g_ybuf[b * NFFN * 4 + tid]);
        if (tid < 192) v1 = ld_rlx4(&g_ybuf[b * NFFN * 4 + 256 + tid]);
        TSV(27, it + 1);
        if (!__any_sync(~0u, max(max4(0, v0), max4(0, v1)) == SENT)) break;
        SPINCHK(it, 8);
      }
      TS(18);
      float y0 = __uint_as_float(v0.x) + __uint_as_float(v1.x), y1 = __uint_as_float(v0.y) + __uint_as_float(v1.y);
      float y2 = __uint_as_float(v0.z) + __uint_as_float(v1.z), y3 = __uint_as_float(v0.w) + __uint_as_float(v1.w);
      float z0 = ((lane & 16) ? y2 : y0) + __shfl_xor_sync(~0u, (lane & 16) ? y0 : y2, 16), z1 = ((lane & 16) ? y3 : y1) + __shfl_xor_sync(~0u, (lane & 16) ? y1 : y3, 16);
      z0 = ((lane & 8) ? z1 : z0) + __shfl_xor_sync(~0u, (lane & 8) ? z0 : z1, 8);
      z0 += __shfl_xor_sync(~0u, z0, 4);
      const uint32_t yx = msc + 128;
      if (!(lane & 4)) sts1(yx + wid * 64 + (t * 4 + (lane >> 3)) * 4, __float_as_uint(z0));
      bar_sync(1, 256);
      if (tid < 16) {
        float y = 0.f;
#pragma unroll
        for (int w = 0; w < 8; w++) y += __uint_as_float(lds1(yx + w * 64 + tid * 4));
        for (int it = 0; max(fn, fh) == SENT; it++) { fn = ld_rlx(fq); fh = ld_rlx(fq + 64); SPINCHK(it, 9); }
        const uint32_t key = (tid & 1) ? sel.z : sel.x;
        const float r = __uint_as_float(key ^ (~(uint32_t)((int)key >> 31) | 0x80000000u));
        const float base = (tid & 2) ? bf_hi(fh) + bf_hi(fn) : bf_lo(fh) + bf_lo(fn);
        P.out[(size_t)(2047 - (key & 2047)) * D_ + b * 8 + (tid >> 1)] = __float2bfloat16(fmaf(y, rcp(1.f + ex2(-1.4426950408889634f * r)), base));
      }
      if (b == 0 && tid == 32) g_epoch = lds1(mb + B_SW + 4);
    }
    TS(19); TSG(31);
    if (warp == 0) TS_DUMP(wg);
  }
}

typedef CUresult (*EncodeFn)(CUtensorMap*, CUtensorMapDataType, cuuint32_t, void*, const cuuint64_t*, const cuuint64_t*, const cuuint32_t*,
                             const cuuint32_t*, CUtensorMapInterleave, CUtensorMapSwizzle, CUtensorMapL2promotion, CUtensorMapFloatOOBfill);
void make_map(EncodeFn enc, CUtensorMap* m, const void* p, uint64_t cols, uint64_t rows, uint64_t d0, uint32_t b0, uint32_t b1, uint32_t b2, CUtensorMapSwizzle sw) {
  cuuint64_t dims[3] = {d0, rows, cols / d0}, str[2] = {cols * 2, d0 * 2};
  cuuint32_t box[3] = {b0, b1, b2}, es[3] = {1, 1, 1};
  enc(m, CU_TENSOR_MAP_DATA_TYPE_BFLOAT16, b2 ? 3 : 2, const_cast<void*>(p), dims, str, box, es, CU_TENSOR_MAP_INTERLEAVE_NONE, sw,
      CU_TENSOR_MAP_L2_PROMOTION_L2_128B, CU_TENSOR_MAP_FLOAT_OOB_FILL_NONE);
}

}

extern "C" void kernel_launch(void* const* d_in, const int* in_sizes, int n_in, void* d_out, int out_size) {
  (void)in_sizes; (void)n_in; (void)out_size;
  Ptrs P;
  P.x = (const __nv_bfloat16*)d_in[0]; P.wqkv = (const __nv_bfloat16*)d_in[1]; P.wo = (const __nv_bfloat16*)d_in[2];
  P.wr = (const __nv_bfloat16*)d_in[4]; P.wg = (const __nv_bfloat16*)d_in[5]; P.wu = (const __nv_bfloat16*)d_in[6];
  P.wd = (const __nv_bfloat16*)d_in[7]; P.out = (__nv_bfloat16*)d_out;
  void* fn = nullptr;
  cudaDriverEntryPointQueryResult q;
  cudaGetDriverEntryPoint("cuTensorMapEncodeTiled", &fn, cudaEnableDefault, &q);
  EncodeFn enc = (EncodeFn)fn;
  CUtensorMap tmX, tmW, tmO, tmG, tmU, tmD, tmR;
  make_map(enc, &tmX, P.x, D_, S_, D_, 64, 128, 0, CU_TENSOR_MAP_SWIZZLE_128B);
  make_map(enc, &tmW, P.wqkv, 3 * D_, D_, D_, 64, 64, 3, CU_TENSOR_MAP_SWIZZLE_128B);
  make_map(enc, &tmO, P.wo, D_, D_, 64, 64, 64, 2, CU_TENSOR_MAP_SWIZZLE_128B);
  make_map(enc, &tmG, P.wg, F_, D_, F_, 32, 128, 0, CU_TENSOR_MAP_SWIZZLE_64B);
  make_map(enc, &tmU, P.wu, F_, D_, F_, 32, 128, 0, CU_TENSOR_MAP_SWIZZLE_64B);
  make_map(enc, &tmD, P.wd, D_, F_, 64, 64, 32, 4, CU_TENSOR_MAP_SWIZZLE_128B);
  make_map(enc, &tmR, P.x, D_, S_, 64, 64, 64, 2, CU_TENSOR_MAP_SWIZZLE_128B);
  cudaFuncSetAttribute(fused_kernel, cudaFuncAttributeMaxDynamicSharedMemorySize, SMEM_BYTES);
  fused_kernel<<<NCTA, 384, SMEM_BYTES>>>(tmX, tmW, tmO, tmG, tmU, tmD, tmR, P);
}
```

```cpp
#include <cuda_runtime.h>
#include <cuda.h>
#include <cuda_bf16.h>
#include <stdint.h>
#include <type_traits>

namespace {

constexpr int S_ = 2048, D_ = 1024, F_ = 3584;
constexpr int NCTA = 128, NFFN = 112;
constexpr uint32_t SENT = 0xFFFFFFFFu;
constexpr int SPIN_LIMIT = 1 << 20;

#define ADELAY 800
#define NPK 0x233333333333ull
#define KDELAY 800
constexpr int NDIR = 4;
#define MIX 2
#define BDELAY 1400
#define NOOUT 0
#define PD0 2
#define NPD 8
#define PDT 150
#define DIRX 6
#define SDELAY 600
#define LDELAY 300
#define NOSPEC 0
#define LOCK 1
#define DPF 1
#define STLD 2
#define RELK 1
#define PERT 1
#define QHOLD 1
#define CDELAY 0
#define ODELAY 0
#define YDELAY 500
#define EFX 0
#define EFW 1
#define EFF 1
#define KLEAD 13
#define GDELAY 600
#define PFST 1
#define W0OFF 1
constexpr uint32_t STAGE_B = 57344;
__host__ __device__ constexpr uint32_t xoff(int s, int w) { return ((0x876531CAu >> (4 * (s + 4 * w))) & 15) * 16384; }
__host__ __device__ constexpr uint32_t woff(int s) { return (s < 2 ? 9 * 16384 : 0) + (s & 1) * 8192; }
constexpr uint32_t WSTR = 32768;
constexpr uint32_t OFF_BARS = 229376;
constexpr uint32_t OFF_COLSUM = 229632;
constexpr uint32_t OFF_STATS = 230400;
constexpr uint32_t SMEM_BYTES = 232448;
constexpr uint32_t B_FULL = 0, B_EMPTY = 32, B_AUX = 64, B_SEL2 = 72, B_KVL = 80, B_FULL3 = 88, B_SW = 216, B_OUT = 224, B_LATE = 232, B_SEL = B_FULL + 8, B_FFN = 240;
__host__ __device__ constexpr uint32_t o3(int p) { return p * 8 + (p & 8) * 8; }
__host__ __device__ constexpr uint32_t bar3(int i) { return OFF_STATS + 1024 + (i >> 3) * 128 + ((i & 32) ? 0 : 64) + (i & 7) * 8; }
constexpr uint32_t SLOT_B = 16384;
constexpr uint32_t sb = 1024;
constexpr uint32_t bars = sb + OFF_BARS;
constexpr uint64_t WO_SLOTS = 0x6531428709653142ull;
constexpr uint32_t GU_SLOTS = 0xBA804279u;
constexpr uint32_t HST = 5 * SLOT_B;
constexpr uint32_t OFF_LNP = OFF_STATS;
constexpr uint32_t OFF_MSC = OFF_COLSUM + 512;
constexpr uint32_t OFF_KVB = 13 * SLOT_B + 8192;

struct Scratch {
  uint4 st1[64 * 48];
  uint4 csp[16 * 8 * 48];
  uint4 kvp[16 * 2304];
  uint4 obuf[32 * 64 * 128];
  uint4 st2[S_];
  uint32_t pred[S_];
  uint4 cst[8 * 32];
  uint4 hsel[64 * 128];
  uint32_t cand[8 * 32];
  uint4 ybuf[NCTA * NFFN * 4];
  unsigned epoch;
};
__device__ __align__(1024) Scratch G;
#define TS_DECL
#define TS(i)
#define TSG(i)
#define TSV(i, v)
#define TS_DUMP(slot)
#define PTS(i)

__device__ __forceinline__ uint32_t smem_u32(const void* p) { return (uint32_t)__cvta_generic_to_shared(p); }
__device__ __forceinline__ void mbar_init(uint32_t bar, uint32_t cnt) { asm volatile("mbarrier.init.shared::cta.b64 [%0], %1;" :: "r"(bar), "r"(cnt) : "memory"); }
__device__ __forceinline__ void mbar_expect_tx(uint32_t bar, uint32_t bytes) { asm volatile("mbarrier.arrive.expect_tx.shared::cta.b64 _, [%0], %1;" :: "r"(bar), "r"(bytes) : "memory"); }
__device__ __forceinline__ void mbar_arrive(uint32_t bar) { asm volatile("mbarrier.arrive.shared::cta.b64 _, [%0];" :: "r"(bar) : "memory"); }
#define SPINCHK(it, code) if ((it) > SPIN_LIMIT) break
__device__ __forceinline__ void mbar_wait(uint32_t bar, uint32_t parity) {
  asm volatile("{\n.reg .pred p;\n.reg .u32 c;\nmov.u32 c, 0;\n"
               "WL:\nmbarrier.try_wait.parity.shared::cta.b64 p, [%0], %1;\n@p bra WD;\n"
               "add.u32 c, c, 1;\nsetp.lt.u32 p, c, 1048576;\n@p bra WL;\nWD:\n}" :: "r"(bar), "r"(parity) : "memory");
}
__device__ __forceinline__ uint64_t l2_stream() { uint64_t p; asm("createpolicy.fractional.L2::evict_first.b64 %0, 1.0;" : "=l"(p)); return p; }
__device__ __forceinline__ void tma_2d(uint32_t dst, const CUtensorMap* tm, int c0, int c1, uint32_t bar, bool stream) {
  if (stream) asm volatile("cp.async.bulk.tensor.2d.shared::cluster.global.mbarrier::complete_tx::bytes.L2::cache_hint [%0], [%1, {%3, %4}], [%2], %5;"
                           :: "r"(dst), "l"(tm), "r"(bar), "r"(c0), "r"(c1), "l"(l2_stream()) : "memory");
  else asm volatile("cp.async.bulk.tensor.2d.shared::cluster.global.mbarrier::complete_tx::bytes [%0], [%1, {%3, %4}], [%2];"
                    :: "r"(dst), "l"(tm), "r"(bar), "r"(c0), "r"(c1) : "memory");
}
__device__ __forceinline__ void tma_3d(uint32_t dst, const CUtensorMap* tm, int c0, int c1, int c2, uint32_t bar, bool stream) {
  if (stream) asm volatile("cp.async.bulk.tensor.3d.shared::cluster.global.mbarrier::complete_tx::bytes.L2::cache_hint [%0], [%1, {%3, %4, %5}], [%2], %6;"
                           :: "r"(dst), "l"(tm), "r"(bar), "r"(c0), "r"(c1), "r"(c2), "l"(l2_stream()) : "memory");
  else asm volatile("cp.async.bulk.tensor.3d.shared::cluster.global.mbarrier::complete_tx::bytes [%0], [%1, {%3, %4, %5}], [%2];"
                    :: "r"(dst), "l"(tm), "r"(bar), "r"(c0), "r"(c1), "r"(c2) : "memory");
}
__device__ __forceinline__ void tma_2d_mc(uint32_t dst, const CUtensorMap* tm, int c0, int c1, uint32_t bar, bool stream) {
  if (stream) asm volatile("cp.async.bulk.tensor.2d.shared::cluster.global.mbarrier::complete_tx::bytes.multicast::cluster.L2::cache_hint [%0], [%1, {%3, %4}], [%2], %5, %6;"
                           :: "r"(dst), "l"(tm), "r"(bar), "r"(c0), "r"(c1), "h"((uint16_t)3), "l"(l2_stream()) : "memory");
  else asm volatile("cp.async.bulk.tensor.2d.shared::cluster.global.mbarrier::complete_tx::bytes.multicast::cluster [%0], [%1, {%3, %4}], [%2], %5;"
                    :: "r"(dst), "l"(tm), "r"(bar), "r"(c0), "r"(c1), "h"((uint16_t)3) : "memory");
}
__device__ __forceinline__ bool elect_one() {
  uint32_t p;
  asm volatile("{\n.reg .pred q;\nelect.sync _|q, 0xFFFFFFFF;\nselp.u32 %0, 1, 0, q;\n}" : "=r"(p));
  return p;
}
__device__ __forceinline__ void bulk_load_mc(uint32_t dst, const void* src, uint32_t bar, uint16_t mask) {
  asm volatile("cp.async.bulk.shared::cluster.global.mbarrier::complete_tx::bytes.multicast::cluster [%0], [%1], 8192, [%2], %3;"
               :: "r"(dst), "l"(src), "r"(bar), "h"(mask) : "memory");
}
__device__ __forceinline__ void bulk_load(uint32_t dst, const void* src, uint32_t bytes, uint32_t bar) {
  asm volatile("cp.async.bulk.shared::cluster.global.mbarrier::complete_tx::bytes [%0], [%1], %2, [%3];" :: "r"(dst), "l"(src), "r"(bytes), "r"(bar) : "memory");
}
__device__ __forceinline__ void bulk_store(void* dst, uint32_t src, uint32_t bytes) {
  asm volatile("cp.async.bulk.global.shared::cta.bulk_group [%0], [%1], %2;" :: "l"(dst), "r"(src), "r"(bytes) : "memory");
}
__device__ __forceinline__ void mbar_arrive_rem(uint32_t bar) { asm volatile("mbarrier.arrive.shared::cluster.b64 _, [%0];" :: "r"(bar) : "memory"); }
template <uint32_t O> __device__ __forceinline__ void ldsm4_o(uint32_t addr, uint32_t& a, uint32_t& b, uint32_t& c, uint32_t& d) {
  asm volatile("ldmatrix.sync.aligned.m8n8.x4.shared.b16 {%0,%1,%2,%3}, [%4+%5];" : "=r"(a), "=r"(b), "=r"(c), "=r"(d) : "r"(addr), "n"(O) : "memory");
}
template <uint32_t O> __device__ __forceinline__ void ldsm4t_o(uint32_t addr, uint32_t (&r)[4]) {
  asm volatile("ldmatrix.sync.aligned.m8n8.x4.trans.shared.b16 {%0,%1,%2,%3}, [%4+%5];" : "=r"(r[0]), "=r"(r[1]), "=r"(r[2]), "=r"(r[3]) : "r"(addr), "n"(O) : "memory");
}
__device__ __forceinline__ void mma16816(float (&c)[4], const uint32_t (&a)[4], uint32_t b0, uint32_t b1) {
  asm("mma.sync.aligned.m16n8k16.row.col.f32.bf16.bf16.f32 {%0,%1,%2,%3}, {%4,%5,%6,%7}, {%8,%9}, {%0,%1,%2,%3};"
      : "+f"(c[0]), "+f"(c[1]), "+f"(c[2]), "+f"(c[3]) : "r"(a[0]), "r"(a[1]), "r"(a[2]), "r"(a[3]), "r"(b0), "r"(b1));
}
__device__ __forceinline__ void l2_prefetch(const void* p) { asm volatile("prefetch.global.L2 [%0];" :: "l"(p) : "memory"); }
__device__ __forceinline__ uint32_t clk() { uint32_t t; asm volatile("mov.u32 %0, %%clock;" : "=r"(t) :: "memory"); return t; }
__device__ __forceinline__ void delay(uint32_t t0, uint32_t n) { while (clk() - t0 < n) {} }
__device__ __forceinline__ void tmap_prefetch(const CUtensorMap* tm) { asm volatile("prefetch.tensormap [%0];" :: "l"(tm) : "memory"); }
__device__ __forceinline__ void wg_fence() { asm volatile("wgmma.fence.sync.aligned;" ::: "memory"); }
__device__ __forceinline__ void wg_commit() { asm volatile("wgmma.commit_group.sync.aligned;" ::: "memory"); }
template <int N> __device__ __forceinline__ void wg_wait() { asm volatile("wgmma.wait_group.sync.aligned %0;" :: "n"(N) : "memory"); }
template <int N> __device__ __forceinline__ void pin(float (&d)[N]) {
#pragma unroll
  for (int i = 0; i < N; i++) asm volatile("" : "+f"(d[i]) :: "memory");
}
__device__ __forceinline__ void pin4(uint4& v) { asm volatile("" : "+r"(v.x), "+r"(v.y), "+r"(v.z), "+r"(v.w) :: "memory"); }
template <uint32_t SBO, uint32_t SWZ> __device__ __forceinline__ uint64_t dsc(uint32_t lo) { return ((uint64_t)((SBO >> 4) | (SWZ << 30)) << 32) | lo; }
__host__ __device__ constexpr uint32_t dlo(uint32_t addr, uint32_t lbo) { return (addr >> 4) | ((lbo >> 4) << 16); }
__device__ __forceinline__ void bar_sync(int id, int n) { asm volatile("bar.sync %0, %1;" :: "r"(id), "r"(n) : "memory"); }
__device__ __forceinline__ void bar_arrive(int id, int n) { asm volatile("bar.arrive %0, %1;" :: "r"(id), "r"(n) : "memory"); }
__device__ __forceinline__ void fence_async_smem() { asm volatile("fence.proxy.async.shared::cta;" ::: "memory"); }
__device__ __forceinline__ void fence_gpu() { asm volatile("fence.acq_rel.gpu;" ::: "memory"); }
__device__ __forceinline__ uint4 ld_cg4(const void* p) { uint4 v; asm volatile("ld.global.cg.v4.u32 {%0,%1,%2,%3}, [%4];" : "=r"(v.x), "=r"(v.y), "=r"(v.z), "=r"(v.w) : "l"(p) : "memory"); return v; }
__device__ __forceinline__ uint4 ld_rlx4(const void* p) { uint4 v; asm volatile("ld.relaxed.gpu.global.v4.u32 {%0,%1,%2,%3}, [%4];" : "=r"(v.x), "=r"(v.y), "=r"(v.z), "=r"(v.w) : "l"(p) : "memory"); return v; }
__device__ __forceinline__ uint32_t ld_rlx(const void* p) { uint32_t v; asm volatile("ld.relaxed.gpu.global.u32 %0, [%1];" : "=r"(v) : "l"(p) : "memory"); return v; }
__device__ __forceinline__ void st_rlx4(void* p, uint4 v) { asm volatile("st.relaxed.gpu.global.v4.u32 [%0], {%1,%2,%3,%4};" :: "l"(p), "r"(v.x), "r"(v.y), "r"(v.z), "r"(v.w) : "memory"); }
__device__ __forceinline__ void st_rlx2(void* p, uint32_t a, uint32_t b) { asm volatile("st.relaxed.gpu.global.v2.u32 [%0], {%1,%2};" :: "l"(p), "r"(a), "r"(b) : "memory"); }
__device__ __forceinline__ void st_rlx(void* p, uint32_t a) { asm volatile("st.relaxed.gpu.global.u32 [%0], %1;" :: "l"(p), "r"(a) : "memory"); }
__device__ __forceinline__ void red4(bool on, void* p, float a, float b, float c, float d) {
  asm volatile("{\n.reg .pred q;\nsetp.ne.b32 q, %5, 0;\n@q red.relaxed.gpu.global.add.v4.f32 [%0], {%1,%2,%3,%4};\n}" :: "l"(p), "f"(a), "f"(b), "f"(c), "f"(d), "r"((int)on) : "memory");
}
__device__ __forceinline__ uint32_t pack2(float lo, float hi) { uint32_t r; asm("cvt.rn.bf16x2.f32 %0, %1, %2;" : "=r"(r) : "f"(hi), "f"(lo)); return r; }
__device__ __forceinline__ float bf_lo(uint32_t v) { return __uint_as_float(v << 16); }
__device__ __forceinline__ float bf_hi(uint32_t v) { return __uint_as_float(v & 0xFFFF0000u); }
__device__ __forceinline__ void stsm4(uint32_t addr, uint32_t a, uint32_t b, uint32_t c, uint32_t d) {
  asm volatile("stmatrix.sync.aligned.m8n8.x4.shared.b16 [%0], {%1,%2,%3,%4};" :: "r"(addr), "r"(a), "r"(b), "r"(c), "r"(d) : "memory");
}
template <uint32_t O> __device__ __forceinline__ void stsm4_o(uint32_t addr, uint32_t a, uint32_t b, uint32_t c, uint32_t d) {
  asm volatile("stmatrix.sync.aligned.m8n8.x4.shared.b16 [%0+%5], {%1,%2,%3,%4};" :: "r"(addr), "r"(a), "r"(b), "r"(c), "r"(d), "n"(O) : "memory");
}
__device__ __forceinline__ void sts4(uint32_t addr, uint32_t a, uint32_t b, uint32_t c, uint32_t d) { asm volatile("st.shared.v4.u32 [%0], {%1,%2,%3,%4};" :: "r"(addr), "r"(a), "r"(b), "r"(c), "r"(d) : "memory"); }
__device__ __forceinline__ void sts2f(uint32_t addr, float a, float b) { asm volatile("st.shared.v2.f32 [%0], {%1,%2};" :: "r"(addr), "f"(a), "f"(b) : "memory"); }
__device__ __forceinline__ void sts1(uint32_t addr, uint32_t a) { asm volatile("st.shared.u32 [%0], %1;" :: "r"(addr), "r"(a) : "memory"); }
__device__ __forceinline__ float2 lds2f(uint32_t addr) { float2 v; asm volatile("ld.shared.v2.f32 {%0,%1}, [%2];" : "=f"(v.x), "=f"(v.y) : "r"(addr) : "memory"); return v; }
template <uint32_t O> __device__ __forceinline__ float2 lds2f_o(uint32_t addr) { float2 v; asm volatile("ld.shared.v2.f32 {%0,%1}, [%2+%3];" : "=f"(v.x), "=f"(v.y) : "r"(addr), "n"(O) : "memory"); return v; }
template <int I, int N, class F> __device__ __forceinline__ void static_for(F&& f) { if constexpr (I < N) { f(std::integral_constant<int, I>{}); static_for<I + 1, N>(f); } }
__device__ __forceinline__ uint4 lds4(uint32_t addr) { uint4 v; asm volatile("ld.shared.v4.u32 {%0,%1,%2,%3}, [%4];" : "=r"(v.x), "=r"(v.y), "=r"(v.z), "=r"(v.w) : "r"(addr) : "memory"); return v; }
__device__ __forceinline__ uint32_t lds1(uint32_t addr) { uint32_t v; asm volatile("ld.shared.u32 %0, [%1];" : "=r"(v) : "r"(addr) : "memory"); return v; }
__device__ __forceinline__ float ex2(float x) { float y; asm("ex2.approx.ftz.f32 %0, %1;" : "=f"(y) : "f"(x)); return y; }
__device__ __forceinline__ uint32_t max4(uint32_t m, const uint4& v) { return __vimax3_u32(__vimax3_u32(m, v.x, v.y), v.z, v.w); }
__device__ __forceinline__ float rsq(float x) { float y; asm("rsqrt.approx.ftz.f32 %0, %1;" : "=f"(y) : "f"(x)); return y; }
__device__ __forceinline__ float rcp(float x) { float y; asm("rcp.approx.ftz.f32 %0, %1;" : "=f"(y) : "f"(x)); return y; }
__device__ __forceinline__ uint2 ld_rlx2(const void* p) { uint2 v; asm volatile("ld.relaxed.gpu.global.v2.u32 {%0,%1}, [%2];" : "=r"(v.x), "=r"(v.y) : "l"(p) : "memory"); return v; }
template <uint32_t O> __device__ __forceinline__ uint4 lds4_o(uint32_t addr) { uint4 v; asm volatile("ld.shared.v4.u32 {%0,%1,%2,%3}, [%4+%5];" : "=r"(v.x), "=r"(v.y), "=r"(v.z), "=r"(v.w) : "r"(addr), "n"(O) : "memory"); return v; }
__device__ __forceinline__ uint32_t hadd2(uint32_t a, uint32_t b) { uint32_t r; asm("add.rn.bf16x2 %0, %1, %2;" : "=r"(r) : "r"(a), "r"(b)); return r; }
__device__ __forceinline__ uint4 hadd8(const uint4& a, const uint4& b) { return make_uint4(hadd2(a.x, b.x), hadd2(a.y, b.y), hadd2(a.z, b.z), hadd2(a.w, b.w)); }
__device__ __forceinline__ bool hnan(uint32_t a) { return (a & 0x7FFF0000u) > 0x7F800000u; }
__device__ __forceinline__ uint32_t hfma2(uint32_t a, uint32_t b, uint32_t c) { uint32_t r; asm("fma.rn.bf16x2 %0, %1, %2, %3;" : "=r"(r) : "r"(a), "r"(b), "r"(c)); return r; }
__device__ __forceinline__ uint32_t ordered(float v) { const uint32_t u = __float_as_uint(v); return u ^ ((uint32_t)((int)u >> 31) | 0x80000000u); }
__device__ __forceinline__ uint32_t route(const uint4& v, float sw, int row, float2& pr) {
  const float mean = __uint_as_float(v.x) * (1.f / D_);
  pr.x = rsq(fmaxf(fmaf(-mean, mean, __uint_as_float(v.y) * (1.f / D_)), 0.f) + 1e-5f);
  pr.y = -mean * pr.x;
  return min(ordered(pr.x * fmaf(-mean, sw, __uint_as_float(v.z))) & ~2047u, 0xFFFFF000u) | (2047 - row);
}
__device__ __forceinline__ uint2 top2(uint32_t a, uint32_t b, uint32_t c, uint32_t d) {
  const uint32_t h0 = max(a, b), h1 = max(c, d), h = max(h0, h1), l = __vimax3_u32(min(h0, h1), min(a, b), min(c, d));
  const uint32_t m1 = __reduce_max_sync(~0u, h);
  return make_uint2(m1, __reduce_max_sync(~0u, h == m1 ? l : h));
}
__device__ __forceinline__ uint32_t hmul2(uint32_t a, uint32_t b) { uint32_t r; asm("mul.rn.bf16x2 %0, %1, %2;" : "=r"(r) : "r"(a), "r"(b)); return r; }
__device__ __forceinline__ uint32_t phi2(float u0, float u1, uint32_t r2, float rl) {
  uint32_t p, r;
  asm("cvt.rn.relu.bf16x2.f32 %0, %1, %2;" : "=r"(p) : "f"(u1), "f"(u0));
  asm("fma.rn.bf16x2 %0, %1, %2, %3;" : "=r"(r) : "r"(p), "r"(r2), "r"(pack2(__saturatef(ex2(u0 * rl) + 1e-6f), __saturatef(ex2(u1 * rl) + 1e-6f))));
  return r;
}

template<int TA, int TB, int OFF, int SZ> __device__ __forceinline__ void wgmma_n192_ss(float (&d)[SZ], uint64_t da, uint64_t db, int scale_d) {
  asm volatile("{\n.reg .pred p;\nsetp.ne.b32 p, %98, 0;\n"
    "wgmma.mma_async.sync.aligned.m64n192k16.f32.bf16.bf16 {%0,%1,%2,%3,%4,%5,%6,%7,%8,%9,%10,%11,%12,%13,%14,%15,%16,%17,%18,%19,%20,%21,%22,%23,%24,%25,%26,%27,%28,%29,%30,%31,%32,%33,%34,%35,%36,%37,%38,%39,%40,%41,%42,%43,%44,%45,%46,%47,%48,%49,%50,%51,%52,%53,%54,%55,%56,%57,%58,%59,%60,%61,%62,%63,%64,%65,%66,%67,%68,%69,%70,%71,%72,%73,%74,%75,%76,%77,%78,%79,%80,%81,%82,%83,%84,%85,%86,%87,%88,%89,%90,%91,%92,%93,%94,%95}, %96, %97, p, 1, 1, %99, %100;\n}\n"
    : "+f"(d[OFF+0]), "+f"(d[OFF+1]), "+f"(d[OFF+2]), "+f"(d[OFF+3]), "+f"(d[OFF+4]), "+f"(d[OFF+5]), "+f"(d[OFF+6]), "+f"(d[OFF+7]),
      "+f"(d[OFF+8]), "+f"(d[OFF+9]), "+f"(d[OFF+10]), "+f"(d[OFF+11]), "+f"(d[OFF+12]), "+f"(d[OFF+13]), "+f"(d[OFF+14]), "+f"(d[OFF+15]),
      "+f"(d[OFF+16]), "+f"(d[OFF+17]), "+f"(d[OFF+18]), "+f"(d[OFF+19]), "+f"(d[OFF+20]), "+f"(d[OFF+21]), "+f"(d[OFF+22]), "+f"(d[OFF+23]),
      "+f"(d[OFF+24]), "+f"(d[OFF+25]), "+f"(d[OFF+26]), "+f"(d[OFF+27]), "+f"(d[OFF+28]), "+f"(d[OFF+29]), "+f"(d[OFF+30]), "+f"(d[OFF+31]),
      "+f"(d[OFF+32]), "+f"(d[OFF+33]), "+f"(d[OFF+34]), "+f"(d[OFF+35]), "+f"(d[OFF+36]), "+f"(d[OFF+37]), "+f"(d[OFF+38]), "+f"(d[OFF+39]),
      "+f"(d[OFF+40]), "+f"(d[OFF+41]), "+f"(d[OFF+42]), "+f"(d[OFF+43]), "+f"(d[OFF+44]), "+f"(d[OFF+45]), "+f"(d[OFF+46]), "+f"(d[OFF+47]),
      "+f"(d[OFF+48]), "+f"(d[OFF+49]), "+f"(d[OFF+50]), "+f"(d[OFF+51]), "+f"(d[OFF+52]), "+f"(d[OFF+53]), "+f"(d[OFF+54]), "+f"(d[OFF+55]),
      "+f"(d[OFF+56]), "+f"(d[OFF+57]), "+f"(d[OFF+58]), "+f"(d[OFF+59]), "+f"(d[OFF+60]), "+f"(d[OFF+61]), "+f"(d[OFF+62]), "+f"(d[OFF+63]),
      "+f"(d[OFF+64]), "+f"(d[OFF+65]), "+f"(d[OFF+66]), "+f"(d[OFF+67]), "+f"(d[OFF+68]), "+f"(d[OFF+69]), "+f"(d[OFF+70]), "+f"(d[OFF+71]),
      "+f"(d[OFF+72]), "+f"(d[OFF+73]), "+f"(d[OFF+74]), "+f"(d[OFF+75]), "+f"(d[OFF+76]), "+f"(d[OFF+77]), "+f"(d[OFF+78]), "+f"(d[OFF+79]),
      "+f"(d[OFF+80]), "+f"(d[OFF+81]), "+f"(d[OFF+82]), "+f"(d[OFF+83]), "+f"(d[OFF+84]), "+f"(d[OFF+85]), "+f"(d[OFF+86]), "+f"(d[OFF+87]),
      "+f"(d[OFF+88]), "+f"(d[OFF+89]), "+f"(d[OFF+90]), "+f"(d[OFF+91]), "+f"(d[OFF+92]), "+f"(d[OFF+93]), "+f"(d[OFF+94]), "+f"(d[OFF+95])
    : "l"(da), "l"(db), "r"(scale_d), "n"(TA), "n"(TB));
}
template<int TA, int TB, int OFF, int SZ> __device__ __forceinline__ void wgmma_n128_ss(float (&d)[SZ], uint64_t da, uint64_t db, int scale_d) {
  asm volatile("{\n.reg .pred p;\nsetp.ne.b32 p, %66, 0;\n"
    "wgmma.mma_async.sync.aligned.m64n128k16.f32.bf16.bf16 {%0,%1,%2,%3,%4,%5,%6,%7,%8,%9,%10,%11,%12,%13,%14,%15,%16,%17,%18,%19,%20,%21,%22,%23,%24,%25,%26,%27,%28,%29,%30,%31,%32,%33,%34,%35,%36,%37,%38,%39,%40,%41,%42,%43,%44,%45,%46,%47,%48,%49,%50,%51,%52,%53,%54,%55,%56,%57,%58,%59,%60,%61,%62,%63}, %64, %65, p, 1, 1, %67, %68;\n}\n"
    : "+f"(d[OFF+0]), "+f"(d[OFF+1]), "+f"(d[OFF+2]), "+f"(d[OFF+3]), "+f"(d[OFF+4]), "+f"(d[OFF+5]), "+f"(d[OFF+6]), "+f"(d[OFF+7]),
      "+f"(d[OFF+8]), "+f"(d[OFF+9]), "+f"(d[OFF+10]), "+f"(d[OFF+11]), "+f"(d[OFF+12]), "+f"(d[OFF+13]), "+f"(d[OFF+14]), "+f"(d[OFF+15]),
      "+f"(d[OFF+16]), "+f"(d[OFF+17]), "+f"(d[OFF+18]), "+f"(d[OFF+19]), "+f"(d[OFF+20]), "+f"(d[OFF+21]), "+f"(d[OFF+22]), "+f"(d[OFF+23]),
      "+f"(d[OFF+24]), "+f"(d[OFF+25]), "+f"(d[OFF+26]), "+f"(d[OFF+27]), "+f"(d[OFF+28]), "+f"(d[OFF+29]), "+f"(d[OFF+30]), "+f"(d[OFF+31]),
      "+f"(d[OFF+32]), "+f"(d[OFF+33]), "+f"(d[OFF+34]), "+f"(d[OFF+35]), "+f"(d[OFF+36]), "+f"(d[OFF+37]), "+f"(d[OFF+38]), "+f"(d[OFF+39]),
      "+f"(d[OFF+40]), "+f"(d[OFF+41]), "+f"(d[OFF+42]), "+f"(d[OFF+43]), "+f"(d[OFF+44]), "+f"(d[OFF+45]), "+f"(d[OFF+46]), "+f"(d[OFF+47]),
      "+f"(d[OFF+48]), "+f"(d[OFF+49]), "+f"(d[OFF+50]), "+f"(d[OFF+51]), "+f"(d[OFF+52]), "+f"(d[OFF+53]), "+f"(d[OFF+54]), "+f"(d[OFF+55]),
      "+f"(d[OFF+56]), "+f"(d[OFF+57]), "+f"(d[OFF+58]), "+f"(d[OFF+59]), "+f"(d[OFF+60]), "+f"(d[OFF+61]), "+f"(d[OFF+62]), "+f"(d[OFF+63])
    : "l"(da), "l"(db), "r"(scale_d), "n"(TA), "n"(TB));
}
template<int TA, int TB, int OFF, int SZ> __device__ __forceinline__ void wgmma_n64_ss(float (&d)[SZ], uint64_t da, uint64_t db, int scale_d) {
  asm volatile("{\n.reg .pred p;\nsetp.ne.b32 p, %34, 0;\n"
    "wgmma.mma_async.sync.aligned.m64n64k16.f32.bf16.bf16 {%0,%1,%2,%3,%4,%5,%6,%7,%8,%9,%10,%11,%12,%13,%14,%15,%16,%17,%18,%19,%20,%21,%22,%23,%24,%25,%26,%27,%28,%29,%30,%31}, %32, %33, p, 1, 1, %35, %36;\n}\n"
    : "+f"(d[OFF+0]), "+f"(d[OFF+1]), "+f"(d[OFF+2]), "+f"(d[OFF+3]), "+f"(d[OFF+4]), "+f"(d[OFF+5]), "+f"(d[OFF+6]), "+f"(d[OFF+7]),
      "+f"(d[OFF+8]), "+f"(d[OFF+9]), "+f"(d[OFF+10]), "+f"(d[OFF+11]), "+f"(d[OFF+12]), "+f"(d[OFF+13]), "+f"(d[OFF+14]), "+f"(d[OFF+15]),
      "+f"(d[OFF+16]), "+f"(d[OFF+17]), "+f"(d[OFF+18]), "+f"(d[OFF+19]), "+f"(d[OFF+20]), "+f"(d[OFF+21]), "+f"(d[OFF+22]), "+f"(d[OFF+23]),
      "+f"(d[OFF+24]), "+f"(d[OFF+25]), "+f"(d[OFF+26]), "+f"(d[OFF+27]), "+f"(d[OFF+28]), "+f"(d[OFF+29]), "+f"(d[OFF+30]), "+f"(d[OFF+31])
    : "l"(da), "l"(db), "r"(scale_d), "n"(TA), "n"(TB));
}
template<int TB, int OFF, int SZ> __device__ __forceinline__ void wgmma_n64_rs(float (&d)[SZ], uint32_t a0, uint32_t a1, uint32_t a2, uint32_t a3, uint64_t db, int scale_d) {
  asm volatile("{\n.reg .pred p;\nsetp.ne.b32 p, %37, 0;\n"
    "wgmma.mma_async.sync.aligned.m64n64k16.f32.bf16.bf16 {%0,%1,%2,%3,%4,%5,%6,%7,%8,%9,%10,%11,%12,%13,%14,%15,%16,%17,%18,%19,%20,%21,%22,%23,%24,%25,%26,%27,%28,%29,%30,%31}, {%32,%33,%34,%35}, %36, p, 1, 1, %38;\n}\n"
    : "+f"(d[OFF+0]), "+f"(d[OFF+1]), "+f"(d[OFF+2]), "+f"(d[OFF+3]), "+f"(d[OFF+4]), "+f"(d[OFF+5]), "+f"(d[OFF+6]), "+f"(d[OFF+7]),
      "+f"(d[OFF+8]), "+f"(d[OFF+9]), "+f"(d[OFF+10]), "+f"(d[OFF+11]), "+f"(d[OFF+12]), "+f"(d[OFF+13]), "+f"(d[OFF+14]), "+f"(d[OFF+15]),
      "+f"(d[OFF+16]), "+f"(d[OFF+17]), "+f"(d[OFF+18]), "+f"(d[OFF+19]), "+f"(d[OFF+20]), "+f"(d[OFF+21]), "+f"(d[OFF+22]), "+f"(d[OFF+23]),
      "+f"(d[OFF+24]), "+f"(d[OFF+25]), "+f"(d[OFF+26]), "+f"(d[OFF+27]), "+f"(d[OFF+28]), "+f"(d[OFF+29]), "+f"(d[OFF+30]), "+f"(d[OFF+31])
    : "r"(a0), "r"(a1), "r"(a2), "r"(a3), "l"(db), "r"(scale_d), "n"(TB));
}
template<int TA, int TB, int OFF, int SZ> __device__ __forceinline__ void wgmma_n72_ss(float (&d)[SZ], uint64_t da, uint64_t db, int scale_d) {
  asm volatile("{\n.reg .pred p;\nsetp.ne.b32 p, %38, 0;\n"
    "wgmma.mma_async.sync.aligned.m64n72k16.f32.bf16.bf16 {%0,%1,%2,%3,%4,%5,%6,%7,%8,%9,%10,%11,%12,%13,%14,%15,%16,%17,%18,%19,%20,%21,%22,%23,%24,%25,%26,%27,%28,%29,%30,%31,%32,%33,%34,%35}, %36, %37, p, 1, 1, %39, %40;\n}\n"
    : "+f"(d[OFF+0]), "+f"(d[OFF+1]), "+f"(d[OFF+2]), "+f"(d[OFF+3]), "+f"(d[OFF+4]), "+f"(d[OFF+5]), "+f"(d[OFF+6]), "+f"(d[OFF+7]),
      "+f"(d[OFF+8]), "+f"(d[OFF+9]), "+f"(d[OFF+10]), "+f"(d[OFF+11]), "+f"(d[OFF+12]), "+f"(d[OFF+13]), "+f"(d[OFF+14]), "+f"(d[OFF+15]),
      "+f"(d[OFF+16]), "+f"(d[OFF+17]), "+f"(d[OFF+18]), "+f"(d[OFF+19]), "+f"(d[OFF+20]), "+f"(d[OFF+21]), "+f"(d[OFF+22]), "+f"(d[OFF+23]),
      "+f"(d[OFF+24]), "+f"(d[OFF+25]), "+f"(d[OFF+26]), "+f"(d[OFF+27]), "+f"(d[OFF+28]), "+f"(d[OFF+29]), "+f"(d[OFF+30]), "+f"(d[OFF+31]),
      "+f"(d[OFF+32]), "+f"(d[OFF+33]), "+f"(d[OFF+34]), "+f"(d[OFF+35])
    : "l"(da), "l"(db), "r"(scale_d), "n"(TA), "n"(TB));
}
template<int TB, int OFF, int SZ> __device__ __forceinline__ void wgmma_n40_rs(float (&d)[SZ], uint32_t a0, uint32_t a1, uint32_t a2, uint32_t a3, uint64_t db, int scale_d) {
  asm volatile("{\n.reg .pred p;\nsetp.ne.b32 p, %25, 0;\n"
    "wgmma.mma_async.sync.aligned.m64n40k16.f32.bf16.bf16 {%0,%1,%2,%3,%4,%5,%6,%7,%8,%9,%10,%11,%12,%13,%14,%15,%16,%17,%18,%19}, {%20,%21,%22,%23}, %24, p, 1, 1, %26;\n}\n"
    : "+f"(d[OFF+0]), "+f"(d[OFF+1]), "+f"(d[OFF+2]), "+f"(d[OFF+3]), "+f"(d[OFF+4]), "+f"(d[OFF+5]), "+f"(d[OFF+6]), "+f"(d[OFF+7]),
      "+f"(d[OFF+8]), "+f"(d[OFF+9]), "+f"(d[OFF+10]), "+f"(d[OFF+11]), "+f"(d[OFF+12]), "+f"(d[OFF+13]), "+f"(d[OFF+14]), "+f"(d[OFF+15]),
      "+f"(d[OFF+16]), "+f"(d[OFF+17]), "+f"(d[OFF+18]), "+f"(d[OFF+19])
    : "r"(a0), "r"(a1), "r"(a2), "r"(a3), "l"(db), "r"(scale_d), "n"(TB));
}
template<int TB, int OFF, int SZ> __device__ __forceinline__ void wgmma_n128_rs(float (&d)[SZ], uint32_t a0, uint32_t a1, uint32_t a2, uint32_t a3, uint64_t db, int scale_d) {
  asm volatile("{\n.reg .pred p;\nsetp.ne.b32 p, %69, 0;\n"
    "wgmma.mma_async.sync.aligned.m64n128k16.f32.bf16.bf16 {%0,%1,%2,%3,%4,%5,%6,%7,%8,%9,%10,%11,%12,%13,%14,%15,%16,%17,%18,%19,%20,%21,%22,%23,%24,%25,%26,%27,%28,%29,%30,%31,%32,%33,%34,%35,%36,%37,%38,%39,%40,%41,%42,%43,%44,%45,%46,%47,%48,%49,%50,%51,%52,%53,%54,%55,%56,%57,%58,%59,%60,%61,%62,%63}, {%64,%65,%66,%67}, %68, p, 1, 1, %70;\n}\n"
    : "+f"(d[OFF+0]), "+f"(d[OFF+1]), "+f"(d[OFF+2]), "+f"(d[OFF+3]), "+f"(d[OFF+4]), "+f"(d[OFF+5]), "+f"(d[OFF+6]), "+f"(d[OFF+7]),
      "+f"(d[OFF+8]), "+f"(d[OFF+9]), "+f"(d[OFF+10]), "+f"(d[OFF+11]), "+f"(d[OFF+12]), "+f"(d[OFF+13]), "+f"(d[OFF+14]), "+f"(d[OFF+15]),
      "+f"(d[OFF+16]), "+f"(d[OFF+17]), "+f"(d[OFF+18]), "+f"(d[OFF+19]), "+f"(d[OFF+20]), "+f"(d[OFF+21]), "+f"(d[OFF+22]), "+f"(d[OFF+23]),
      "+f"(d[OFF+24]), "+f"(d[OFF+25]), "+f"(d[OFF+26]), "+f"(d[OFF+27]), "+f"(d[OFF+28]), "+f"(d[OFF+29]), "+f"(d[OFF+30]), "+f"(d[OFF+31]),
      "+f"(d[OFF+32]), "+f"(d[OFF+33]), "+f"(d[OFF+34]), "+f"(d[OFF+35]), "+f"(d[OFF+36]), "+f"(d[OFF+37]), "+f"(d[OFF+38]), "+f"(d[OFF+39]),
      "+f"(d[OFF+40]), "+f"(d[OFF+41]), "+f"(d[OFF+42]), "+f"(d[OFF+43]), "+f"(d[OFF+44]), "+f"(d[OFF+45]), "+f"(d[OFF+46]), "+f"(d[OFF+47]),
      "+f"(d[OFF+48]), "+f"(d[OFF+49]), "+f"(d[OFF+50]), "+f"(d[OFF+51]), "+f"(d[OFF+52]), "+f"(d[OFF+53]), "+f"(d[OFF+54]), "+f"(d[OFF+55]),
      "+f"(d[OFF+56]), "+f"(d[OFF+57]), "+f"(d[OFF+58]), "+f"(d[OFF+59]), "+f"(d[OFF+60]), "+f"(d[OFF+61]), "+f"(d[OFF+62]), "+f"(d[OFF+63])
    : "r"(a0), "r"(a1), "r"(a2), "r"(a3), "l"(db), "r"(scale_d), "n"(TB));
}

struct Ptrs { const __nv_bfloat16 *x, *wqkv, *wo, *wr, *wg, *wu, *wd; __nv_bfloat16* out; };

__global__ void __cluster_dims__(2, 1, 1) __launch_bounds__(384, 1) fused_kernel(const __grid_constant__ CUtensorMap tmX, const __grid_constant__ CUtensorMap tmW,
                                                       const __grid_constant__ CUtensorMap tmO, const __grid_constant__ CUtensorMap tmG,
                                                       const __grid_constant__ CUtensorMap tmU, const __grid_constant__ CUtensorMap tmD,
                                                       const __grid_constant__ CUtensorMap tmM, const __grid_constant__ CUtensorMap tmPG,
                                                       const __grid_constant__ CUtensorMap tmPU, const __grid_constant__ CUtensorMap tmPD,
                                                       const Ptrs P) {
  extern __shared__ __align__(1024) uint8_t smem_raw[];
  const int tid = threadIdx.x, wid = __shfl_sync(~0u, tid >> 5, 0), wg = wid >> 2, lane = tid & 31;
#define MAPV 1
  const int pj = blockIdx.x >> 1, pi = pj - 36;
  const int gi = pj < 4 ? 0 : pj < 36 ? (pj - 4) & 7 : 1 + pi % 7, gk = pj < 4 ? 4 + pj : pj < 36 ? (pj - 4) >> 3 : 4 + pi / 7;
  const int b = MAPV == 0 ? blockIdx.x : MAPV == 1 ? gk * 16 + gi * 2 + (blockIdx.x & 1) : MAPV >= 4 ? gk * 16 + (((MAPV == 4 ? 0x73216540 : 0x75416320) >> (4 * gi)) & 7) * 2 + (blockIdx.x & 1) : MAPV == 2 ? gi * 16 + gk * 2 + (blockIdx.x & 1)
              : ((gi >> 2) * 4 + (gk & 3)) * 16 + ((gi & 3) + (gk & 4)) * 2 + (blockIdx.x & 1);
  const int rb = b >> 4, cg = b & 15, hf = cg >> 3, c3 = cg & 7;
  const int jp = cg >> 1;
  const int fidx = jp == rb ? -1 : b - 2 * rb - (jp > rb ? 2 : 0);
  const uint32_t rank = b & 1, own = rank << 24;
  const uint32_t zero = gridDim.y - 1;
  const uint32_t sm = own + sb, mb = own + bars;
  auto chunk_of = [&](int p) { return (int)((0x1765432FEDCBA980ull >> (4 * p)) & 15) ^ (p == 0 || p == 15 ? cg : p < 9 ? cg & 8 : cg & 14); };
  const int kl = (jp & 3) * 256;
  auto k_of = [&](int kb) { return kb >= 12 ? kl + (kb - 12) * 64 : kb * 64 < kl ? kb * 64 : kb * 64 + 256; };
  auto load_w = [&](int kb) {
#pragma unroll
    for (int i = 0; i < 3; i++) tma_2d(sm + woff(kb & 3) + i * WSTR, &tmW, i * D_ + cg * 64, k_of(kb), mb + B_FULL + 8 * (kb & 3), EFW);
  };
  TS_DECL; TS(0); TSG(30);
  if (wid == 8) {
    if (elect_one()) {
      if (smem_u32(smem_raw) != sm) {
#pragma unroll
        for (int i = 0; i < PERT; i++) sts1(mb, lds1(mb));
        asm volatile("trap;");
      }
#pragma unroll
      for (int s = 0; s < 4; s++) mbar_init(mb + B_FULL + 8 * s, 1);
      asm volatile("fence.mbarrier_init.release.cluster;" ::: "memory");
      fence_async_smem();
    }
  } else if (wid == 9) {
    if (elect_one()) {
#pragma unroll
      for (int i = 4; i < 32; i++)
        if (i != 27) mbar_init(mb + 8 * i, i < 8 ? 8 : i == 8 ? 64 : i == 26 ? 2 : i == 29 ? 3 : 1);
      asm volatile("fence.mbarrier_init.release.cluster;" ::: "memory");
      fence_async_smem();
    }
  } else if (wid == 11) {
#pragma unroll
    for (int i = 0; i < 2; i++) sts4(sm + OFF_STATS + i * 512 + lane * 16, SENT, SENT, SENT, SENT);
    fence_async_smem();
  }
  __syncwarp();
  asm volatile("barrier.cluster.arrive.relaxed.aligned;" ::: "memory");
  if (wid == 8) {
    if (elect_one()) {
      mbar_expect_tx(mb + B_FULL, STAGE_B);
      tma_2d(sm + xoff(0, 0), &tmX, k_of(0), rb * 256, mb + B_FULL, EFX);
      tma_2d(sm + xoff(0, 1), &tmX, k_of(0), rb * 256 + 128, mb + B_FULL, EFX);
      load_w(0);
    }
    __syncwarp();
  }
  asm volatile("barrier.cluster.wait.aligned;" ::: "memory");

  if (wg == 2) {
    asm volatile("setmaxnreg.dec.sync.aligned.u32 56;");
    auto wait3 = [&](int i) { mbar_wait(sm + bar3(i), 0); };
    if (wid == 8) {
      if (elect_one()) {
        int np = fidx >= 0 ? 0 : 32;
        if (fidx >= 0) mbar_expect_tx(mb + B_FFN, 32 * 512);
#pragma unroll 1
        for (int kb = 1; kb < 16; kb++) {
          const uint32_t fb = mb + B_FULL + 8 * (kb & 3);
          mbar_wait(fb + B_EMPTY, ((kb >> 2) & 1) ^ 1);
          mbar_expect_tx(fb, STAGE_B);
          tma_2d_mc(sm + xoff(kb & 3, rank), &tmX, k_of(kb), rb * 256 + rank * 128, fb, EFX);
          load_w(kb);
          if (kb >= 12) asm volatile("mbarrier.arrive.shared::cta.b64 _, [%0], 7;" :: "r"(fb + B_EMPTY) : "memory");
#pragma unroll 1
          for (int n = ((NPK << 16) >> (4 * kb)) & 15; n > 0 && np < 32; n--, np++)
            tma_2d(sm + OFF_STATS + 1024, (np & 1) ? &tmPU : &tmPG, (fidx >> 1) * 64, (np >> 1) * 64 + rank * 32, mb + B_FFN, false);
        }
        if (fidx >= 0) { mbar_wait(mb + B_FFN, 0); mbar_expect_tx(mb + B_FFN, 65536 + NPD * 512); mbar_expect_tx(mb + B_FFN + 8, 65536); }
        mbar_wait(mb + B_AUX, 0);
#pragma unroll 1
        for (int p = 0; p < 16; p++) {
          const uint32_t a = sm + bar3(0) + o3(p);
          sts4(sm + OFF_STATS + p * 128 + ((p & 7) << 4), 0x3F803F80u, 0x3F803F80u, 0x3F803F80u, 0x3F803F80u);
          mbar_init(a, 1); mbar_init(a + 256, 1); mbar_init(a + 448, 8); mbar_init(a + 704, p == 0 ? 8 << rank : p == 12 ? 1 : 8);
          mbar_expect_tx(a, 8192); mbar_expect_tx(a + 256, 8192); mbar_expect_tx(mb + B_FULL3 + 8 * p, SLOT_B);
        }
        asm volatile("fence.mbarrier_init.release.cluster;" ::: "memory");
        fence_async_smem();
        mbar_arrive_rem(bars + B_LATE); mbar_arrive_rem((1u << 24) + bars + B_LATE);
        PTS(2);
        const uint4* src = &G.obuf[(rb * 4 + rank * 2 + hf) * 64 * 128];
        wait3(48);
        delay(clk(), ADELAY);
#pragma unroll 1
        for (int i = 1; i < 17; i++) {
          const int p = min(i, 15);
          const uint32_t d = sm + (10 + (p & 3)) * SLOT_B + rank * 8192, fb = sm + bar3(0) + o3(p) + rank * 256;
          const uint4* q = src + chunk_of(i & 15) * 512;
          mbar_wait(sm + bar3(48) + o3(max(p - 4, 0)), 0);
          bulk_load_mc(d, q, fb, i < 15 ? 3 : 1 << ((i ^ rank ^ 1) & 1));
          if (i == 1) PTS(7);
        }
        PTS(15);
      }
    } else {
      const int r4 = lane >> 3, c8 = lane & 7;
      const uint32_t eb = (lane << 24) + bars + B_EMPTY;
      auto tagged = [](float v, uint32_t tag) { return ((__float_as_uint(v) + 128) & ~255u) | tag; };
      auto gather = [&](uint32_t tag) {
        const int q = (wid - 9) * 24 + lane;
        const uint4* cp = lane < 24 ? &G.csp[cg * 8 * 48 + q] : &G.st1[rb * 8 * 48 + (wid - 9) * 8 + lane - 24];
        uint4 v[8];
        delay(clk(), GDELAY);
#pragma unroll 1
        for (int it = 0;; it++) {
#pragma unroll
          for (int i = 0; i < 8; i++) v[i] = ld_rlx4(cp + i * 48);
          uint32_t x = 0;
#pragma unroll
          for (int i = 0; i < 8; i++) { v[i].x ^= tag; v[i].y ^= tag; v[i].z ^= tag; v[i].w ^= tag; x |= v[i].x | v[i].y | v[i].z | v[i].w; }
          if (!__any_sync(~0u, (x & 255) != 0)) break;
          SPINCHK(it, 3);
        }
        float c[4] = {0.f, 0.f, 0.f, 0.f};
#pragma unroll
        for (int i = 0; i < 8; i++) { c[0] += __uint_as_float(v[i].x); c[1] += __uint_as_float(v[i].y); c[2] += __uint_as_float(v[i].z); c[3] += __uint_as_float(v[i].w); }
        const uint32_t h0 = pack2(c[0], c[1]), h1 = pack2(c[2], c[3]), ca = sm + OFF_COLSUM + (q >> 1) * 32 + (q & 1) * 8;
        if (lane < 24) {
          sts2f(ca, __uint_as_float(h0), __uint_as_float(h1));
          sts2f(ca + 16, __uint_as_float(pack2(c[0] - bf_lo(h0), c[1] - bf_hi(h0))), __uint_as_float(pack2(c[2] - bf_lo(h1), c[3] - bf_hi(h1))));
        }
        fence_async_smem();
        mbar_arrive(mb + B_AUX);
      };
      const int r2 = lane >> 4, c16 = lane & 15;
      float a[12];
#pragma unroll
      for (int i = 0; i < 12; i++) a[i] = 0.f;
      auto add_w = [&](const uint2 (&w)[12]) {
#pragma unroll
        for (int i = 0; i < 12; i++) { float* q = a + (i >> 2) * 4; q[0] += bf_lo(w[i].x); q[1] += bf_hi(w[i].x); q[2] += bf_lo(w[i].y); q[3] += bf_hi(w[i].y); }
      };
      auto red_w = [&](float (&c)[6]) {
#pragma unroll
        for (int i = 0; i < 6; i++) { const int o = (i >> 1) * 4 + (i & 1); c[i] = (r2 ? a[o + 2] : a[o]) + __shfl_xor_sync(~0u, r2 ? a[o] : a[o + 2], 16); }
      };
      auto add_x = [&](int i, uint32_t v) {
        const float d0 = bf_lo(v), d1 = bf_hi(v);
        a[i] += d0 + d1; a[4 + i] = fmaf(d0, d0, fmaf(d1, d1, a[4 + i]));
      };
      auto red_x = [&]() {
        float u[4], v[2];
#pragma unroll
        for (int i = 0; i < 4; i++) u[i] = ((lane & 4) ? a[4 + i] : a[i]) + __shfl_xor_sync(~0u, (lane & 4) ? a[i] : a[4 + i], 4);
#pragma unroll
        for (int i = 0; i < 2; i++) v[i] = ((lane & 2) ? u[2 + i] : u[i]) + __shfl_xor_sync(~0u, (lane & 2) ? u[i] : u[2 + i], 2);
        return ((lane & 1) ? v[1] : v[0]) + __shfl_xor_sync(~0u, (lane & 1) ? v[0] : v[1], 1);
      };
      if (wid == 9) {
        const uint32_t a0 = sm + rb * 1024 + r2 * 128 + (((c16 >> 1) ^ r2) << 4) + (c16 & 1) * 8;
#pragma unroll 1
        for (int kb = 0; kb < 16 - NDIR; kb++) {
          uint2 w[12];
          const uint32_t so = a0 + woff(kb & 3);
          mbar_wait(mb + B_FULL + 8 * (kb & 3), (kb >> 2) & 1);
          static_for<0, 12>([&](auto ic) { constexpr int i = decltype(ic)::value;
            const float2 v = lds2f_o<(i >> 2) * WSTR + (i & 3) * 256>(so ^ ((i & 3) << 5)); w[i] = make_uint2(__float_as_uint(v.x), __float_as_uint(v.y)); });
          uint32_t done = 0;
#pragma unroll
          for (int i = 0; i < 12; i++) done |= w[i].y;
          if (lane < 2) mbar_arrive_rem(eb + 8 * (kb & 3) + (done & zero));
          add_w(w);
        }
        float c[6];
        red_w(c);
        bar_sync(5, 96);
#pragma unroll
        for (int i = 0; i < 3; i++) { const float2 v = lds2f(sm + OFF_STATS + 256 + i * 256 + lane * 8); c[i * 2] += v.x; c[i * 2 + 1] += v.y; }
        TS(6);
        const uint32_t tag = lds1(mb + B_SW + 4) & 255;
#pragma unroll
        for (int sg = 0; sg < 3; sg++) st_rlx2((uint2*)&G.csp[(cg * 8 + rb) * 48] + sg * 32 + c16 * 2 + r2, tagged(c[sg * 2], tag), tagged(c[sg * 2 + 1], tag));
      } else if (wid == 10) {
        const uint32_t xa = sm + (c3 * 16 + r4) * 128 + c8 * 16;
        const uint4* gx = (const uint4*)(P.x + (b * 16 + r4) * D_ + kl) + c8 - DIRX * 8;
#pragma unroll 1
        for (int kb = 0; kb < 12; kb++) {
          uint4 d[4], v[4];
          const bool direct = (unsigned)(kb - DIRX) < 4;
          if (direct) {
#pragma unroll
            for (int j = 0; j < 4; j++) d[j] = ld_cg4(gx + j * 512 + kb * 8);
          }
          const uint32_t so = xa + xoff(kb & 3, hf);
          mbar_wait(mb + B_FULL + 8 * (kb & 3), (kb >> 2) & 1);
          v[0] = lds4_o<0>(so); v[1] = lds4_o<512>(so); v[2] = lds4_o<1024>(so); v[3] = lds4_o<1536>(so);
          if (lane < 2) mbar_arrive_rem(eb + 8 * (kb & 3) + ((v[0].x | v[1].x | v[2].x | v[3].x) & zero));
#pragma unroll
          for (int j = 0; j < 4; j++) { add_x(j, v[j].x); add_x(j, v[j].y); add_x(j, v[j].z); add_x(j, v[j].w); }
          if (direct) {
#pragma unroll
            for (int j = 0; j < 4; j++) { add_x(j, d[j].x); add_x(j, d[j].y); add_x(j, d[j].z); add_x(j, d[j].w); }
          }
        }
        const float mean = red_x() * (1.f / D_);
        bar_sync(5, 96);
        const float var = fmaxf(fmaf(-mean, mean, __shfl_xor_sync(~0u, mean, 4)), 0.f);
        const uint32_t tag = lds1(mb + B_SW + 4) & 255;
        if (c8 < 4) st_rlx2((uint2*)G.st1 + (b >> 1) * 96 + rank * 16 + r4 + 4 * c8, tagged(-mean, tag), tagged(rsqrtf(var + 1e-5f), tag));
      } else {
        mbar_wait(mb + B_FULL + 8 * PFST, 0);
        if (elect_one()) {
#pragma unroll 1
          for (int i = 0; i < 32; i++) bulk_store(&G.obuf[((rb * 4 + (i >> 3)) * 64 + cg * 4) * 128 + (i & 7) * 64], sm + OFF_STATS, 1024);
#pragma unroll 1
          for (int i = 0; i < 5; i++) bulk_store(&G.kvp[cg * 2304 + rb * 288 + i * 64], sm + OFF_STATS, i < 4 ? 1024 : 512);
          asm volatile("cp.async.bulk.commit_group;" ::: "memory");
          tmap_prefetch(&tmO); tmap_prefetch(&tmG); tmap_prefetch(&tmU); tmap_prefetch(&tmD); tmap_prefetch(&tmPD); tmap_prefetch(&tmM);
        }
        __syncwarp();
#pragma unroll
        for (int i = 0; i < NDIR * DPF; i++) {
          if (lane < 24) l2_prefetch(P.wqkv + (k_of(16 - NDIR + i) + rb * 8 + (lane & 7)) * 3072 + (lane >> 3) * 1024 + cg * 64);
        }
        const uint32_t ep = ld_rlx(&G.epoch);
        float s = 0.f;
#pragma unroll
        for (int i = 0; i < 4; i++) {
          const uint4 v = ld_cg4((const uint4*)P.wr + lane + i * 32);
          s += (bf_lo(v.x) + bf_hi(v.x)) + (bf_lo(v.y) + bf_hi(v.y)) + (bf_lo(v.z) + bf_hi(v.z)) + (bf_lo(v.w) + bf_hi(v.w));
        }
#pragma unroll
        for (int o = 16; o; o >>= 1) s += __shfl_xor_sync(~0u, s, o);
        if (lane == 0) sts2f(mb + B_SW, s, __uint_as_float(ep + 1));
#pragma unroll 1
        for (int i = 0; i < NDIR; i++) {
          const uint2* gw = (const uint2*)(P.wqkv + (k_of(16 - NDIR + i) + rb * 8 + r2) * 3072 + cg * 64) + c16;
          uint2 w[12];
#pragma unroll
          for (int j = 0; j < 12; j++) w[j] = ld_rlx2(gw + (j >> 2) * 256 + (j & 3) * 1536);
          add_w(w);
        }
        float c[6];
        red_w(c);
        PTS(1);
        asm volatile("cp.async.bulk.wait_group 0;\nfence.proxy.async.global;" ::: "memory");
        __syncwarp();
        sts1(sm + OFF_STATS + lane * 4, 0);
#pragma unroll
        for (int i = 0; i < 3; i++) sts2f(sm + OFF_STATS + 256 + i * 256 + lane * 8, c[i * 2], c[i * 2 + 1]);
        fence_async_smem();
        fence_gpu();
        bar_arrive(5, 96); PTS(0);
        {
          const uint32_t m2 = pack2(s * (-1.f / D_), s * (-1.f / D_));
          const uint4* gx = (const uint4*)(P.x + (b * 16 + r2) * D_) + c16;
          uint32_t e[8];
#pragma unroll
          for (int j = 0; j < 8; j++) e[j] = 0;
#pragma unroll 1
          for (int r = 0; r < 128; r += 16) {
            uint4 v[8], w = ld_cg4((const uint4*)P.wr + c16 + r);
#pragma unroll
            for (int j = 0; j < 8; j++) v[j] = ld_cg4(gx + j * 256 + r);
            w = hadd8(w, make_uint4(m2, m2, m2, m2));
#pragma unroll
            for (int j = 0; j < 8; j++) e[j] = hfma2(v[j].x, w.x, hfma2(v[j].y, w.y, hfma2(v[j].z, w.z, hfma2(v[j].w, w.w, e[j]))));
          }
#pragma unroll
          for (int j = 0; j < 8; j++) a[j] = bf_lo(e[j]) + bf_hi(e[j]);
          float pd = red_x();
          pd += __shfl_xor_sync(~0u, pd, 8);
          if (!(lane & 8)) st_rlx(&G.pred[b * 16 + c8 * 2 + r2], (ordered(pd) & ~255u) | (lds1(mb + B_SW + 4) & 255));
          PTS(8);
        }
      }
      if (wid < 11) gather(lds1(mb + B_SW + 4) & 255);
      if (wid == 9) {
        TS(2);
        {
          const uint4 sv = make_uint4(SENT, SENT, SENT, SENT);
          uint4* y = &G.ybuf[b * NFFN * 4 + lane];
#pragma unroll
          for (int i = 0; i < 14; i++) y[i * 32] = sv;
          if (lane < 16) G.st2[b * 16 + lane] = make_uint4(0, 0, 0, 0);
          G.hsel[b * 64 + lane] = sv; G.hsel[b * 64 + 32 + lane] = sv;
          if (b < 8) { G.cand[b * 32 + lane] = SENT; G.cst[b * 32 + lane] = make_uint4(0, 0, 0, 0); }
          fence_gpu();
          __syncwarp();
          if (lane == 0) mbar_arrive(mb + B_LATE);
        }
        TS(3);
        TS_DUMP(2);
      } else if (wid == 10) {
        {
          mbar_wait(mb + B_FULL + 24, 1);
#pragma unroll 1
          for (int r = -4; r < (fidx >= 0 ? 16 : 0); r++) {
            l2_prefetch((r < 0 ? (const char*)P.wo + (b + 1) * 16384 : (const char*)P.wd + fidx * 65536) + r * 4096 + lane * 128);
            delay(clk(), PDT);
          }
          PTS(4);
        }
      }
      mbar_wait(mb + B_LATE, 0);
      if (wid == 9) {
        if (elect_one()) {
          mbar_expect_tx(mb + B_KVL, 36864);
          wait3(60);
          const uint32_t t0 = clk();
#pragma unroll 1
          for (int p = 0; p < 16; p++) {
            if (p == 2) {
              mbar_wait(mb + B_EMPTY, 1);
              delay(t0, KDELAY);
              bulk_load(sm + 10 * SLOT_B, &G.kvp[cg * 2304], SLOT_B, mb + B_KVL);
              bulk_load(sm + 12 * SLOT_B, &G.kvp[cg * 2304 + 1024], SLOT_B + 4096, mb + B_KVL);
              PTS(3);
            }
            const bool mix = (unsigned)(p - 1) < 8;
            const int c1 = mix ? ((p - 1) >> 1) * 16 : 0, c2 = mix ? (hf ^ 1) * 8 + ((p - 1) & 1) * 4 : chunk_of(p) * 4;
            const uint32_t d = sm + (uint32_t)((WO_SLOTS >> (4 * p)) & 15) * SLOT_B;
            if ((0xFC94 >> p) & 1) mbar_wait(p < 10 ? mb + B_EMPTY + 8 * (p >> 1) : sm + bar3(32) + 8 * (p - 9), p < 10);
            asm volatile("cp.async.bulk.tensor.4d.shared::cluster.global.mbarrier::complete_tx::bytes [%0], [%1, {0, %3, %4, %5}], [%2];"
                         :: "r"(d), "l"(mix ? &tmM : &tmO), "r"(mb + B_FULL3 + 8 * p), "r"(c1), "r"(c2), "r"(c3 * 2) : "memory");
            if (p >= 10) PTS(7 + p);
          }
          if (fidx >= 0) {
            mbar_expect_tx(mb + B_FULL, 65536);
#pragma unroll 1
            for (int i = 0; i < 8; i++) {
              const int f = (0x76325140 >> (4 * i)) & 15;
              const uint32_t d = sm + ((GU_SLOTS >> (4 * f)) & 15) * SLOT_B, fb = mb + (i < 4 ? B_FULL : B_FFN);
              mbar_wait(sm + bar3(32) + o3(7 + i - (i > 5)), 0);
              tma_2d(d, &tmG, fidx * 32, f * 128, fb, EFF);
              tma_2d(d + 8192, &tmU, fidx * 32, f * 128, fb, EFF);
              PTS(23 + i);
            }
#pragma unroll 1
            for (int i = 0; i < 4; i++) {
              mbar_wait(sm + bar3(32) + o3(13 + ((i + 1) >> 1)), 0);
              tma_3d(sm + ((0xD3C1 >> (4 * i)) & 15) * SLOT_B, &tmD, 0, fidx * 32, i * 4, mb + B_FFN + 8, EFF);
            }
          }
        }
      } else if (wid == 11) {
        const uint2 w = ld_rlx2((const uint2*)(P.wr + c3 * 128) + lane);
        wait3(36);
        sts1(sm + OFF_LNP + (lane & 1) * 128 + (lane >> 1) * 4, w.x); sts1(sm + OFF_LNP + (lane & 1) * 128 + 64 + (lane >> 1) * 4, w.y);
        if (lane < 16) sts1(sm + OFF_LNP + 256 + lane * 4, 0x3F803F80u);
        const uint32_t tag = lds1(mb + B_SW + 4) & 255;
        uint4 k;
        for (int it = 0;; it++) {
          k = ld_rlx4((const uint4*)&G.pred[rb * 256 + hf * 64 + r2 * 128] + c16);
          k.x ^= tag; k.y ^= tag; k.z ^= tag; k.w ^= tag;
          if (!__any_sync(~0u, (k.x | k.y | k.z | k.w) & 255)) break;
          SPINCHK(it, 13);
        }
        const uint2 ahead = top2(k.x | (lane * 4), k.y | (lane * 4 + 1), k.z | (lane * 4 + 2), k.w | (lane * 4 + 3));
        if (lane == 0) sts2f(sm + OFF_MSC + 8, __uint_as_float((ahead.x & 127) ^ NOSPEC), __uint_as_float((ahead.y & 127) ^ NOSPEC));
        __syncwarp();
        if (lane == 0) mbar_arrive(mb + B_FULL3 + 8 * 15);
      } else if (fidx >= 0 && elect_one()) {
#pragma unroll 1
        for (int i = 0; i < NPD; i++) { mbar_wait(sm + bar3(32) + o3(PD0 + i), 0); tma_2d(sm + OFF_COLSUM, &tmPD, 0, fidx * 256 + i * 32, mb + B_FFN, false); }
      }
    }
    __syncwarp();
    const float sw = __uint_as_float(lds1(mb + B_SW));
    const int rr = lane >> 4, row00 = rb * 256 + hf * 64;
    uint2 pick;
    if (wid == 8) {
      wait3(61);
      delay(clk(), SDELAY);
      uint4 v;
      int id;
      for (int it = 0;; it++) {
        v = ld_rlx4(&G.cst[jp * 32 + lane]);
        id = __float2int_rn(__uint_as_float(v.w));
        if (!__any_sync(~0u, (id & 15) != 8)) break;
        SPINCHK(it, 14);
      }
      float2 pr;
      const uint32_t k = route(v, sw, id >> 4, pr);
      pick.x = __reduce_max_sync(~0u, k); pick.y = __reduce_max_sync(~0u, k == pick.x ? 0 : k);
      if (k == pick.x || k == pick.y) sts4(sm + OFF_MSC + 16 + (k == pick.y) * 16, k, lane, __float_as_uint(pr.x), __float_as_uint(pr.y));
      __syncwarp();
      if (lane == 0) { mbar_arrive(mb + B_SEL); PTS(16); }
    } else if (wid == 9) {
      wait3(61);
      delay(clk(), LDELAY);
      uint4 v[4];
      for (int it = 0;; it++) {
#pragma unroll
        for (int i = 0; i < 4; i++) v[i] = ld_rlx4(&G.st2[row00 + (i >> 1) * 128 + (i & 1) * 32 + lane]);
        if (!__any_sync(~0u, (v[0].w & v[1].w & v[2].w & v[3].w) != 0x41000000u)) break;
        SPINCHK(it, 6);
      }
      uint32_t k[4];
#pragma unroll
      for (int i = 0; i < 4; i++) { float2 pr; k[i] = route(v[i], sw, row00 + (i >> 1) * 128 + (i & 1) * 32 + lane, pr); sts2f(sm + OFF_LNP + (i * 32 + lane) * 8, pr.x, pr.y); }
      const uint2 m = top2(k[0], k[1], k[2], k[3]);
      if (lane == 0) { st_rlx2(&G.cand[c3 * 32 + (rb * 2 + hf) * 2], m.x, m.y); sts2f(sm + OFF_MSC + 0, __uint_as_float(m.x), __uint_as_float(m.y)); }
      wait3(62);
      __syncwarp();
      if (lane == 0) { mbar_arrive(mb + B_OUT); PTS(12); }
      const int ca = 2047 - (((lane & 4) ? m.y : m.x) & 2047), ta = ((ca >> 1) & 64) + (ca & 63);
      uint32_t h0, h1, h2, h3;
      ldsm4_o<0>(sm + HST + ta * 256 + ((((lane & 3) * 4 + (lane >> 3)) ^ (ta & 7)) << 4), h0, h1, h2, h3);
      st_rlx4(&G.hsel[(32 + (rb * 2 + hf) * 2 + rr) * 128 + c3 * 16 + (lane & 15)], make_uint4(h0, h1, h2, h3));
    }
    mbar_wait(mb + B_OUT, 0);
    const float2 cf = lds2f(sm + OFF_MSC + 0);
    const int ca0 = ~__float_as_int(cf.x), ca1 = ~__float_as_int(cf.y), cand0 = ((ca0 >> 1) & 64) + (ca0 & 63), cand1 = ((ca1 >> 1) & 64) + (ca1 & 63);
    auto put_row = [&](int tr, const uint4& v, const float2& pr) {
      const float f = 1.f + pr.x, n = pr.y;
      *(uint4*)(P.out + (size_t)(row00 + tr + (tr & 64)) * D_ + c3 * 128 + (lane & 15) * 8) =
          make_uint4(pack2(fmaf(bf_lo(v.x), f, n), fmaf(bf_hi(v.x), f, n)), pack2(fmaf(bf_lo(v.y), f, n), fmaf(bf_hi(v.y), f, n)),
                     pack2(fmaf(bf_lo(v.z), f, n), fmaf(bf_hi(v.z), f, n)), pack2(fmaf(bf_lo(v.w), f, n), fmaf(bf_hi(v.w), f, n)));
    };
    if (wid == 8) {
      delay(clk(), CDELAY);
      uint32_t k;
      for (int it = 0;; it++) { k = ld_rlx(&G.cand[c3 * 32 + lane]); if (!__any_sync(~0u, k == SENT)) break; SPINCHK(it, 12); }
      const uint32_t m1 = __reduce_max_sync(~0u, k), m2 = __reduce_max_sync(~0u, k == m1 ? 0 : k);
      const uint32_t miss = ((m1 ^ pick.x) | (m2 ^ pick.y)) & 2047;
      if (miss && (k == m1 || k == m2)) {
        float2 pr;
        route(ld_rlx4(&G.st2[2047 - (k & 2047)]), sw, 0, pr);
        sts4(sm + OFF_MSC + 48 + (k == m2) * 16, k, 32 + lane, __float_as_uint(pr.x), __float_as_uint(pr.y));
      }
      if (lane == 0) sts1(sm + OFF_MSC + 80, miss);
      __syncwarp();
      if (lane == 0) { mbar_arrive(mb + B_SEL2); PTS(13); }
      const uint32_t kc = __float_as_uint(rr ? cf.y : cf.x);
      const int c = rr ? cand1 : cand0;
      if (kc != m1 && kc != m2) put_row(c, lds4(sm + HST + c * 256 + (((lane & 15) ^ (c & 7)) << 4)), lds2f(sm + OFF_LNP + c * 8));
    } else {
#pragma unroll 1
      for (int t0 = (11 - wid) * 8 + rr; t0 < 128 * !NOOUT; t0 += 24) {
        uint4 v[4];
        float2 pr[4];
        const uint32_t ad = sm + HST + t0 * 256 + (((lane & 15) ^ rr) << 4);
        static_for<0, 4>([&](auto ic) { constexpr int i = decltype(ic)::value; v[i] = lds4_o<i * 512>(ad ^ (i << 5)); pr[i] = lds2f_o<i * 16>(sm + OFF_LNP + t0 * 8); });
#pragma unroll
        for (int i = 0; i < 4; i++) if (t0 + 2 * i != cand0 && t0 + 2 * i != cand1) put_row(t0 + 2 * i, v[i], pr[i]);
        if (ODELAY) delay(clk(), ODELAY);
      }
      if (wid == 11 && lane == 0) PTS(31);
    }
  } else {
    asm volatile("setmaxnreg.inc.sync.aligned.u32 224;");
    const int t128 = tid & 127, warp = wid & 3, g = lane >> 2, t = lane & 3;
    const int mb3 = rb * 4 + wg * 2 + hf;
    uint32_t pq[2][16];
    float acc[64];
    {
      float acc0[96], acc1[96];
#pragma unroll
      for (int i = 0; i < 96; i++) { asm volatile("" : "=f"(acc0[i])); asm volatile("" : "=f"(acc1[i])); }
      const uint32_t xo0 = dlo(sb, 16) + hf * 512, xo1 = dlo(sb, 16) + (hf ^ 1) * 512;
      const uint32_t eb0 = (t128 << 24) + bars + B_EMPTY;
#pragma unroll 1
      for (int kb = 0; kb < 12; kb++) {
        const int s = kb & 3;
        mbar_wait(mb + B_FULL + 8 * s, (kb >> 2) & 1);
        if (LOCK) bar_sync(13, 256);
        if (kb == 0) TS(1);
        const uint32_t xs = xoff(s, wg) >> 4, ws = dlo(sb + woff(s), WSTR);
        pin(acc0); pin(acc1);
        wg_fence();
#pragma unroll
        for (int k = 0; k < 4; k++) {
          const uint64_t db = dsc<1024, 1>(ws + k * 128);
          const int sd = k == 0 ? kb : 1;
          wgmma_n192_ss<0, 1, 0>(acc0, dsc<1024, 1>(xs + xo0 + k * 2), db, sd);
          wgmma_n192_ss<0, 1, 0>(acc1, dsc<1024, 1>(xs + xo1 + k * 2), db, sd);
          if (k == RELK || k == 3) wg_commit();
          if (k == RELK) {
            wg_wait<1>();
            if (kb > 0 && t128 < 2) mbar_arrive_rem(eb0 + 8 * ((kb - 1) & 3));
          }
        }
        pin(acc0); pin(acc1);
      }
      float qa0[32], qa1[32], kv0[64], kv1[64];
#pragma unroll
      for (int i = 0; i < 96; i++) { if (i < 32) { qa0[i] = acc0[i]; qa1[i] = acc1[i]; } else { kv0[i - 32] = acc0[i]; kv1[i - 32] = acc1[i]; } }
      uint2 st[2][2];
      uint4 am;
      auto center = [&](float (&q)[32], float (&kv)[64], const uint2 (&v)[2]) {
        const uint32_t n0 = v[0].x & (t == 0 ? ~255u : 0u), n1 = v[1].x & (t == 0 ? ~255u : 0u);
        am = make_uint4(__byte_perm(n0, 0, 0x3232), __byte_perm(n1, 0, 0x3232),
                        __byte_perm(__float_as_uint(__uint_as_float(n0) - bf_hi(n0)), 0, 0x3232), __byte_perm(__float_as_uint(__uint_as_float(n1) - bf_hi(n1)), 0, 0x3232));
        wg_fence();
        wgmma_n64_rs<1, 0>(q, am.x, am.y, am.z, am.w, dsc<32, 0>(dlo(sb + OFF_COLSUM, 0)), 1);
        wgmma_n128_rs<1, 0>(kv, am.x, am.y, am.z, am.w, dsc<32, 0>(dlo(sb + OFF_COLSUM + 256, 0)), 1);
      };
      static_for<0, 4>([&](auto sc) {
        constexpr int s = decltype(sc)::value;
        if (wg || s < KLEAD - 12) mbar_wait(mb + B_FULL + 8 * s, 1);
        const uint32_t xs = (wg ? xoff(s, 1) : xoff(s, 0)) >> 4, ws = dlo(sb + woff(s) + WSTR, WSTR);
        pin(kv0); pin(kv1); pin(qa0); pin(qa1);
        wg_fence();
#pragma unroll
        for (int k = 0; k < 4; k++) {
          const uint64_t db = dsc<1024, 1>(ws + k * 128);
          wgmma_n128_ss<0, 1, 0>(kv0, dsc<1024, 1>(xs + xo0 + k * 2), db, 1);
          wgmma_n128_ss<0, 1, 0>(kv1, dsc<1024, 1>(xs + xo1 + k * 2), db, 1);
          if (k & 1) wg_commit();
          if (k == 1 && (s == 0 || (s == 2 && KLEAD == 13))) {
            wg_wait<1>();
            if (s == 0) { if (t128 < 2) mbar_arrive_rem(eb0 + 24); }
            else if (!wg) bar_arrive(10, 256);
          }
        }
        if (s == KLEAD - 13 && !wg) {
          wg_wait<0>();
          bar_arrive(9, 256);
#pragma unroll
          for (int k2 = KLEAD; k2 < 16; k2++) mbar_wait(mb + B_FULL + 8 * (k2 & 3), 1);
        }
        if (s == (wg ? STLD : KLEAD - 13)) {
          mbar_wait(mb + B_AUX, 0);
#pragma unroll
          for (int i = 0; i < 4; i++) st[i >> 1][i & 1] = ld_rlx2((const uint2*)G.st1 + ((rb * 4 + wg * 2 + ((i >> 1) ^ hf)) * 2 + (warp >> 1)) * 96 + (warp & 1) * 16 + (i & 1) * 8 + g);
        }
        if (s == KLEAD - 13 && !wg) bar_sync(6, 256);
      });
      center(qa0, kv0, st[0]);
      wg_commit();
      if (wg) bar_arrive(6, 256);
      float rl[2][2];
      uint32_t r2[2][2];
#pragma unroll
      for (int i = 0; i < 4; i++) { const float r = __uint_as_float(st[i >> 1][i & 1].y & ~255u); r2[i >> 1][i & 1] = pack2(r, r); rl[i >> 1][i & 1] = r * 1.4426950408889634f; }
      const uint32_t sad = sm + (wg ? 11 : 2) * SLOT_B + (warp * 16 + (lane & 15)) * 128 + (((lane >> 4) ^ (lane & 7)) << 4);
      wg_wait<0>();
      pin(kv0); pin(kv1); pin(qa0); pin(qa1); pin4(am);
      center(qa1, kv1, st[1]);
      wg_commit();
      if (wg) bar_arrive(11, 256);
      TS(2);
      bar_sync(wg ? 9 : 11, 256);
      auto phi8 = [&](const float* a, int m) {
        return make_uint4(phi2(a[0], a[1], r2[m][0], rl[m][0]), phi2(a[2], a[3], r2[m][1], rl[m][1]), phi2(a[4], a[5], r2[m][0], rl[m][0]), phi2(a[6], a[7], r2[m][1], rl[m][1]));
      };
      auto stage = [&](float (&a)[64], auto mc) {
        constexpr int m = decltype(mc)::value;
#pragma unroll
        for (int j = 0; j < 4; j++) {
          const int v = 32 + j * 8;
          const uint4 r = phi8(a + j * 8, m);
          stsm4_o<m * 8192>(sad ^ (j << 5), r.x, r.y, r.z, r.w);
          stsm4_o<WSTR + m * 8192>(sad ^ (j << 5), hmul2(pack2(a[v], a[v + 1]), r2[m][0]), hmul2(pack2(a[v + 2], a[v + 3]), r2[m][1]),
                                                   hmul2(pack2(a[v + 4], a[v + 5]), r2[m][0]), hmul2(pack2(a[v + 6], a[v + 7]), r2[m][1]));
        }
      };
      stage(kv0, std::integral_constant<int, 0>{});
      wg_wait<0>();
      pin(kv1); pin(qa1); pin4(am);
      if (wg && KLEAD == 13) bar_sync(10, 256);
      stage(kv1, std::integral_constant<int, 1>{});
      fence_async_smem();
      TS(3);
      if (!wg) bar_arrive(4, 256);
      else {
        float ka[36];
#pragma unroll
        for (int i = 0; i < 36; i++) asm volatile("" : "=f"(ka[i]));
        auto kv_mma = [&](auto ic) {
          constexpr int i = decltype(ic)::value;
          constexpr uint32_t o = sb + (i < 8 ? 11 : 2) * SLOT_B + (i & 7) * 2048;
          wgmma_n72_ss<1, 1, 0>(ka, dsc<1024, 1>(dlo(o, 8192)), dsc<1024, 1>(dlo(o + WSTR, sb + OFF_STATS - o - WSTR)), i);
        };
        mbar_wait(mb + B_LATE, 0);
        bar_sync(3, 128);
        wg_fence();
        static_for<0, 8>(kv_mma);
        wg_commit();
        uint4* dst = &G.kvp[cg * 2304 + rb * 32];
        bar_sync(4, 256);
        static_for<8, 16>(kv_mma);
        wg_commit();
        if (QHOLD == 1) bar_arrive(8, 256);
        wg_wait<0>();
        pin(ka);
        if (QHOLD == 2) bar_arrive(8, 256);
        TS(4);
        if (warp < 2) {
          st_rlx4(dst + warp * 512 + lane, make_uint4(pack2(ka[0], ka[1]), pack2(ka[4], ka[5]), pack2(ka[8], ka[9]), pack2(ka[12], ka[13])));
          st_rlx4(dst + warp * 512 + 256 + lane, make_uint4(pack2(ka[2], ka[3]), pack2(ka[6], ka[7]), pack2(ka[10], ka[11]), pack2(ka[14], ka[15])));
        } else {
          st_rlx4(dst + warp * 512 + lane, make_uint4(pack2(ka[16], ka[17]), pack2(ka[20], ka[21]), pack2(ka[24], ka[25]), pack2(ka[28], ka[29])));
          st_rlx4(dst + warp * 512 + 256 + lane, make_uint4(pack2(ka[18], ka[19]), pack2(ka[22], ka[23]), pack2(ka[26], ka[27]), pack2(ka[30], ka[31])));
        }
        st_rlx((uint32_t*)(dst + 2048) + t128, pack2(ka[32], ka[34]));
        if (QHOLD == 3) bar_arrive(8, 256);
        if (t128 == 0) mbar_arrive(sm + bar3(60));
      }
      TS(5);
      uint32_t xr[8][4], done = 0;
      {
        const uint32_t xa = sm + hf * 8192 + (warp * 16 + (lane & 15)) * 128 + (((lane >> 4) ^ (lane & 7)) << 4);
#pragma unroll
        for (int q = 0; q < 8; q++) { ldsm4_o<0>((xa ^ ((q & 3) << 5)) + xoff(rank * 2 + (q >> 2), wg), xr[q][0], xr[q][1], xr[q][2], xr[q][3]); done |= xr[q][3]; }
      }
      bar_sync(wg ? 7 : 8, 256 + (done & zero));
#pragma unroll 1
      for (int s = 0; s < 4; s++) {
        const uint32_t xs = xoff(s, wg) >> 4, ws = dlo(sb + woff(s), 8192);
        pin(qa0); pin(qa1);
        wg_fence();
#pragma unroll
        for (int k = 0; k < 4; k++) {
          const uint64_t db = dsc<1024, 1>(ws + k * 128);
          wgmma_n64_ss<0, 1, 0>(qa0, dsc<1024, 1>(xs + xo0 + k * 2), db, 1);
          wgmma_n64_ss<0, 1, 0>(qa1, dsc<1024, 1>(xs + xo1 + k * 2), db, 1);
        }
        wg_commit();
        if (s == 3 && !wg) bar_arrive(7, 256);
        wg_wait<1>();
        pin(qa0); pin(qa1);
        if (s == 2 && t128 == 0) mbar_arrive(mb + B_EMPTY + 16 * wg);
      }
      wg_wait<0>();
      pin(qa0); pin(qa1);
      if (t128 == 0) mbar_arrive(mb + B_EMPTY + 8 + 16 * wg);
      TS(29);
#pragma unroll
      for (int j = 0; j < 8; j++) {
        const uint4 r = phi8(j < 4 ? qa1 + j * 8 : qa0 + (j & 3) * 8, j < 4);
        uint32_t* q = pq[j < 4] + (j & 3) * 4;
        q[0] = r.x; q[1] = r.y; q[2] = r.z; q[3] = r.w;
      }
#pragma unroll
      for (int q = 0; q < 32; q++) { asm volatile("" : "+r"(xr[q >> 2][q & 3])); acc[q * 2] = bf_lo(xr[q >> 2][q & 3]); acc[q * 2 + 1] = bf_hi(xr[q >> 2][q & 3]); }
#pragma unroll
      for (int i = 0; i < 16; i++) asm volatile("" : "+r"(pq[0][i]), "+r"(pq[1][i]) :: "memory");
      pin(acc);
      TS(6);
      if (!wg) {
        uint4 a[2], v[2][8];
        uint32_t z[8], zs;
        const uint4* src = &G.kvp[cg * 2304 + warp * 512 + lane];
        const uint32_t* zsrc = (const uint32_t*)&G.kvp[cg * 2304 + 2048] + t128;
        mbar_wait(mb + B_KVL, 0);
        static_for<0, 16>([&](auto ic) { constexpr int i = decltype(ic)::value; v[i >> 3][i & 7] = lds4_o<sb + 10 * SLOT_B + i * 512>(own + (warp + (warp & 2)) * 8192 + lane * 16); });
#pragma unroll
        for (int i = 0; i < 8; i++) z[i] = lds1(sm + 13 * SLOT_B + i * 512 + t128 * 4);
#pragma unroll 1
        for (int it = 0;; it++) {
          zs = hadd2(hadd2(hadd2(z[0], z[1]), hadd2(z[2], z[3])), hadd2(hadd2(z[4], z[5]), hadd2(z[6], z[7])));
#pragma unroll
          for (int h = 0; h < 2; h++) a[h] = hadd8(hadd8(hadd8(v[h][0], v[h][1]), hadd8(v[h][2], v[h][3])), hadd8(hadd8(v[h][4], v[h][5]), hadd8(v[h][6], v[h][7])));
          const uint4 c = hadd8(a[0], a[1]);
          TSV(20, it + 1);
          if (!__any_sync(~0u, hnan(hadd2(hadd2(hadd2(c.x, c.y), hadd2(c.z, c.w)), zs)))) break;
          uint32_t mm = 0;
#pragma unroll
          for (int i = 0; i < 8; i++) {
            const uint32_t m = max4(max4(z[i], v[0][i]), v[1][i]);
            if (m == SENT) { v[0][i] = ld_rlx4(src + i * 32); v[1][i] = ld_rlx4(src + 256 + i * 32); z[i] = ld_rlx(zsrc + i * 128); }
            mm = max(mm, m);
          }
          if (!__any_sync(~0u, mm == SENT)) break;
          SPINCHK(it, 4);
        }
        TS(23);
        const uint32_t kb0 = sm + OFF_KVB + warp * 2048 + (lane & 7) * 128;
#pragma unroll
        for (int h = 0; h < 2; h++) stsm4(kb0 + h * 1024 + (((lane >> 3) ^ (lane & 7)) << 4), a[h].x, a[h].y, a[h].z, a[h].w);
        asm volatile("stmatrix.sync.aligned.m8n8.x2.shared.b16 [%0], {%1,%2};" :: "r"(kb0 + (lane & 8) * 128 + ((4 ^ (lane & 7)) << 4)), "r"(zs), "r"(zs >> 16) : "memory");
        fence_async_smem();
        bar_arrive(12, 256);
      }
      bar_sync(wg ? 12 : 2, wg ? 256 : 128);
    }
    TS(7);
    const int tid2 = __shfl_sync(~0u, tid, lane);
    {
    const int t128 = tid2 & 127, lane = tid2 & 31, g = lane >> 2, t = lane & 3;
    uint4 abuf[4][4], ost[2][4];
    uint4* const od0 = &G.obuf[(mb3 * 64 + cg * 4) * 128 + t128];
    uint4* const od1 = &G.obuf[((mb3 ^ 1) * 64 + hf * 32 + c3) * 128 + t128];
    uint32_t to;
    {
      float oa[4][20];
#pragma unroll
      for (int i = 0; i < 4; i++)
#pragma unroll
        for (int j = 0; j < 20; j++) oa[i][j] = 0.f;
#pragma unroll
      for (int i = 0; i < 4; i++) pin(oa[i]);
      wg_fence();
#pragma unroll
      for (int m = 1; m >= 0; m--) {
#pragma unroll
        for (int ks = 0; ks < 4; ks++)
          wgmma_n40_rs<1, 0>(oa[m * 2 + (ks >> 1)], pq[m][ks * 4], pq[m][ks * 4 + 1], pq[m][ks * 4 + 2], pq[m][ks * 4 + 3], dsc<1024, 1>(dlo(sb + OFF_KVB + ks * 2048, 8192)), 1);
      }
      wg_commit();
      wg_wait<0>();
#pragma unroll
      for (int i = 0; i < 4; i++) pin(oa[i]);
      if (lane >= wg && lane < 2) mbar_arrive_rem((lane << 24) + sb + bar3(48));
      to = clk();
#pragma unroll
      for (int m = 1; m >= 0; m--) {
#pragma unroll
        for (int h = 0; h < 2; h++) {
          const float (&d)[20] = oa[m * 2 + h];
          const float i0 = rcp(d[16] + 1e-6f), i1 = rcp(d[18] + 1e-6f);
#pragma unroll
          for (int k2 = 0; k2 < 2; k2++) {
            const uint4 v = make_uint4(pack2(d[k2 * 8] * i0, d[k2 * 8 + 1] * i0), pack2(d[k2 * 8 + 2] * i1, d[k2 * 8 + 3] * i1),
                                       pack2(d[k2 * 8 + 4] * i0, d[k2 * 8 + 5] * i0), pack2(d[k2 * 8 + 6] * i1, d[k2 * 8 + 7] * i1));
            ost[m][h * 2 + k2] = v;
            if (m == 1) { if (h * 2 + k2 < MIX) st_rlx4(od1 + (h * 2 + k2) * 1024, v); }
            else abuf[0][h * 2 + k2] = v;
          }
        }
      }
    }
    TS(8);
    {
      const uint32_t la = own + wg * 8192 + t128 * 16, fa = sm + wg * 256;
#pragma unroll
      for (int i = 4; i < 16; i++) abuf[i >> 2][i & 3] = make_uint4(0, 0, 0, 0);
#pragma unroll 1
      for (int pp = 0; pp < 16; pp += 4) {
        static_for<0, 4>([&](auto jc) {
          constexpr int j = decltype(jc)::value;
          constexpr uint32_t ro = sb + (10 + ((j + 1) & 3)) * SLOT_B;
          const int p = pp + j;
          const uint32_t o1 = ((p + 1) >> 3) * 128 + ((p + 1) & 7) * 8;
          uint4 (&a)[4] = abuf[j];
          uint4 (&n)[4] = abuf[(j + 1) & 3];
          auto fetch = [&]() {
            mbar_wait(fa + bar3(0) + o1, 0);
            n[0] = lds4_o<ro>(la); n[1] = lds4_o<ro + 2048>(la); n[2] = lds4_o<ro + 4096>(la); n[3] = lds4_o<ro + 6144>(la);
          };
          const bool early = j == 3 ? pp < 12 : (j > 0 || pp > 0);
          const uint32_t bs = dlo(sb, 8192) + ((WO_SLOTS >> (4 * p)) & 15) * (SLOT_B >> 4);
          mbar_wait(mb + B_FULL3 + 8 * p, 0);
          if (early) fetch();
          if (p == 1) TS(28);
          if (p == 2) TS(9);
          pin(acc);
          wg_fence();
#pragma unroll
          for (int k = 0; k < 4; k++) wgmma_n128_rs<1, 0>(acc, a[k].x, a[k].y, a[k].z, a[k].w, dsc<1024, 1>(bs + k * 128), 1);
          wg_commit();
          if (pp == 0) {
            if (j == 0) {
              delay(to, BDELAY);
#pragma unroll
              for (int k = MIX; k < 4; k++) st_rlx4(od1 + k * 1024, ost[1][k]);
            }
            if (j == ((jp >> 1) & 1) + W0OFF) {
#pragma unroll
              for (int k = 0; k < 4; k++) st_rlx4(od0 + k * 128, ost[0][k]);
            }
            if (j == 0) { TS(24); fetch(); TS(27); }
          }
          if (__any_sync(~0u, max(max4(max4(0, n[0]), n[1]), max4(max4(0, n[2]), n[3])) == SENT)) {
            int pl = p + 1; asm volatile("" : "+r"(pl));
            const uint4* q = &G.obuf[(mb3 * 64 + chunk_of(pl) * 4) * 128 + t128];
#pragma unroll 1
            for (int it = 0;; it++) {
#pragma unroll
              for (int i = 0; i < 4; i++) n[i] = ld_rlx4(q + i * 128);
              TSV(21, _ts + 1);
              if (!__any_sync(~0u, max(max4(max4(0, n[0]), n[1]), max4(max4(0, n[2]), n[3])) == SENT)) break;
              SPINCHK(it, 5);
            }
          }
          if (lane == 0 && p < 11) mbar_arrive_rem((wg << 24) + sb + bar3(48) + o1);
          wg_wait<1>();
          pin(acc);
#pragma unroll
          for (int i = 0; i < 4; i++) pin4(abuf[(j + 3) & 3][i]);
          if (lane == 0) mbar_arrive(sm + bar3(32) + (p >> 3) * 128 + (p & 7) * 8);
        });
      }
    }
    uint4 wb[4];
#pragma unroll
    for (int i = 0; i < 4; i++) wb[i] = lds4(sm + OFF_LNP + ((g & 1) ? t * 64 : 256) + i * 16);
    const float2 ah = lds2f(sm + OFF_MSC + 8);
    wg_wait<0>();
    pin(acc);
#pragma unroll
    for (int i = 0; i < 4; i++) pin4(abuf[3][i]);
    TS(10);
    const uint32_t msc = sm + OFF_MSC;
    uint32_t hp[8][4];
    {
      float se[2][4], q[4] = {0.f, 0.f, 0.f, 0.f};
#pragma unroll
      for (int i = 0; i < 8; i++) se[i >> 2][i & 3] = 0.f;
#pragma unroll
      for (int j = 0; j < 8; j++) {
#pragma unroll
        for (int i = 0; i < 4; i++) { const float a = acc[j * 8 + i * 2], c = acc[j * 8 + i * 2 + 1]; hp[j][i] = pack2(a, c); q[i] = fmaf(a, a, fmaf(c, c, q[i])); }
        mma16816(se[j & 1], hp[j], (j & 1) ? wb[j >> 1].z : wb[j >> 1].x, (j & 1) ? wb[j >> 1].w : wb[j >> 1].y);
      }
      const bool od = t & 1;
      const float q0 = q[0] + q[2], q1 = q[1] + q[3];
      float qq = (od ? q1 : q0) + __shfl_xor_sync(~0u, od ? q0 : q1, 1);
      qq += __shfl_xor_sync(~0u, qq, 2);
      const float ss = od ? se[0][2] + se[1][2] : se[0][0] + se[1][0], ee = od ? se[0][3] + se[1][3] : se[0][1] + se[1][1];
#pragma unroll 1
      for (int c = 0; c < 2; c++) {
        const int tr = __float_as_int(c ? ah.y : ah.x), slot = (rb * 2 + hf) * 2 + c;
        if ((tr >> 4) == wid) {
          const int sl = (tr & 7) * 4 + ((tr >> 3) & 1);
          const float s1 = __shfl_sync(~0u, ss, sl), s2 = __shfl_sync(~0u, qq, sl), s3 = __shfl_sync(~0u, ee, sl);
          red4(lane < 8, &G.cst[lane * 32 + slot], s1, s2, s3, c3 ? 1.f : (float)((mb3 * 64 + (tr & 63)) * 16 + 1));
          if (g == (tr & 7)) {
#pragma unroll
            for (int i = 0; i < 4; i++)
              st_rlx4(&G.hsel[slot * 128 + c3 * 16 + i * 4 + t], (tr & 8) ? make_uint4(hp[2 * i][1], hp[2 * i][3], hp[2 * i + 1][1], hp[2 * i + 1][3])
                                                                          : make_uint4(hp[2 * i][0], hp[2 * i][2], hp[2 * i + 1][0], hp[2 * i + 1][2]));
          }
        }
      }
      red4(t < 2, &G.st2[mb3 * 64 + warp * 16 + (t & 1) * 8 + g], ss, qq, ee, 1.f);
      if (lane == 0) mbar_arrive(sm + bar3(61));
      TS(11);
    }
    uint32_t wa[32][4], wd[8][2][4];
    const uint32_t ga = own + ((lane >> 3) & 1) * 8192 + ((lane >> 4) * 8 + (lane & 7)) * 64 + ((warp ^ ((lane >> 1) & 3)) << 4);
    const uint32_t dw = sm + ((0xD3C1 >> (2 * (wid & 6))) & 15) * SLOT_B + (wid & 1) * 8192;
    const uint32_t da = dw + ((lane >> 4) * 8 + (lane & 7)) * 128 + ((((lane >> 3) & 1) ^ (lane & 7)) << 4);
    const uint32_t xl = own + (wg ? 3 : 1) * SLOT_B + (lane & 7) * 16, xh = own + (wg ? 13 : 12) * SLOT_B + (lane & 7) * 16;
    float ya[8][4];
    int pass = 0;
    auto load_gu = [&](int f) {
      const uint32_t ad = ga + ((GU_SLOTS >> (16 * wg + 4 * f)) & 15) * SLOT_B;
      static_for<0, 8>([&](auto ic) { constexpr int i = decltype(ic)::value; ldsm4t_o<sb + i * 1024>(ad, wa[f * 8 + i]); });
    };
    if (fidx >= 0) mbar_wait(mb + B_FULL, 0);
    load_gu(0); load_gu(1);
    {
      bar_sync(1, 256);
      const uint32_t ha = sm + HST + wid * 4096 + (lane & 15) * 256 + (((lane >> 4) ^ (lane & 7)) << 4);
      static_for<0, 8>([&](auto jc) { constexpr int j = decltype(jc)::value; stsm4_o<(j >> 2) * 128>(ha ^ ((j & 3) << 5), hp[j][0], hp[j][1], hp[j][2], hp[j][3]); });
      asm volatile("fence.acq_rel.cta;" ::: "memory");
      __syncwarp();
      if (lane == 0) mbar_arrive(sm + bar3(62));
    }
    if (fidx >= 0) mbar_wait(mb + B_FFN, 1);
#pragma unroll 1
    for (;; pass++) {
      if (pass) { load_gu(0); load_gu(1); }
      load_gu(2);
      TS(15);
      mbar_wait(mb + B_SEL, 0);
      const uint4 sx = lds4(msc + 16 + pass * 32 + (lane & 16));
      TS(26);
      const uint4* xp = &G.hsel[sx.y * 128 + wid * 16 + (lane & 15)];
      uint4 xv = ld_rlx4(xp);
      load_gu(3);
      if (!pass) {
        if (fidx >= 0) mbar_wait(mb + B_FFN + 8, 0);
        static_for<0, 8>([&](auto ic) { constexpr int i = decltype(ic)::value; ldsm4t_o<(i & 1) * 2048>(da ^ ((i >> 1) << 5), wd[i >> 1][i & 1]); });
      }
#pragma unroll 1
      for (int it = 0; __any_sync(~0u, max4(0, xv) == SENT); it++) { xv = ld_rlx4(xp); SPINCHK(it, 7); }
      const float f = __uint_as_float(sx.z), n = __uint_as_float(sx.w);
      sts4(dw + ((lane & 12) * 2 + (lane >> 4) * 4 + t) * 16, pack2(fmaf(bf_lo(xv.x), f, n), fmaf(bf_hi(xv.x), f, n)), pack2(fmaf(bf_lo(xv.y), f, n), fmaf(bf_hi(xv.y), f, n)),
           pack2(fmaf(bf_lo(xv.z), f, n), fmaf(bf_hi(xv.z), f, n)), pack2(fmaf(bf_lo(xv.w), f, n), fmaf(bf_hi(xv.w), f, n)));
      if (wid == rb && (g & 3) == (cg >> 2)) sts4(msc + 96 + (lane >> 4) * 16 + t * 32, xv.x, xv.y, xv.z, xv.w);
      bar_sync(2 + wg, 128);
      TS(14);
      float gu[4][4];
#pragma unroll
      for (int i = 0; i < 16; i++) gu[i >> 2][i & 3] = 0.f;
      static_for<0, 16>([&](auto ic) {
        constexpr int i = decltype(ic)::value;
        uint4 xb = lds4_o<sb + ((i >> 2) & 1) * 8192 + (i & 3) * 128>(i < 8 ? xl : xh);
        if (i == 13) {
#pragma unroll
          for (int j = 0; j < 8; j++) xb.x |= wd[4 + (j >> 1)][j & 1][3] & zero;
        }
        mma16816(gu[(i & 1) * 2], wa[i * 2], xb.x, xb.y);
        mma16816(gu[(i & 1) * 2 + 1], wa[i * 2 + 1], xb.z, xb.w);
        if (i == 6) static_for<0, 8>([&](auto jc) { constexpr int j = decltype(jc)::value; ldsm4t_o<4096 + (j & 1) * 2048>(da ^ ((j >> 1) << 5), wd[4 + (j >> 1)][j & 1]); });
      });
      if (t == 0) sts4(sm + (wg ? 3 : 1) * SLOT_B + 1024 + (warp * 8 + g) * 16, __float_as_uint((gu[0][0] + gu[1][0]) + (gu[2][0] + gu[3][0])), __float_as_uint((gu[0][1] + gu[1][1]) + (gu[2][1] + gu[3][1])),
                       __float_as_uint((gu[0][2] + gu[1][2]) + (gu[2][2] + gu[3][2])), __float_as_uint((gu[0][3] + gu[1][3]) + (gu[2][3] + gu[3][3])));
      TS(25);
      bar_sync(1, 256);
      const uint4 p0 = lds4_o<sb + SLOT_B + 1024>(own + lane * 16), p1 = lds4_o<sb + 3 * SLOT_B + 1024>(own + lane * 16);
      const float g0 = __uint_as_float(p0.x) + __uint_as_float(p1.x), g1 = __uint_as_float(p0.y) + __uint_as_float(p1.y);
      const float u0 = __uint_as_float(p0.z) + __uint_as_float(p1.z), u1 = __uint_as_float(p0.w) + __uint_as_float(p1.w);
      const uint32_t act = pack2(g0 * rcp(1.f + ex2(-1.4426950408889634f * g0)) * u0, g1 * rcp(1.f + ex2(-1.4426950408889634f * g1)) * u1);
      uint32_t bq[4];
#pragma unroll
      for (int i = 0; i < 4; i++) {
        const uint32_t lo = __shfl_sync(~0u, act, i * 8 + 2 * t), hi = __shfl_sync(~0u, act, i * 8 + 2 * t + 1);
        bq[i] = __byte_perm(lo, hi, (g & 1) ? 0x7632 : 0x5410);
      }
      TS(16);
#pragma unroll
      for (int i = 0; i < 8; i++) { ya[i][0] = 0.f; ya[i][1] = 0.f; ya[i][2] = 0.f; ya[i][3] = 0.f; }
#pragma unroll
      for (int ks = 0; ks < 2; ks++)
#pragma unroll
        for (int i = 0; i < 8; i++) mma16816(ya[i], wd[i][ks], bq[ks * 2], bq[ks * 2 + 1]);
      mbar_wait(mb + B_SEL2, 0);
      if (pass || !lds1(msc + 80)) break;
      bar_sync(1, 256);
    }
    if (fidx >= 0) {
      uint2* const yp = (uint2*)&G.ybuf[((wid * 16 + t * 2) * NFFN + fidx) * 4] + g;
#pragma unroll
      for (int h = 0; h < 2; h++) {
        float o[4];
#pragma unroll
        for (int j = 0; j < 4; j++) o[j] = t == 0 ? ya[h * 4][j] : t == 1 ? ya[h * 4 + 1][j] : t == 2 ? ya[h * 4 + 2][j] : ya[h * 4 + 3][j];
        st_rlx2(yp + h * (8 * NFFN * 8), __float_as_uint(o[0]), __float_as_uint(o[1]));
        st_rlx2(yp + h * (8 * NFFN * 8) + NFFN * 8, __float_as_uint(o[2]), __float_as_uint(o[3]));
      }
    }
    TS(17);
    const uint32_t ty = clk();
    if (wid < 7) {
      const uint4* const yq = &G.ybuf[b * NFFN * 4 + wid * 64 + lane];
      const uint4 sel = lds4(msc + 16 + pass * 32 + (lane & 1) * 16);
      const uint32_t fh = lds1(msc + 96 + (lane & 1) * 16 + (g & 3) * 32 + (cg & 3) * 4);
      const float r = __uint_as_float(sel.x ^ (~(uint32_t)((int)sel.x >> 31) | 0x80000000u));
      float sg = rcp(1.f + ex2(-1.4426950408889634f * r)), base = fmaf((lane & 2) ? bf_hi(fh) : bf_lo(fh), 1.f + __uint_as_float(sel.z), __uint_as_float(sel.w));
      __nv_bfloat16* op = P.out + (size_t)(2047 - (sel.x & 2047)) * D_ + b * 8 + ((lane >> 1) & 7);
      asm volatile("" : "+f"(sg), "+f"(base), "+l"(op) :: "memory");
      delay(ty, YDELAY);
      uint4 v0, v1;
#pragma unroll 1
      for (int it = 0;; it++) {
        v0 = ld_rlx4(yq); v1 = ld_rlx4(yq + 32);
        TSV(22, it + 1);
        if (!__any_sync(~0u, max(max4(0, v0), max4(0, v1)) == SENT)) break;
        SPINCHK(it, 8);
      }
      TS(18);
      float y0 = __uint_as_float(v0.x) + __uint_as_float(v1.x), y1 = __uint_as_float(v0.y) + __uint_as_float(v1.y);
      float y2 = __uint_as_float(v0.z) + __uint_as_float(v1.z), y3 = __uint_as_float(v0.w) + __uint_as_float(v1.w);
      float z0 = ((lane & 16) ? y2 : y0) + __shfl_xor_sync(~0u, (lane & 16) ? y0 : y2, 16), z1 = ((lane & 16) ? y3 : y1) + __shfl_xor_sync(~0u, (lane & 16) ? y1 : y3, 16);
      z0 = ((lane & 8) ? z1 : z0) + __shfl_xor_sync(~0u, (lane & 8) ? z0 : z1, 8);
      z0 += __shfl_xor_sync(~0u, z0, 4);
      const uint32_t yx = sm + OFF_COLSUM;
      if (!(lane & 4)) sts1(yx + (t * 4 + (lane >> 3)) * 32 + wid * 4, __float_as_uint(z0));
      if (wid) bar_arrive(1, 224);
      else {
        bar_sync(1, 224);
        const uint4 a = lds4(yx + (lane & 15) * 32), c = lds4(yx + (lane & 15) * 32 + 16);
        const float y = ((__uint_as_float(a.x) + __uint_as_float(a.y)) + (__uint_as_float(a.z) + __uint_as_float(a.w))) + ((__uint_as_float(c.x) + __uint_as_float(c.y)) + __uint_as_float(c.z));
        if (lane < 16) *op = __float2bfloat16(fmaf(y, sg, base));
        if (b == 0 && lane == 16) G.epoch = lds1(mb + B_SW + 4);
      }
    }
    }
    TS(19); TSG(31);
    if (warp == 0) TS_DUMP(wg);
  }
}

typedef CUresult (*EncodeFn)(CUtensorMap*, CUtensorMapDataType, cuuint32_t, void*, const cuuint64_t*, const cuuint64_t*, const cuuint32_t*,
                             const cuuint32_t*, CUtensorMapInterleave, CUtensorMapSwizzle, CUtensorMapL2promotion, CUtensorMapFloatOOBfill);
void make_map(EncodeFn enc, CUtensorMap* m, const void* p, uint64_t cols, uint64_t rows, uint64_t d0, uint32_t b0, uint32_t b1, uint32_t b2, CUtensorMapSwizzle sw,
              CUtensorMapL2promotion promo = CU_TENSOR_MAP_L2_PROMOTION_L2_128B) {
  cuuint64_t dims[3] = {d0, rows, cols / d0}, str[2] = {cols * 2, d0 * 2};
  cuuint32_t box[3] = {b0, b1, b2}, es[3] = {1, 1, 1};
  enc(m, CU_TENSOR_MAP_DATA_TYPE_BFLOAT16, b2 ? 3 : 2, const_cast<void*>(p), dims, str, box, es, CU_TENSOR_MAP_INTERLEAVE_NONE, sw,
      promo, CU_TENSOR_MAP_FLOAT_OOB_FILL_NONE);
}

}

extern "C" void kernel_launch(void* const* d_in, const int* in_sizes, int n_in, void* d_out, int out_size) {
  (void)in_sizes; (void)n_in; (void)out_size;
  Ptrs P;
  P.x = (const __nv_bfloat16*)d_in[0]; P.wqkv = (const __nv_bfloat16*)d_in[1]; P.wo = (const __nv_bfloat16*)d_in[2];
  P.wr = (const __nv_bfloat16*)d_in[4]; P.wg = (const __nv_bfloat16*)d_in[5]; P.wu = (const __nv_bfloat16*)d_in[6];
  P.wd = (const __nv_bfloat16*)d_in[7]; P.out = (__nv_bfloat16*)d_out;
  void* fn = nullptr;
  cudaDriverEntryPointQueryResult q;
  cudaGetDriverEntryPoint("cuTensorMapEncodeTiled", &fn, cudaEnableDefault, &q);
  EncodeFn enc = (EncodeFn)fn;
  CUtensorMap tmX, tmW, tmO, tmG, tmU, tmD, tmM, tmPG, tmPU, tmPD;
  make_map(enc, &tmX, P.x, D_, S_, D_, 64, 128, 0, CU_TENSOR_MAP_SWIZZLE_128B);
  make_map(enc, &tmW, P.wqkv, 3 * D_, D_, 3 * D_, 64, 64, 0, CU_TENSOR_MAP_SWIZZLE_128B);
  make_map(enc, &tmG, P.wg, F_, D_, F_, 32, 128, 0, CU_TENSOR_MAP_SWIZZLE_64B);
  make_map(enc, &tmU, P.wu, F_, D_, F_, 32, 128, 0, CU_TENSOR_MAP_SWIZZLE_64B);
  make_map(enc, &tmD, P.wd, D_, F_, 64, 64, 32, 4, CU_TENSOR_MAP_SWIZZLE_128B);
  make_map(enc, &tmPG, P.wg, F_, D_, F_, 8, 32, 0, CU_TENSOR_MAP_SWIZZLE_NONE);
  make_map(enc, &tmPU, P.wu, F_, D_, F_, 8, 32, 0, CU_TENSOR_MAP_SWIZZLE_NONE);
  make_map(enc, &tmPD, P.wd, 128, F_ * 8, 128, 8, 32, 0, CU_TENSOR_MAP_SWIZZLE_NONE, CU_TENSOR_MAP_L2_PROMOTION_L2_256B);
  for (int m = 0; m < 2; m++) {
    cuuint64_t dims[4] = {64, m ? 64u : 16u, m ? 16u : 64u, 16}, str[3] = {2 * D_, (m ? 128u : 32u) * D_, 128};
    cuuint32_t box[4] = {64, 16, 4, 2}, es[4] = {1, 1, 1, 1};
    enc(m ? &tmM : &tmO, CU_TENSOR_MAP_DATA_TYPE_BFLOAT16, 4, const_cast<__nv_bfloat16*>(P.wo), dims, str, box, es, CU_TENSOR_MAP_INTERLEAVE_NONE,
        CU_TENSOR_MAP_SWIZZLE_128B, CU_TENSOR_MAP_L2_PROMOTION_L2_128B, CU_TENSOR_MAP_FLOAT_OOB_FILL_NONE);
  }
  cudaFuncSetAttribute(fused_kernel, cudaFuncAttributeMaxDynamicSharedMemorySize, SMEM_BYTES);
  fused_kernel<<<NCTA, 384, SMEM_BYTES>>>(tmX, tmW, tmO, tmG, tmU, tmD, tmM, tmPG, tmPU, tmPD, P);
}
```

```cpp
#include <cuda_runtime.h>
#include <cuda.h>
#include <cuda_bf16.h>
#include <stdint.h>
#include <type_traits>

namespace {

constexpr int S_ = 2048, D_ = 1024, F_ = 3584;
constexpr int NCTA = 128, NFFN = 112;
constexpr uint32_t SENT = 0xFFFFFFFFu;
constexpr int SPIN_LIMIT = 1 << 20;

#define ADELAY 500
#define NPK 0x233333333333ull
#define KDELAY 800
#define SBAR 2
#define BDELAY 1500
#define NOOUT 0
#define OHOLD 72
#define OUTEF 0
#define CUTS 7
#define EFO 0
#define EFWO 0
#define TMPF 1
#define INIF 0
#define PD0 2
#define NPD 8
#define PDT 100
#define KORD 0xBA9F87E6D54C3210ull
#define SDELAY 450
#define LDELAY 500
#define NOSPEC 0
#define LOCK 1
#define STLD 2
#define RELK 1
#define PERT 1
#define QHOLD 1
#define CDELAY 0
#define YDELAY 500
#define EFX 0
#define EFW 1
#define EFF 1
#define GDELAY 800
#define PFST 1
#define W0OFF 1
constexpr uint32_t STAGE_B = 57344;
__host__ __device__ constexpr uint32_t xoff(int s, int w) { return ((0x86CA5731u >> (4 * (s + 4 * w))) & 15) * 16384; }
__host__ __device__ constexpr uint32_t woff(int s) { return (s < 2 ? 9 * 16384 : 0) + (s & 1) * 8192; }
constexpr uint32_t WSTR = 32768;
constexpr uint32_t OFF_BARS = 229376;
constexpr uint32_t OFF_COLSUM = 229632;
constexpr uint32_t OFF_STATS = 230400;
constexpr uint32_t SMEM_BYTES = 232448;
constexpr uint32_t B_FULL = 0, B_EMPTY = 32, B_AUX = 64, B_SEL2 = 72, B_KVL = 80, B_FULL3 = 88, B_SW = 216, B_OUT = 224, B_LATE = 232, B_SEL = B_FULL + 8, B_FFN = 240;
__host__ __device__ constexpr uint32_t o3(int p) { return p * 8 + (p & 8) * 8; }
__host__ __device__ constexpr uint32_t bar3(int i) { return OFF_STATS + 1024 + (i >> 3) * 128 + ((i & 32) ? 0 : 64) + (i & 7) * 8; }
constexpr uint32_t SLOT_B = 16384;
constexpr uint32_t sb = 1024;
constexpr uint32_t bars = sb + OFF_BARS;
constexpr uint64_t WO_SLOTS = 0x6573142098657314ull;
constexpr uint32_t GU_SLOTS = 0xBA291408u, D_SLOTS = 0xD7C3;
constexpr uint32_t HST = 5 * SLOT_B;
constexpr uint32_t OFF_LNP = OFF_STATS;
constexpr uint32_t OFF_MSC = OFF_COLSUM + 512;
constexpr uint32_t OFF_KVB = 2 * SLOT_B + 8192;

struct Scratch {
  uint4 st1[64 * 48];
  uint4 csp[16 * 8 * 48];
  uint4 kvp[16 * 2304];
  uint4 obuf[32 * 64 * 128];
  uint4 st2[S_];
  uint32_t pred[S_];
  uint4 cst[8 * 32];
  uint4 hsel[64 * 128];
  uint32_t cand[8 * 32];
  uint4 ybuf[NCTA * NFFN * 4];
  unsigned epoch;
};
__device__ __align__(1024) Scratch G;
#define TS_DECL
#define TS(i)
#define TSG(i)
#define TSV(i, v)
#define TS_DUMP(slot)
#define PTS(i)

__device__ __forceinline__ uint32_t smem_u32(const void* p) { return (uint32_t)__cvta_generic_to_shared(p); }
__device__ __forceinline__ void mbar_init(uint32_t bar, uint32_t cnt) { asm volatile("mbarrier.init.shared::cta.b64 [%0], %1;" :: "r"(bar), "r"(cnt) : "memory"); }
__device__ __forceinline__ void mbar_expect_tx(uint32_t bar, uint32_t bytes) { asm volatile("mbarrier.arrive.expect_tx.shared::cta.b64 _, [%0], %1;" :: "r"(bar), "r"(bytes) : "memory"); }
__device__ __forceinline__ void mbar_arrive(uint32_t bar) { asm volatile("mbarrier.arrive.shared::cta.b64 _, [%0];" :: "r"(bar) : "memory"); }
#define SPINCHK(it, code) if ((it) > SPIN_LIMIT) break
__device__ __forceinline__ void mbar_wait(uint32_t bar, uint32_t parity) {
  asm volatile("{\n.reg .pred p;\n.reg .u32 c;\nmov.u32 c, 0;\n"
               "WL:\nmbarrier.try_wait.parity.shared::cta.b64 p, [%0], %1;\n@p bra WD;\n"
               "add.u32 c, c, 1;\nsetp.lt.u32 p, c, 1048576;\n@p bra WL;\nWD:\n}" :: "r"(bar), "r"(parity) : "memory");
}
__device__ __forceinline__ uint64_t l2_stream() { uint64_t p; asm("createpolicy.fractional.L2::evict_first.b64 %0, 1.0;" : "=l"(p)); return p; }
__device__ __forceinline__ void tma_2d(uint32_t dst, const CUtensorMap* tm, int c0, int c1, uint32_t bar, bool stream) {
  if (stream) asm volatile("cp.async.bulk.tensor.2d.shared::cluster.global.mbarrier::complete_tx::bytes.L2::cache_hint [%0], [%1, {%3, %4}], [%2], %5;"
                           :: "r"(dst), "l"(tm), "r"(bar), "r"(c0), "r"(c1), "l"(l2_stream()) : "memory");
  else asm volatile("cp.async.bulk.tensor.2d.shared::cluster.global.mbarrier::complete_tx::bytes [%0], [%1, {%3, %4}], [%2];"
                    :: "r"(dst), "l"(tm), "r"(bar), "r"(c0), "r"(c1) : "memory");
}
__device__ __forceinline__ void tma_3d(uint32_t dst, const CUtensorMap* tm, int c0, int c1, int c2, uint32_t bar, bool stream) {
  if (stream) asm volatile("cp.async.bulk.tensor.3d.shared::cluster.global.mbarrier::complete_tx::bytes.L2::cache_hint [%0], [%1, {%3, %4, %5}], [%2], %6;"
                           :: "r"(dst), "l"(tm), "r"(bar), "r"(c0), "r"(c1), "r"(c2), "l"(l2_stream()) : "memory");
  else asm volatile("cp.async.bulk.tensor.3d.shared::cluster.global.mbarrier::complete_tx::bytes [%0], [%1, {%3, %4, %5}], [%2];"
                    :: "r"(dst), "l"(tm), "r"(bar), "r"(c0), "r"(c1), "r"(c2) : "memory");
}
__device__ __forceinline__ void tma_2d_mc(uint32_t dst, const CUtensorMap* tm, int c0, int c1, uint32_t bar, bool stream) {
  if (stream) asm volatile("cp.async.bulk.tensor.2d.shared::cluster.global.mbarrier::complete_tx::bytes.multicast::cluster.L2::cache_hint [%0], [%1, {%3, %4}], [%2], %5, %6;"
                           :: "r"(dst), "l"(tm), "r"(bar), "r"(c0), "r"(c1), "h"((uint16_t)3), "l"(l2_stream()) : "memory");
  else asm volatile("cp.async.bulk.tensor.2d.shared::cluster.global.mbarrier::complete_tx::bytes.multicast::cluster [%0], [%1, {%3, %4}], [%2], %5;"
                    :: "r"(dst), "l"(tm), "r"(bar), "r"(c0), "r"(c1), "h"((uint16_t)3) : "memory");
}
__device__ __forceinline__ bool elect_one() {
  uint32_t p;
  asm volatile("{\n.reg .pred q;\nelect.sync _|q, 0xFFFFFFFF;\nselp.u32 %0, 1, 0, q;\n}" : "=r"(p));
  return p;
}
__device__ __forceinline__ void bulk_load_mc(uint32_t dst, const void* src, uint32_t bar, uint16_t mask) {
  if (EFO) asm volatile("cp.async.bulk.shared::cluster.global.mbarrier::complete_tx::bytes.multicast::cluster.L2::cache_hint [%0], [%1], 8192, [%2], %3, %4;"
               :: "r"(dst), "l"(src), "r"(bar), "h"(mask), "l"(l2_stream()) : "memory");
  else asm volatile("cp.async.bulk.shared::cluster.global.mbarrier::complete_tx::bytes.multicast::cluster [%0], [%1], 8192, [%2], %3;"
               :: "r"(dst), "l"(src), "r"(bar), "h"(mask) : "memory");
}
__device__ __forceinline__ void bulk_load(uint32_t dst, const void* src, uint32_t bytes, uint32_t bar) {
  asm volatile("cp.async.bulk.shared::cluster.global.mbarrier::complete_tx::bytes [%0], [%1], %2, [%3];" :: "r"(dst), "l"(src), "r"(bytes), "r"(bar) : "memory");
}
__device__ __forceinline__ void mbar_arrive_rem(uint32_t bar) { asm volatile("mbarrier.arrive.shared::cluster.b64 _, [%0];" :: "r"(bar) : "memory"); }
template <uint32_t O> __device__ __forceinline__ void ldsm4_o(uint32_t addr, uint32_t& a, uint32_t& b, uint32_t& c, uint32_t& d) {
  asm volatile("ldmatrix.sync.aligned.m8n8.x4.shared.b16 {%0,%1,%2,%3}, [%4+%5];" : "=r"(a), "=r"(b), "=r"(c), "=r"(d) : "r"(addr), "n"(O) : "memory");
}
template <uint32_t O> __device__ __forceinline__ void ldsm4t_o(uint32_t addr, uint32_t (&r)[4]) {
  asm volatile("ldmatrix.sync.aligned.m8n8.x4.trans.shared.b16 {%0,%1,%2,%3}, [%4+%5];" : "=r"(r[0]), "=r"(r[1]), "=r"(r[2]), "=r"(r[3]) : "r"(addr), "n"(O) : "memory");
}
__device__ __forceinline__ void mma16816(float (&c)[4], const uint32_t (&a)[4], uint32_t b0, uint32_t b1) {
  asm("mma.sync.aligned.m16n8k16.row.col.f32.bf16.bf16.f32 {%0,%1,%2,%3}, {%4,%5,%6,%7}, {%8,%9}, {%0,%1,%2,%3};"
      : "+f"(c[0]), "+f"(c[1]), "+f"(c[2]), "+f"(c[3]) : "r"(a[0]), "r"(a[1]), "r"(a[2]), "r"(a[3]), "r"(b0), "r"(b1));
}
__device__ __forceinline__ void l2_prefetch(const void* p) { asm volatile("prefetch.global.L2 [%0];" :: "l"(p) : "memory"); }
__device__ __forceinline__ uint32_t clk() { uint32_t t; asm volatile("mov.u32 %0, %%clock;" : "=r"(t) :: "memory"); return t; }
__device__ __forceinline__ void delay(uint32_t t0, uint32_t n) { while (clk() - t0 < n) {} }
__device__ __forceinline__ void cut(uint32_t zero) { asm volatile("{\n.reg .pred p;\nsetp.ne.u32 p, %0, 0;\nCUT:\n@p bra.uni CUT;\n}" :: "r"(zero) : "memory"); }
__device__ __forceinline__ void tmap_prefetch(const CUtensorMap* tm) { asm volatile("prefetch.tensormap [%0];" :: "l"(tm) : "memory"); }
__device__ __forceinline__ void wg_fence() { asm volatile("wgmma.fence.sync.aligned;" ::: "memory"); }
__device__ __forceinline__ void wg_commit() { asm volatile("wgmma.commit_group.sync.aligned;" ::: "memory"); }
template <int N> __device__ __forceinline__ void wg_wait() { asm volatile("wgmma.wait_group.sync.aligned %0;" :: "n"(N) : "memory"); }
template <int N> __device__ __forceinline__ void pin(float (&d)[N]) {
#pragma unroll
  for (int i = 0; i < N; i++) asm volatile("" : "+f"(d[i]) :: "memory");
}
__device__ __forceinline__ void pin4(uint4& v) { asm volatile("" : "+r"(v.x), "+r"(v.y), "+r"(v.z), "+r"(v.w) :: "memory"); }
template <uint32_t SBO, uint32_t SWZ> __device__ __forceinline__ uint64_t dsc(uint32_t lo) { return ((uint64_t)((SBO >> 4) | (SWZ << 30)) << 32) | lo; }
__host__ __device__ constexpr uint32_t dlo(uint32_t addr, uint32_t lbo) { return (addr >> 4) | ((lbo >> 4) << 16); }
__device__ __forceinline__ void bar_sync(int id, int n) { asm volatile("bar.sync %0, %1;" :: "r"(id), "r"(n) : "memory"); }
__device__ __forceinline__ void bar_arrive(int id, int n) { asm volatile("bar.arrive %0, %1;" :: "r"(id), "r"(n) : "memory"); }
__device__ __forceinline__ void fence_async_smem() { asm volatile("fence.proxy.async.shared::cta;" ::: "memory"); }
__device__ __forceinline__ void fence_gpu() { asm volatile("fence.acq_rel.gpu;" ::: "memory"); }
__device__ __forceinline__ uint4 ld_cg4(const void* p) { uint4 v; asm volatile("ld.global.cg.v4.u32 {%0,%1,%2,%3}, [%4];" : "=r"(v.x), "=r"(v.y), "=r"(v.z), "=r"(v.w) : "l"(p) : "memory"); return v; }
__device__ __forceinline__ uint4 ld_rlx4(const void* p) { uint4 v; asm volatile("ld.relaxed.gpu.global.v4.u32 {%0,%1,%2,%3}, [%4];" : "=r"(v.x), "=r"(v.y), "=r"(v.z), "=r"(v.w) : "l"(p) : "memory"); return v; }
__device__ __forceinline__ uint32_t ld_rlx(const void* p) { uint32_t v; asm volatile("ld.relaxed.gpu.global.u32 %0, [%1];" : "=r"(v) : "l"(p) : "memory"); return v; }
__device__ __forceinline__ void st_rlx4(void* p, uint4 v) { asm volatile("st.relaxed.gpu.global.v4.u32 [%0], {%1,%2,%3,%4};" :: "l"(p), "r"(v.x), "r"(v.y), "r"(v.z), "r"(v.w) : "memory"); }
__device__ __forceinline__ void st_rlx2(void* p, uint32_t a, uint32_t b) { asm volatile("st.relaxed.gpu.global.v2.u32 [%0], {%1,%2};" :: "l"(p), "r"(a), "r"(b) : "memory"); }
__device__ __forceinline__ void st_rlx(void* p, uint32_t a) { asm volatile("st.relaxed.gpu.global.u32 [%0], %1;" :: "l"(p), "r"(a) : "memory"); }
__device__ __forceinline__ void red4(bool on, void* p, float a, float b, float c, float d) {
  asm volatile("{\n.reg .pred q;\nsetp.ne.b32 q, %5, 0;\n@q red.relaxed.gpu.global.add.v4.f32 [%0], {%1,%2,%3,%4};\n}" :: "l"(p), "f"(a), "f"(b), "f"(c), "f"(d), "r"((int)on) : "memory");
}
__device__ __forceinline__ uint32_t pack2(float lo, float hi) { uint32_t r; asm("cvt.rn.bf16x2.f32 %0, %1, %2;" : "=r"(r) : "f"(hi), "f"(lo)); return r; }
__device__ __forceinline__ float bf_lo(uint32_t v) { return __uint_as_float(v << 16); }
__device__ __forceinline__ float bf_hi(uint32_t v) { return __uint_as_float(v & 0xFFFF0000u); }
__device__ __forceinline__ void stsm4(uint32_t addr, uint32_t a, uint32_t b, uint32_t c, uint32_t d) {
  asm volatile("stmatrix.sync.aligned.m8n8.x4.shared.b16 [%0], {%1,%2,%3,%4};" :: "r"(addr), "r"(a), "r"(b), "r"(c), "r"(d) : "memory");
}
template <uint32_t O> __device__ __forceinline__ void stsm4_o(uint32_t addr, uint32_t a, uint32_t b, uint32_t c, uint32_t d) {
  asm volatile("stmatrix.sync.aligned.m8n8.x4.shared.b16 [%0+%5], {%1,%2,%3,%4};" :: "r"(addr), "r"(a), "r"(b), "r"(c), "r"(d), "n"(O) : "memory");
}
__device__ __forceinline__ void sts4(uint32_t addr, uint32_t a, uint32_t b, uint32_t c, uint32_t d) { asm volatile("st.shared.v4.u32 [%0], {%1,%2,%3,%4};" :: "r"(addr), "r"(a), "r"(b), "r"(c), "r"(d) : "memory"); }
__device__ __forceinline__ void sts2f(uint32_t addr, float a, float b) { asm volatile("st.shared.v2.f32 [%0], {%1,%2};" :: "r"(addr), "f"(a), "f"(b) : "memory"); }
__device__ __forceinline__ void sts1(uint32_t addr, uint32_t a) { asm volatile("st.shared.u32 [%0], %1;" :: "r"(addr), "r"(a) : "memory"); }
__device__ __forceinline__ float2 lds2f(uint32_t addr) { float2 v; asm volatile("ld.shared.v2.f32 {%0,%1}, [%2];" : "=f"(v.x), "=f"(v.y) : "r"(addr) : "memory"); return v; }
template <uint32_t O> __device__ __forceinline__ float2 lds2f_o(uint32_t addr) { float2 v; asm volatile("ld.shared.v2.f32 {%0,%1}, [%2+%3];" : "=f"(v.x), "=f"(v.y) : "r"(addr), "n"(O) : "memory"); return v; }
template <int I, int N, class F> __device__ __forceinline__ void static_for(F&& f) { if constexpr (I < N) { f(std::integral_constant<int, I>{}); static_for<I + 1, N>(f); } }
__device__ __forceinline__ uint4 lds4(uint32_t addr) { uint4 v; asm volatile("ld.shared.v4.u32 {%0,%1,%2,%3}, [%4];" : "=r"(v.x), "=r"(v.y), "=r"(v.z), "=r"(v.w) : "r"(addr) : "memory"); return v; }
__device__ __forceinline__ uint32_t lds1(uint32_t addr) { uint32_t v; asm volatile("ld.shared.u32 %0, [%1];" : "=r"(v) : "r"(addr) : "memory"); return v; }
__device__ __forceinline__ float ex2(float x) { float y; asm("ex2.approx.ftz.f32 %0, %1;" : "=f"(y) : "f"(x)); return y; }
__device__ __forceinline__ uint32_t max4(uint32_t m, const uint4& v) { return __vimax3_u32(__vimax3_u32(m, v.x, v.y), v.z, v.w); }
__device__ __forceinline__ float rsq(float x) { float y; asm("rsqrt.approx.ftz.f32 %0, %1;" : "=f"(y) : "f"(x)); return y; }
__device__ __forceinline__ float rcp(float x) { float y; asm("rcp.approx.ftz.f32 %0, %1;" : "=f"(y) : "f"(x)); return y; }
__device__ __forceinline__ uint2 ld_rlx2(const void* p) { uint2 v; asm volatile("ld.relaxed.gpu.global.v2.u32 {%0,%1}, [%2];" : "=r"(v.x), "=r"(v.y) : "l"(p) : "memory"); return v; }
template <uint32_t O> __device__ __forceinline__ uint4 lds4_o(uint32_t addr) { uint4 v; asm volatile("ld.shared.v4.u32 {%0,%1,%2,%3}, [%4+%5];" : "=r"(v.x), "=r"(v.y), "=r"(v.z), "=r"(v.w) : "r"(addr), "n"(O) : "memory"); return v; }
__device__ __forceinline__ uint32_t hadd2(uint32_t a, uint32_t b) { uint32_t r; asm("add.rn.bf16x2 %0, %1, %2;" : "=r"(r) : "r"(a), "r"(b)); return r; }
__device__ __forceinline__ uint4 hadd8(const uint4& a, const uint4& b) { return make_uint4(hadd2(a.x, b.x), hadd2(a.y, b.y), hadd2(a.z, b.z), hadd2(a.w, b.w)); }
__device__ __forceinline__ bool hnan(uint32_t a) { return (a & 0x7FFF0000u) > 0x7F800000u; }
__device__ __forceinline__ uint32_t hfma2(uint32_t a, uint32_t b, uint32_t c) { uint32_t r; asm("fma.rn.bf16x2 %0, %1, %2, %3;" : "=r"(r) : "r"(a), "r"(b), "r"(c)); return r; }
__device__ __forceinline__ uint32_t ordered(float v) { const uint32_t u = __float_as_uint(v); return u ^ ((uint32_t)((int)u >> 31) | 0x80000000u); }
__device__ __forceinline__ uint32_t route(const uint4& v, float sw, int row, float2& pr) {
  const float mean = __uint_as_float(v.x) * (1.f / D_);
  pr.x = rsq(fmaxf(fmaf(-mean, mean, __uint_as_float(v.y) * (1.f / D_)), 0.f) + 1e-5f);
  pr.y = -mean * pr.x;
  return min(ordered(pr.x * fmaf(-mean, sw, __uint_as_float(v.z))) & ~2047u, 0xFFFFF000u) | (2047 - row);
}
__device__ __forceinline__ uint2 top2(uint32_t a, uint32_t b, uint32_t c, uint32_t d) {
  const uint32_t h0 = max(a, b), h1 = max(c, d), h = max(h0, h1), l = __vimax3_u32(min(h0, h1), min(a, b), min(c, d));
  const uint32_t m1 = __reduce_max_sync(~0u, h);
  return make_uint2(m1, __reduce_max_sync(~0u, h == m1 ? l : h));
}
__device__ __forceinline__ uint32_t hmul2(uint32_t a, uint32_t b) { uint32_t r; asm("mul.rn.bf16x2 %0, %1, %2;" : "=r"(r) : "r"(a), "r"(b)); return r; }
__device__ __forceinline__ uint32_t phi2(float u0, float u1, uint32_t r2, float rl) {
  uint32_t p, r;
  asm("cvt.rn.relu.bf16x2.f32 %0, %1, %2;" : "=r"(p) : "f"(u1), "f"(u0));
  asm("fma.rn.bf16x2 %0, %1, %2, %3;" : "=r"(r) : "r"(p), "r"(r2), "r"(pack2(__saturatef(ex2(u0 * rl) + 1e-6f), __saturatef(ex2(u1 * rl) + 1e-6f))));
  return r;
}

template<int TA, int TB, int OFF, int SZ> __device__ __forceinline__ void wgmma_n192_ss(float (&d)[SZ], uint64_t da, uint64_t db, int scale_d) {
  asm volatile("{\n.reg .pred p;\nsetp.ne.b32 p, %98, 0;\n"
    "wgmma.mma_async.sync.aligned.m64n192k16.f32.bf16.bf16 {%0,%1,%2,%3,%4,%5,%6,%7,%8,%9,%10,%11,%12,%13,%14,%15,%16,%17,%18,%19,%20,%21,%22,%23,%24,%25,%26,%27,%28,%29,%30,%31,%32,%33,%34,%35,%36,%37,%38,%39,%40,%41,%42,%43,%44,%45,%46,%47,%48,%49,%50,%51,%52,%53,%54,%55,%56,%57,%58,%59,%60,%61,%62,%63,%64,%65,%66,%67,%68,%69,%70,%71,%72,%73,%74,%75,%76,%77,%78,%79,%80,%81,%82,%83,%84,%85,%86,%87,%88,%89,%90,%91,%92,%93,%94,%95}, %96, %97, p, 1, 1, %99, %100;\n}\n"
    : "+f"(d[OFF+0]), "+f"(d[OFF+1]), "+f"(d[OFF+2]), "+f"(d[OFF+3]), "+f"(d[OFF+4]), "+f"(d[OFF+5]), "+f"(d[OFF+6]), "+f"(d[OFF+7]),
      "+f"(d[OFF+8]), "+f"(d[OFF+9]), "+f"(d[OFF+10]), "+f"(d[OFF+11]), "+f"(d[OFF+12]), "+f"(d[OFF+13]), "+f"(d[OFF+14]), "+f"(d[OFF+15]),
      "+f"(d[OFF+16]), "+f"(d[OFF+17]), "+f"(d[OFF+18]), "+f"(d[OFF+19]), "+f"(d[OFF+20]), "+f"(d[OFF+21]), "+f"(d[OFF+22]), "+f"(d[OFF+23]),
      "+f"(d[OFF+24]), "+f"(d[OFF+25]), "+f"(d[OFF+26]), "+f"(d[OFF+27]), "+f"(d[OFF+28]), "+f"(d[OFF+29]), "+f"(d[OFF+30]), "+f"(d[OFF+31]),
      "+f"(d[OFF+32]), "+f"(d[OFF+33]), "+f"(d[OFF+34]), "+f"(d[OFF+35]), "+f"(d[OFF+36]), "+f"(d[OFF+37]), "+f"(d[OFF+38]), "+f"(d[OFF+39]),
      "+f"(d[OFF+40]), "+f"(d[OFF+41]), "+f"(d[OFF+42]), "+f"(d[OFF+43]), "+f"(d[OFF+44]), "+f"(d[OFF+45]), "+f"(d[OFF+46]), "+f"(d[OFF+47]),
      "+f"(d[OFF+48]), "+f"(d[OFF+49]), "+f"(d[OFF+50]), "+f"(d[OFF+51]), "+f"(d[OFF+52]), "+f"(d[OFF+53]), "+f"(d[OFF+54]), "+f"(d[OFF+55]),
      "+f"(d[OFF+56]), "+f"(d[OFF+57]), "+f"(d[OFF+58]), "+f"(d[OFF+59]), "+f"(d[OFF+60]), "+f"(d[OFF+61]), "+f"(d[OFF+62]), "+f"(d[OFF+63]),
      "+f"(d[OFF+64]), "+f"(d[OFF+65]), "+f"(d[OFF+66]), "+f"(d[OFF+67]), "+f"(d[OFF+68]), "+f"(d[OFF+69]), "+f"(d[OFF+70]), "+f"(d[OFF+71]),
      "+f"(d[OFF+72]), "+f"(d[OFF+73]), "+f"(d[OFF+74]), "+f"(d[OFF+75]), "+f"(d[OFF+76]), "+f"(d[OFF+77]), "+f"(d[OFF+78]), "+f"(d[OFF+79]),
      "+f"(d[OFF+80]), "+f"(d[OFF+81]), "+f"(d[OFF+82]), "+f"(d[OFF+83]), "+f"(d[OFF+84]), "+f"(d[OFF+85]), "+f"(d[OFF+86]), "+f"(d[OFF+87]),
      "+f"(d[OFF+88]), "+f"(d[OFF+89]), "+f"(d[OFF+90]), "+f"(d[OFF+91]), "+f"(d[OFF+92]), "+f"(d[OFF+93]), "+f"(d[OFF+94]), "+f"(d[OFF+95])
    : "l"(da), "l"(db), "r"(scale_d), "n"(TA), "n"(TB));
}
template<int TA, int TB, int OFF, int SZ> __device__ __forceinline__ void wgmma_n128_ss(float (&d)[SZ], uint64_t da, uint64_t db, int scale_d) {
  asm volatile("{\n.reg .pred p;\nsetp.ne.b32 p, %66, 0;\n"
    "wgmma.mma_async.sync.aligned.m64n128k16.f32.bf16.bf16 {%0,%1,%2,%3,%4,%5,%6,%7,%8,%9,%10,%11,%12,%13,%14,%15,%16,%17,%18,%19,%20,%21,%22,%23,%24,%25,%26,%27,%28,%29,%30,%31,%32,%33,%34,%35,%36,%37,%38,%39,%40,%41,%42,%43,%44,%45,%46,%47,%48,%49,%50,%51,%52,%53,%54,%55,%56,%57,%58,%59,%60,%61,%62,%63}, %64, %65, p, 1, 1, %67, %68;\n}\n"
    : "+f"(d[OFF+0]), "+f"(d[OFF+1]), "+f"(d[OFF+2]), "+f"(d[OFF+3]), "+f"(d[OFF+4]), "+f"(d[OFF+5]), "+f"(d[OFF+6]), "+f"(d[OFF+7]),
      "+f"(d[OFF+8]), "+f"(d[OFF+9]), "+f"(d[OFF+10]), "+f"(d[OFF+11]), "+f"(d[OFF+12]), "+f"(d[OFF+13]), "+f"(d[OFF+14]), "+f"(d[OFF+15]),
      "+f"(d[OFF+16]), "+f"(d[OFF+17]), "+f"(d[OFF+18]), "+f"(d[OFF+19]), "+f"(d[OFF+20]), "+f"(d[OFF+21]), "+f"(d[OFF+22]), "+f"(d[OFF+23]),
      "+f"(d[OFF+24]), "+f"(d[OFF+25]), "+f"(d[OFF+26]), "+f"(d[OFF+27]), "+f"(d[OFF+28]), "+f"(d[OFF+29]), "+f"(d[OFF+30]), "+f"(d[OFF+31]),
      "+f"(d[OFF+32]), "+f"(d[OFF+33]), "+f"(d[OFF+34]), "+f"(d[OFF+35]), "+f"(d[OFF+36]), "+f"(d[OFF+37]), "+f"(d[OFF+38]), "+f"(d[OFF+39]),
      "+f"(d[OFF+40]), "+f"(d[OFF+41]), "+f"(d[OFF+42]), "+f"(d[OFF+43]), "+f"(d[OFF+44]), "+f"(d[OFF+45]), "+f"(d[OFF+46]), "+f"(d[OFF+47]),
      "+f"(d[OFF+48]), "+f"(d[OFF+49]), "+f"(d[OFF+50]), "+f"(d[OFF+51]), "+f"(d[OFF+52]), "+f"(d[OFF+53]), "+f"(d[OFF+54]), "+f"(d[OFF+55]),
      "+f"(d[OFF+56]), "+f"(d[OFF+57]), "+f"(d[OFF+58]), "+f"(d[OFF+59]), "+f"(d[OFF+60]), "+f"(d[OFF+61]), "+f"(d[OFF+62]), "+f"(d[OFF+63])
    : "l"(da), "l"(db), "r"(scale_d), "n"(TA), "n"(TB));
}
template<int TA, int TB, int OFF, int SZ> __device__ __forceinline__ void wgmma_n64_ss(float (&d)[SZ], uint64_t da, uint64_t db, int scale_d) {
  asm volatile("{\n.reg .pred p;\nsetp.ne.b32 p, %34, 0;\n"
    "wgmma.mma_async.sync.aligned.m64n64k16.f32.bf16.bf16 {%0,%1,%2,%3,%4,%5,%6,%7,%8,%9,%10,%11,%12,%13,%14,%15,%16,%17,%18,%19,%20,%21,%22,%23,%24,%25,%26,%27,%28,%29,%30,%31}, %32, %33, p, 1, 1, %35, %36;\n}\n"
    : "+f"(d[OFF+0]), "+f"(d[OFF+1]), "+f"(d[OFF+2]), "+f"(d[OFF+3]), "+f"(d[OFF+4]), "+f"(d[OFF+5]), "+f"(d[OFF+6]), "+f"(d[OFF+7]),
      "+f"(d[OFF+8]), "+f"(d[OFF+9]), "+f"(d[OFF+10]), "+f"(d[OFF+11]), "+f"(d[OFF+12]), "+f"(d[OFF+13]), "+f"(d[OFF+14]), "+f"(d[OFF+15]),
      "+f"(d[OFF+16]), "+f"(d[OFF+17]), "+f"(d[OFF+18]), "+f"(d[OFF+19]), "+f"(d[OFF+20]), "+f"(d[OFF+21]), "+f"(d[OFF+22]), "+f"(d[OFF+23]),
      "+f"(d[OFF+24]), "+f"(d[OFF+25]), "+f"(d[OFF+26]), "+f"(d[OFF+27]), "+f"(d[OFF+28]), "+f"(d[OFF+29]), "+f"(d[OFF+30]), "+f"(d[OFF+31])
    : "l"(da), "l"(db), "r"(scale_d), "n"(TA), "n"(TB));
}
template<int TB, int OFF, int SZ> __device__ __forceinline__ void wgmma_n64_rs(float (&d)[SZ], uint32_t a0, uint32_t a1, uint32_t a2, uint32_t a3, uint64_t db, int scale_d) {
  asm volatile("{\n.reg .pred p;\nsetp.ne.b32 p, %37, 0;\n"
    "wgmma.mma_async.sync.aligned.m64n64k16.f32.bf16.bf16 {%0,%1,%2,%3,%4,%5,%6,%7,%8,%9,%10,%11,%12,%13,%14,%15,%16,%17,%18,%19,%20,%21,%22,%23,%24,%25,%26,%27,%28,%29,%30,%31}, {%32,%33,%34,%35}, %36, p, 1, 1, %38;\n}\n"
    : "+f"(d[OFF+0]), "+f"(d[OFF+1]), "+f"(d[OFF+2]), "+f"(d[OFF+3]), "+f"(d[OFF+4]), "+f"(d[OFF+5]), "+f"(d[OFF+6]), "+f"(d[OFF+7]),
      "+f"(d[OFF+8]), "+f"(d[OFF+9]), "+f"(d[OFF+10]), "+f"(d[OFF+11]), "+f"(d[OFF+12]), "+f"(d[OFF+13]), "+f"(d[OFF+14]), "+f"(d[OFF+15]),
      "+f"(d[OFF+16]), "+f"(d[OFF+17]), "+f"(d[OFF+18]), "+f"(d[OFF+19]), "+f"(d[OFF+20]), "+f"(d[OFF+21]), "+f"(d[OFF+22]), "+f"(d[OFF+23]),
      "+f"(d[OFF+24]), "+f"(d[OFF+25]), "+f"(d[OFF+26]), "+f"(d[OFF+27]), "+f"(d[OFF+28]), "+f"(d[OFF+29]), "+f"(d[OFF+30]), "+f"(d[OFF+31])
    : "r"(a0), "r"(a1), "r"(a2), "r"(a3), "l"(db), "r"(scale_d), "n"(TB));
}
template<int TA, int TB, int OFF, int SZ> __device__ __forceinline__ void wgmma_n72_ss(float (&d)[SZ], uint64_t da, uint64_t db, int scale_d) {
  asm volatile("{\n.reg .pred p;\nsetp.ne.b32 p, %38, 0;\n"
    "wgmma.mma_async.sync.aligned.m64n72k16.f32.bf16.bf16 {%0,%1,%2,%3,%4,%5,%6,%7,%8,%9,%10,%11,%12,%13,%14,%15,%16,%17,%18,%19,%20,%21,%22,%23,%24,%25,%26,%27,%28,%29,%30,%31,%32,%33,%34,%35}, %36, %37, p, 1, 1, %39, %40;\n}\n"
    : "+f"(d[OFF+0]), "+f"(d[OFF+1]), "+f"(d[OFF+2]), "+f"(d[OFF+3]), "+f"(d[OFF+4]), "+f"(d[OFF+5]), "+f"(d[OFF+6]), "+f"(d[OFF+7]),
      "+f"(d[OFF+8]), "+f"(d[OFF+9]), "+f"(d[OFF+10]), "+f"(d[OFF+11]), "+f"(d[OFF+12]), "+f"(d[OFF+13]), "+f"(d[OFF+14]), "+f"(d[OFF+15]),
      "+f"(d[OFF+16]), "+f"(d[OFF+17]), "+f"(d[OFF+18]), "+f"(d[OFF+19]), "+f"(d[OFF+20]), "+f"(d[OFF+21]), "+f"(d[OFF+22]), "+f"(d[OFF+23]),
      "+f"(d[OFF+24]), "+f"(d[OFF+25]), "+f"(d[OFF+26]), "+f"(d[OFF+27]), "+f"(d[OFF+28]), "+f"(d[OFF+29]), "+f"(d[OFF+30]), "+f"(d[OFF+31]),
      "+f"(d[OFF+32]), "+f"(d[OFF+33]), "+f"(d[OFF+34]), "+f"(d[OFF+35])
    : "l"(da), "l"(db), "r"(scale_d), "n"(TA), "n"(TB));
}
template<int TB, int OFF, int SZ> __device__ __forceinline__ void wgmma_n40_rs(float (&d)[SZ], uint32_t a0, uint32_t a1, uint32_t a2, uint32_t a3, uint64_t db, int scale_d) {
  asm volatile("{\n.reg .pred p;\nsetp.ne.b32 p, %25, 0;\n"
    "wgmma.mma_async.sync.aligned.m64n40k16.f32.bf16.bf16 {%0,%1,%2,%3,%4,%5,%6,%7,%8,%9,%10,%11,%12,%13,%14,%15,%16,%17,%18,%19}, {%20,%21,%22,%23}, %24, p, 1, 1, %26;\n}\n"
    : "+f"(d[OFF+0]), "+f"(d[OFF+1]), "+f"(d[OFF+2]), "+f"(d[OFF+3]), "+f"(d[OFF+4]), "+f"(d[OFF+5]), "+f"(d[OFF+6]), "+f"(d[OFF+7]),
      "+f"(d[OFF+8]), "+f"(d[OFF+9]), "+f"(d[OFF+10]), "+f"(d[OFF+11]), "+f"(d[OFF+12]), "+f"(d[OFF+13]), "+f"(d[OFF+14]), "+f"(d[OFF+15]),
      "+f"(d[OFF+16]), "+f"(d[OFF+17]), "+f"(d[OFF+18]), "+f"(d[OFF+19])
    : "r"(a0), "r"(a1), "r"(a2), "r"(a3), "l"(db), "r"(scale_d), "n"(TB));
}
template<int TB, int OFF, int SZ> __device__ __forceinline__ void wgmma_n128_rs(float (&d)[SZ], uint32_t a0, uint32_t a1, uint32_t a2, uint32_t a3, uint64_t db, int scale_d) {
  asm volatile("{\n.reg .pred p;\nsetp.ne.b32 p, %69, 0;\n"
    "wgmma.mma_async.sync.aligned.m64n128k16.f32.bf16.bf16 {%0,%1,%2,%3,%4,%5,%6,%7,%8,%9,%10,%11,%12,%13,%14,%15,%16,%17,%18,%19,%20,%21,%22,%23,%24,%25,%26,%27,%28,%29,%30,%31,%32,%33,%34,%35,%36,%37,%38,%39,%40,%41,%42,%43,%44,%45,%46,%47,%48,%49,%50,%51,%52,%53,%54,%55,%56,%57,%58,%59,%60,%61,%62,%63}, {%64,%65,%66,%67}, %68, p, 1, 1, %70;\n}\n"
    : "+f"(d[OFF+0]), "+f"(d[OFF+1]), "+f"(d[OFF+2]), "+f"(d[OFF+3]), "+f"(d[OFF+4]), "+f"(d[OFF+5]), "+f"(d[OFF+6]), "+f"(d[OFF+7]),
      "+f"(d[OFF+8]), "+f"(d[OFF+9]), "+f"(d[OFF+10]), "+f"(d[OFF+11]), "+f"(d[OFF+12]), "+f"(d[OFF+13]), "+f"(d[OFF+14]), "+f"(d[OFF+15]),
      "+f"(d[OFF+16]), "+f"(d[OFF+17]), "+f"(d[OFF+18]), "+f"(d[OFF+19]), "+f"(d[OFF+20]), "+f"(d[OFF+21]), "+f"(d[OFF+22]), "+f"(d[OFF+23]),
      "+f"(d[OFF+24]), "+f"(d[OFF+25]), "+f"(d[OFF+26]), "+f"(d[OFF+27]), "+f"(d[OFF+28]), "+f"(d[OFF+29]), "+f"(d[OFF+30]), "+f"(d[OFF+31]),
      "+f"(d[OFF+32]), "+f"(d[OFF+33]), "+f"(d[OFF+34]), "+f"(d[OFF+35]), "+f"(d[OFF+36]), "+f"(d[OFF+37]), "+f"(d[OFF+38]), "+f"(d[OFF+39]),
      "+f"(d[OFF+40]), "+f"(d[OFF+41]), "+f"(d[OFF+42]), "+f"(d[OFF+43]), "+f"(d[OFF+44]), "+f"(d[OFF+45]), "+f"(d[OFF+46]), "+f"(d[OFF+47]),
      "+f"(d[OFF+48]), "+f"(d[OFF+49]), "+f"(d[OFF+50]), "+f"(d[OFF+51]), "+f"(d[OFF+52]), "+f"(d[OFF+53]), "+f"(d[OFF+54]), "+f"(d[OFF+55]),
      "+f"(d[OFF+56]), "+f"(d[OFF+57]), "+f"(d[OFF+58]), "+f"(d[OFF+59]), "+f"(d[OFF+60]), "+f"(d[OFF+61]), "+f"(d[OFF+62]), "+f"(d[OFF+63])
    : "r"(a0), "r"(a1), "r"(a2), "r"(a3), "l"(db), "r"(scale_d), "n"(TB));
}

struct Ptrs { const __nv_bfloat16 *x, *wqkv, *wo, *wr, *wg, *wu, *wd; __nv_bfloat16* out; };

__global__ void __cluster_dims__(2, 1, 1) __launch_bounds__(384, 1) fused_kernel(const __grid_constant__ CUtensorMap tmX, const __grid_constant__ CUtensorMap tmW,
                                                       const __grid_constant__ CUtensorMap tmO, const __grid_constant__ CUtensorMap tmG,
                                                       const __grid_constant__ CUtensorMap tmU, const __grid_constant__ CUtensorMap tmD,
                                                       const __grid_constant__ CUtensorMap tmM, const __grid_constant__ CUtensorMap tmPG,
                                                       const __grid_constant__ CUtensorMap tmPU, const __grid_constant__ CUtensorMap tmPD,
                                                       const Ptrs P) {
  extern __shared__ __align__(1024) uint8_t smem_raw[];
  if (TMPF && threadIdx.x == 0) { tmap_prefetch(&tmX); tmap_prefetch(&tmW); }
  const int tid = threadIdx.x, wid = __shfl_sync(~0u, tid >> 5, 0), wg = wid >> 2, lane = tid & 31;
  const int pj = blockIdx.x >> 1, pi = pj - 36;
  const int b = (pj < 4 ? 32 + pj * 8 : pj < 36 ? pj - 4 : 33 + pi + ((pi * 37) >> 8)) * 2 + (blockIdx.x & 1);
  const int rb = b >> 4, cg = b & 15, hf = cg >> 3, c3 = cg & 7;
  const int jp = cg >> 1;
  const int fidx = jp == rb ? -1 : b - 2 * rb - (jp > rb ? 2 : 0);
  const uint32_t rank = b & 1, own = rank << 24;
  const uint32_t zero = gridDim.y - 1;
  const uint32_t sm = own + sb, mb = own + bars;
  auto chunk_of = [&](int p) { return (int)((0x1765432FEDCBA980ull >> (4 * p)) & 15) ^ (p == 0 || p == 15 ? cg : p < 9 ? cg & 8 : cg & 14); };
  const int kl = (jp & 3) * 256;
  auto k_of = [&](int kb) { return kb >= 12 ? kl + (kb - 12) * 64 : kb * 64 < kl ? kb * 64 : kb * 64 + 256; };
  auto load_w = [&](int kb) {
#pragma unroll
    for (int i = 0; i < 3; i++) tma_2d(sm + woff(kb & 3) + i * WSTR, &tmW, i * D_ + cg * 64, k_of(kb), mb + B_FULL + 8 * (kb & 3), EFW);
  };
  TS_DECL; TS(0); TSG(30);
  if (wid == 8) {
    if (elect_one()) {
      if (smem_u32(smem_raw) != sm) {
#pragma unroll
        for (int i = 0; i < PERT; i++) sts1(mb, lds1(mb));
        asm volatile("trap;");
      }
#pragma unroll
      for (int s = 0; s < 4; s++) mbar_init(mb + B_FULL + 8 * s, 1);
      asm volatile("fence.mbarrier_init.release.cluster;" ::: "memory");
      if (INIF) fence_async_smem();
    }
  } else if (wid == 9) {
    if (elect_one()) {
#pragma unroll
      for (int i = 4; i < 32; i++)
        if (i != 27) mbar_init(mb + 8 * i, i < 8 ? 8 : i == 8 ? 64 : i == 26 ? 2 : i == 29 ? 4 : 1);
      asm volatile("fence.mbarrier_init.release.cluster;" ::: "memory");
      if (INIF) fence_async_smem();
    }
  }
  __syncwarp();
  asm volatile("barrier.cluster.arrive.relaxed.aligned;" ::: "memory");
  if (wid == 8) {
    if (elect_one()) {
      mbar_expect_tx(mb + B_FULL, STAGE_B);
      tma_2d(sm + xoff(0, 0), &tmX, k_of(0), rb * 256, mb + B_FULL, EFX);
      tma_2d(sm + xoff(0, 1), &tmX, k_of(0), rb * 256 + 128, mb + B_FULL, EFX);
      load_w(0);
    }
    __syncwarp();
  }
  asm volatile("barrier.cluster.wait.aligned;" ::: "memory");

  if (wg == 2) {
    asm volatile("setmaxnreg.dec.sync.aligned.u32 56;");
    auto wait3 = [&](int i) { mbar_wait(sm + bar3(i), 0); };
    if (wid == 8) {
      if (elect_one()) {
        int np = fidx >= 0 ? 0 : 32;
        if (fidx >= 0) mbar_expect_tx(mb + B_FFN, 32 * 512);
#pragma unroll 1
        for (int kb = 1; kb < 16; kb++) {
          const uint32_t fb = mb + B_FULL + 8 * (kb & 3);
          mbar_wait(fb + B_EMPTY, ((kb >> 2) & 1) ^ 1);
          mbar_expect_tx(fb, STAGE_B);
          tma_2d_mc(sm + xoff(kb & 3, rank), &tmX, k_of(kb), rb * 256 + rank * 128, fb, EFX);
          load_w(kb);
          if (kb >= 12) asm volatile("mbarrier.arrive.shared::cta.b64 _, [%0], 7;" :: "r"(fb + B_EMPTY) : "memory");
#pragma unroll 1
          for (int n = ((NPK << 16) >> (4 * kb)) & 15; n > 0 && np < 32; n--, np++)
            tma_2d(sm + OFF_STATS + 512, (np & 1) ? &tmPU : &tmPG, (fidx >> 1) * 64, (np >> 1) * 64 + rank * 32, mb + B_FFN, false);
        }
        if (fidx >= 0) { mbar_wait(mb + B_FFN, 0); mbar_expect_tx(mb + B_FFN, 65536 + NPD * 512); mbar_expect_tx(mb + B_FFN + 8, 65536); }
#pragma unroll
        for (int p = 4; p < 8; p++) sts4(sm + OFF_STATS + p * 144, 0x3F803F80u, 0x3F803F80u, 0x3F803F80u, 0x3F803F80u);
        fence_async_smem();
        mbar_arrive(mb + B_LATE);
        PTS(2);
        mbar_expect_tx(mb + B_KVL, 36864);
        mbar_wait(mb + B_LATE, 0);
        wait3(60);
        delay(clk(), KDELAY);
        bulk_load(sm + 11 * SLOT_B, &G.kvp[cg * 2304], SLOT_B, mb + B_KVL);
        bulk_load(sm + 13 * SLOT_B, &G.kvp[cg * 2304 + 1024], SLOT_B, mb + B_KVL);
        bulk_load(sm + 2 * SLOT_B, &G.kvp[cg * 2304 + 2048], 4096, mb + B_KVL);
        PTS(3);
        const uint4* src = &G.obuf[(rb * 4 + rank * 2 + hf) * 64 * 128];
        wait3(48);
        delay(clk(), ADELAY);
#pragma unroll 1
        for (int i = 1; i < 17; i++) {
          const int p = min(i, 15);
          const uint32_t d = sm + (10 + (p & 3)) * SLOT_B + rank * 8192, fb = sm + bar3(0) + o3(p) + rank * 256;
          const uint4* q = src + chunk_of(i & 15) * 512;
          mbar_wait(sm + bar3(48) + o3(max(p - 4, 0)), 0);
          bulk_load_mc(d, q, fb, i < 15 ? 3 : 1 << ((i ^ rank ^ 1) & 1));
          if (i == 1) PTS(7);
        }
        PTS(15);
      }
    } else {
      const int r4 = lane >> 3, c8 = lane & 7;
      const uint32_t eb = (lane << 24) + bars + B_EMPTY;
      auto tagged = [](float v, uint32_t tag) { return ((__float_as_uint(v) + 128) & ~255u) | tag; };
      auto gather = [&](uint32_t tag) {
        const int q = (wid - 9) * 24 + lane;
        const uint4* cp = lane < 24 ? &G.csp[cg * 8 * 48 + q] : &G.st1[rb * 8 * 48 + (wid - 9) * 8 + lane - 24];
        uint4 v[8];
        delay(clk(), GDELAY);
#pragma unroll 1
        for (int it = 0;; it++) {
#pragma unroll
          for (int i = 0; i < 8; i++) v[i] = ld_rlx4(cp + i * 48);
          uint32_t x = 0;
#pragma unroll
          for (int i = 0; i < 8; i++) { v[i].x ^= tag; v[i].y ^= tag; v[i].z ^= tag; v[i].w ^= tag; x |= v[i].x | v[i].y | v[i].z | v[i].w; }
          if (!__any_sync(~0u, (x & 255) != 0)) break;
          SPINCHK(it, 3);
        }
        float c[4] = {0.f, 0.f, 0.f, 0.f};
#pragma unroll
        for (int i = 0; i < 8; i++) { c[0] += __uint_as_float(v[i].x); c[1] += __uint_as_float(v[i].y); c[2] += __uint_as_float(v[i].z); c[3] += __uint_as_float(v[i].w); }
        const uint32_t h0 = pack2(c[0], c[1]), h1 = pack2(c[2], c[3]), ca = sm + OFF_COLSUM + (q >> 1) * 32 + (q & 1) * 8;
        if (lane < 24) {
          sts2f(ca, __uint_as_float(h0), __uint_as_float(h1));
          sts2f(ca + 16, __uint_as_float(pack2(c[0] - bf_lo(h0), c[1] - bf_hi(h0))), __uint_as_float(pack2(c[2] - bf_lo(h1), c[3] - bf_hi(h1))));
        }
        fence_async_smem();
        mbar_arrive(mb + B_AUX);
      };
      const int r2 = lane >> 4, c16 = lane & 15;
      float a[12];
#pragma unroll
      for (int i = 0; i < 12; i++) a[i] = 0.f;
      auto kb_of = [](int it) { return (int)(KORD >> (4 * it)) & 15; };
      if (wid == 9) {
        const uint32_t a0 = sm + rb * 1024 + r2 * 128 + (((c16 >> 1) ^ r2) << 4) + (c16 & 1) * 8;
        const uint2* gw = (const uint2*)(P.wqkv + (kl + rb * 8 + r2) * 3072 + cg * 64) + c16;
#pragma unroll 1
        for (int it = 0; it < 16; it++) {
          uint2 w[12];
          const int kb = kb_of(it);
          if (kb >= 12) {
#pragma unroll
            for (int j = 0; j < 12; j++) w[j] = ld_rlx2(gw + (j >> 2) * 256 + (j & 3) * 1536);
            gw += 64 * 768;
          } else {
            const uint32_t so = a0 + woff(kb & 3);
            mbar_wait(mb + B_FULL + 8 * (kb & 3), (kb >> 2) & 1);
            static_for<0, 12>([&](auto ic) { constexpr int i = decltype(ic)::value;
              const float2 v = lds2f_o<(i >> 2) * WSTR + (i & 3) * 256>(so ^ ((i & 3) << 5)); w[i] = make_uint2(__float_as_uint(v.x), __float_as_uint(v.y)); });
            uint32_t done = 0;
#pragma unroll
            for (int i = 0; i < 12; i++) done |= w[i].y;
            if (lane < 2) mbar_arrive_rem(eb + 8 * (kb & 3) + (done & zero));
          }
#pragma unroll
          for (int i = 0; i < 12; i++) { float* q = a + (i >> 2) * 4; q[0] += bf_lo(w[i].x); q[1] += bf_hi(w[i].x); q[2] += bf_lo(w[i].y); q[3] += bf_hi(w[i].y); }
        }
        if (lane == 0) PTS(8);
        float c[6];
#pragma unroll
        for (int i = 0; i < 6; i++) {
          const int o = (i >> 1) * 4 + (i & 1);
          c[i] = (r2 ? a[o + 2] : a[o]) + __shfl_xor_sync(~0u, r2 ? a[o] : a[o + 2], 16);
        }
        bar_sync(5, 96);
        if (lane == 0) PTS(5);
        const uint32_t tag = lds1(mb + B_SW + 4) & 255;
#pragma unroll
        for (int sg = 0; sg < 3; sg++) st_rlx2((uint2*)&G.csp[(cg * 8 + rb) * 48] + sg * 32 + c16 * 2 + r2, tagged(c[sg * 2], tag), tagged(c[sg * 2 + 1], tag));
      } else {
       if (wid == 10) {
        if (lane < 24 && (lane & 28) != 4) sts4(sm + OFF_STATS + (lane < 16 ? lane * 128 + c8 * 16 : c8 * 16), 0x3F803F80u, 0x3F803F80u, 0x3F803F80u, 0x3F803F80u);
       } else {
        mbar_wait(mb + B_FULL + 8 * PFST, 0);
        const uint32_t ep = ld_rlx(&G.epoch);
        uint4 v[4];
#pragma unroll
        for (int i = 0; i < 4; i++) v[i] = ld_cg4((const uint4*)P.wr + lane + i * 32);
        if (elect_one()) { tmap_prefetch(&tmO); tmap_prefetch(&tmG); tmap_prefetch(&tmU); tmap_prefetch(&tmD); tmap_prefetch(&tmPD); tmap_prefetch(&tmM); }
        __syncwarp();
        const uint4 sv = make_uint4(SENT, SENT, SENT, SENT);
#pragma unroll 1
        for (int i = 0; i < 9; i++) {
          uint4* q = i < 8 ? &G.obuf[((rb * 4 + (i >> 1)) * 64 + cg * 4) * 128 + (i & 1) * 256 + lane] : &G.kvp[cg * 2304 + rb * 288 + lane];
#pragma unroll
          for (int j = 0; j < 8; j++) q[j * 32] = sv;
          if (i == 8) q[256] = sv;
          else if (lane < ((i & 1) ? 24 : 16)) l2_prefetch((i & 1) ? P.wqkv + (kl + (i >> 1) * 64 + rb * 8 + c8) * 3072 + r4 * 1024 + cg * 64 : P.x + (b * 16 + lane) * D_ + kl + i * 32);
        }
        float s = 0.f;
#pragma unroll 1
        for (int i = 0; i < 4; i++) {
          s += (bf_lo(v[0].x) + bf_hi(v[0].x)) + (bf_lo(v[0].y) + bf_hi(v[0].y)) + (bf_lo(v[0].z) + bf_hi(v[0].z)) + (bf_lo(v[0].w) + bf_hi(v[0].w));
          v[0] = v[1]; v[1] = v[2]; v[2] = v[3];
        }
#pragma unroll
        for (int o = 16; o; o >>= 1) s += __shfl_xor_sync(~0u, s, o);
        if (lane == 0) sts2f(mb + B_SW, s, __uint_as_float(ep + 1));
       }
        const uint32_t xa = sm + (c3 * 16 + r4) * 128 + ((c8 ^ r4) << 4);
        const uint4* gx = (const uint4*)(P.x + (b * 16 + r4) * D_ + kl) + c8;
        uint32_t e[4] = {0, 0, 0, 0};
        uint4 wq;
#pragma unroll 1
        for (int kb = wid == 10 ? 0 : 12; kb < (wid == 10 ? 12 : 16); kb++) {
          uint4 v[4];
          if (!(kb & 3)) wq = ld_cg4((const uint4*)(P.wr + k_of(kb + r4)) + c8);
          if (kb >= 12) {
#pragma unroll
            for (int j = 0; j < 4; j++) v[j] = ld_cg4(gx + j * 512);
            gx += 8;
          } else {
            const uint32_t so = xa + xoff(kb & 3, hf);
            mbar_wait(mb + B_FULL + 8 * (kb & 3), (kb >> 2) & 1);
            v[0] = lds4_o<0>(so); v[1] = lds4_o<512>(so ^ 64); v[2] = lds4_o<1024>(so); v[3] = lds4_o<1536>(so ^ 64);
            if (lane < 2) mbar_arrive_rem(eb + 8 * (kb & 3) + ((v[0].x | v[1].x | v[2].x | v[3].x) & zero));
          }
#pragma unroll
          for (int j = 0; j < 16; j++) {
            const uint32_t u = (j & 3) == 0 ? v[j >> 2].x : (j & 3) == 1 ? v[j >> 2].y : (j & 3) == 2 ? v[j >> 2].z : v[j >> 2].w;
            const float d0 = bf_lo(u), d1 = bf_hi(u);
            a[j >> 2] += d0 + d1; a[4 + (j >> 2)] = fmaf(d0, d0, fmaf(d1, d1, a[4 + (j >> 2)]));
          }
          cut(zero);
          const int sl = (kb & 3) * 8 + c8;
          const uint4 wn = make_uint4(__shfl_sync(~0u, wq.x, sl), __shfl_sync(~0u, wq.y, sl), __shfl_sync(~0u, wq.z, sl), __shfl_sync(~0u, wq.w, sl));
#pragma unroll
          for (int j = 0; j < 4; j++) e[j] = hfma2(v[j].x, wn.x, hfma2(v[j].y, wn.y, hfma2(v[j].z, wn.z, hfma2(v[j].w, wn.w, e[j]))));
        }
        float mean, pd;
#pragma unroll 1
        for (int h = 0; h < 2; h++) {
          float u[4], v[2];
#pragma unroll
          for (int i = 0; i < 4; i++) u[i] = ((lane & 4) ? a[4 + i] : a[i]) + __shfl_xor_sync(~0u, (lane & 4) ? a[i] : a[4 + i], 4);
#pragma unroll
          for (int i = 0; i < 2; i++) v[i] = ((lane & 2) ? u[2 + i] : u[i]) + __shfl_xor_sync(~0u, (lane & 2) ? u[i] : u[2 + i], 2);
          mean = pd;
          pd = ((lane & 1) ? v[1] : v[0]) + __shfl_xor_sync(~0u, (lane & 1) ? v[0] : v[1], 1);
#pragma unroll
          for (int j = 0; j < 4; j++) { a[j] = bf_lo(e[j]); a[4 + j] = bf_hi(e[j]); }
        }
        if (wid == 11) {
          sts2f(sm + OFF_COLSUM + 512 + lane * 8, mean, pd);
          fence_gpu();
          bar_arrive(5, 96); PTS(0);
          if (elect_one()) {
#pragma unroll 1
            for (int p = 0; p < 16; p++) {
              const uint32_t ad = sm + bar3(0) + o3(p);
              mbar_init(ad, 1); mbar_init(ad + 256, 1); mbar_init(ad + 448, 8); mbar_init(ad + 704, p == 0 ? 16 >> rank : p == 12 ? 1 : p == 15 ? 7 : 8);
              mbar_expect_tx(ad, 8192); mbar_expect_tx(ad + 256, 8192); mbar_expect_tx(mb + B_FULL3 + 8 * p, SLOT_B);
            }
            asm volatile("fence.mbarrier_init.release.cluster;" ::: "memory");
            fence_async_smem();
            mbar_arrive_rem(bars + B_LATE); mbar_arrive_rem((1u << 24) + bars + B_LATE);
          }
          __syncwarp();
        } else {
          if (lane == 0) PTS(1);
          bar_sync(5, 96);
          const float2 u = lds2f(sm + OFF_COLSUM + 512 + lane * 8), sw = lds2f(mb + B_SW);
          mean = (mean + u.x) * (1.f / D_);
          pd += u.y;
          pd += __shfl_xor_sync(~0u, pd, 4);
          const float var = fmaxf(fmaf(-mean, mean, __shfl_xor_sync(~0u, mean, 4)), 0.f);
          const uint32_t tag = __float_as_uint(sw.y) & 255;
          if (c8 < 4) {
            st_rlx2((uint2*)G.st1 + (b >> 1) * 96 + rank * 16 + r4 + 4 * c8, tagged(-mean, tag), tagged(rsq(var + 1e-5f), tag));
            st_rlx(&G.pred[b * 16 + r4 + 4 * c8], (ordered(fmaf(-mean, sw.x, pd)) & ~255u) | tag);
          }
        }
      }
      if (wid < 11) gather(lds1(mb + B_SW + 4) & 255);
      if (wid == 9) {
        if (lane == 0) PTS(6);
        {
          const uint4 sv = make_uint4(SENT, SENT, SENT, SENT);
          uint4* y = &G.ybuf[b * NFFN * 4 + lane];
#pragma unroll
          for (int i = 0; i < 14; i++) y[i * 32] = sv;
          if (lane < 16) G.st2[b * 16 + lane] = make_uint4(0, 0, 0, 0);
          G.hsel[b * 64 + lane] = sv; G.hsel[b * 64 + 32 + lane] = sv;
          if (b < 8) { G.cand[b * 32 + lane] = SENT; G.cst[b * 32 + lane] = make_uint4(0, 0, 0, 0); }
          fence_gpu();
          __syncwarp();
          if (lane == 0) mbar_arrive(mb + B_LATE);
        }
      } else if (wid == 10) {
        {
          mbar_wait(mb + B_FULL + 24, 1);
#pragma unroll 1
          for (int r = -4; r < (fidx >= 0 ? 16 : 0); r++) {
            l2_prefetch((r < 0 ? (const char*)P.wo + (b + 1) * 16384 : (const char*)P.wd + fidx * 65536) + r * 4096 + lane * 128);
            delay(clk(), PDT);
          }
          PTS(4);
        }
      }
      mbar_wait(mb + B_LATE, 0);
      if (wid == 9) {
        if (elect_one()) {
          wait3(60);
#pragma unroll 1
          for (int p = 0; p < 16; p++) {
            const bool mix = (unsigned)(p - 1) < 8;
            const int c1 = mix ? ((p - 1) >> 1) * 16 : 0, c2 = mix ? (hf ^ 1) * 8 + ((p - 1) & 1) * 4 : chunk_of(p) * 4;
            const uint32_t d = sm + (uint32_t)((WO_SLOTS >> (4 * p)) & 15) * SLOT_B;
            if ((0xFE22 >> p) & 1) mbar_wait(p < 9 ? mb + B_EMPTY + 8 * (p >> 2) : sm + bar3(32) + 8 * (p - 9), p < 9);
            if (EFWO) asm volatile("cp.async.bulk.tensor.4d.shared::cluster.global.mbarrier::complete_tx::bytes.L2::cache_hint [%0], [%1, {0, %3, %4, %5}], [%2], %6;"
                         :: "r"(d), "l"(mix ? &tmM : &tmO), "r"(mb + B_FULL3 + 8 * p), "r"(c1), "r"(c2), "r"(c3 * 2), "l"(l2_stream()) : "memory");
            else asm volatile("cp.async.bulk.tensor.4d.shared::cluster.global.mbarrier::complete_tx::bytes [%0], [%1, {0, %3, %4, %5}], [%2];"
                         :: "r"(d), "l"(mix ? &tmM : &tmO), "r"(mb + B_FULL3 + 8 * p), "r"(c1), "r"(c2), "r"(c3 * 2) : "memory");
            if (p >= 10) PTS(7 + p);
          }
          if (fidx >= 0) {
            mbar_expect_tx(mb + B_FULL, 65536);
#pragma unroll 1
            for (int i = 0; i < 8; i++) {
              const int f = (0x76325140 >> (4 * i)) & 15;
              const uint32_t d = sm + ((GU_SLOTS >> (4 * f)) & 15) * SLOT_B, fb = mb + (i < 4 ? B_FULL : B_FFN);
              mbar_wait(sm + bar3(32) + o3(7 + i - (i > 5)), 0);
              tma_2d(d, &tmG, fidx * 32, f * 128, fb, EFF);
              tma_2d(d + 8192, &tmU, fidx * 32, f * 128, fb, EFF);
              PTS(23 + i);
            }
#pragma unroll 1
            for (int i = 0; i < 4; i++) {
              mbar_wait(sm + bar3(32) + o3(13 + ((i + 1) >> 1)), 0);
              tma_3d(sm + ((D_SLOTS >> (4 * i)) & 15) * SLOT_B, &tmD, 0, fidx * 32, i * 4, mb + B_FFN + 8, EFF);
            }
          }
        }
      } else if (wid == 11) {
        const uint2 w = ld_rlx2((const uint2*)(P.wr + c3 * 128) + lane);
        wait3(36);
        sts1(sm + OFF_LNP + (lane & 1) * 128 + (lane >> 1) * 4, w.x); sts1(sm + OFF_LNP + (lane & 1) * 128 + 64 + (lane >> 1) * 4, w.y);
        if (lane < 16) sts1(sm + OFF_LNP + 256 + lane * 4, 0x3F803F80u);
        const uint32_t tag = lds1(mb + B_SW + 4) & 255;
        uint4 k;
        for (int it = 0;; it++) {
          k = ld_rlx4((const uint4*)&G.pred[rb * 256 + hf * 64 + r2 * 128] + c16);
          k.x ^= tag; k.y ^= tag; k.z ^= tag; k.w ^= tag;
          if (!__any_sync(~0u, (k.x | k.y | k.z | k.w) & 255)) break;
          SPINCHK(it, 13);
        }
        const uint2 ahead = top2(k.x | (lane * 4), k.y | (lane * 4 + 1), k.z | (lane * 4 + 2), k.w | (lane * 4 + 3));
        if (lane == 0) sts2f(sm + OFF_MSC + 8, __uint_as_float((ahead.x & 127) ^ NOSPEC), __uint_as_float((ahead.y & 127) ^ NOSPEC));
        __syncwarp();
        if (lane == 0) mbar_arrive(mb + B_FULL3 + 8 * 15);
      } else if (fidx >= 0 && elect_one()) {
#pragma unroll 1
        for (int i = 0; i < NPD; i++) { mbar_wait(sm + bar3(32) + o3(PD0 + i), 0); tma_2d(sm + OFF_COLSUM, &tmPD, 0, fidx * 256 + i * 32, mb + B_FFN, false); }
      }
    }
    __syncwarp();
    const float sw = __uint_as_float(lds1(mb + B_SW));
    const int rr = lane >> 4, row00 = rb * 256 + hf * 64;
    uint2 pick;
    if (wid == 8) {
      wait3(61);
      delay(clk(), SDELAY);
      uint4 v;
      int id;
      for (int it = 0;; it++) {
        v = ld_rlx4(&G.cst[jp * 32 + lane]);
        id = __float2int_rn(__uint_as_float(v.w));
        if (!__any_sync(~0u, (id & 15) != 8)) break;
        SPINCHK(it, 14);
      }
      float2 pr;
      const uint32_t k = route(v, sw, id >> 4, pr);
      pick.x = __reduce_max_sync(~0u, k); pick.y = __reduce_max_sync(~0u, k == pick.x ? 0 : k);
      if (k == pick.x || k == pick.y) sts4(sm + OFF_MSC + 16 + (k == pick.y) * 16, k, lane, __float_as_uint(pr.x), __float_as_uint(pr.y));
      __syncwarp();
      if (lane == 0) { mbar_arrive(mb + B_SEL); PTS(16); }
    } else if (wid == 9) {
      wait3(61);
      delay(clk(), LDELAY);
      uint4 v[4];
      for (int it = 0;; it++) {
#pragma unroll
        for (int i = 0; i < 4; i++) v[i] = ld_rlx4(&G.st2[row00 + (i >> 1) * 128 + (i & 1) * 32 + lane]);
        if (!__any_sync(~0u, (v[0].w & v[1].w & v[2].w & v[3].w) != 0x41000000u)) break;
        SPINCHK(it, 6);
      }
      uint32_t k[4];
#pragma unroll
      for (int i = 0; i < 4; i++) {
        float2 pr;
        k[i] = route(v[i], sw, row00 + (i >> 1) * 128 + (i & 1) * 32 + lane, pr);
        const float nm = __uint_as_float(v[i].x) * (-1.f / D_);
        sts2f(sm + OFF_LNP + (i * 32 + lane) * 8, __uint_as_float(pack2(pr.x, pr.x)), __uint_as_float(pack2(nm, nm)));
      }
      const uint2 m = top2(k[0], k[1], k[2], k[3]);
      if (lane == 0) { st_rlx2(&G.cand[c3 * 32 + (rb * 2 + hf) * 2], m.x, m.y); sts2f(sm + OFF_MSC + 0, __uint_as_float(m.x), __uint_as_float(m.y)); }
      wait3(62);
      __syncwarp();
      if (lane == 0) { mbar_arrive(mb + B_OUT); PTS(12); }
      const int ca = 2047 - (((lane & 4) ? m.y : m.x) & 2047), ta = ((ca >> 1) & 64) + (ca & 63);
      uint32_t h0, h1, h2, h3;
      ldsm4_o<0>(sm + HST + ta * 256 + ((((lane & 3) * 4 + (lane >> 3)) ^ (ta & 7)) << 4), h0, h1, h2, h3);
      st_rlx4(&G.hsel[(32 + (rb * 2 + hf) * 2 + rr) * 128 + c3 * 16 + (lane & 15)], make_uint4(h0, h1, h2, h3));
    }
    mbar_wait(mb + B_OUT, 0);
    const float2 cf = lds2f(sm + OFF_MSC + 0);
    const int ca0 = ~__float_as_int(cf.x), ca1 = ~__float_as_int(cf.y), cand0 = ((ca0 >> 1) & 64) + (ca0 & 63), cand1 = ((ca1 >> 1) & 64) + (ca1 & 63);
    auto norm = [](const uint4& v, const float2& pr) {
      const uint32_t r = __float_as_uint(pr.x), m = __float_as_uint(pr.y);
      return make_uint4(hfma2(hadd2(v.x, m), r, v.x), hfma2(hadd2(v.y, m), r, v.y), hfma2(hadd2(v.z, m), r, v.z), hfma2(hadd2(v.w, m), r, v.w));
    };
    uint4* const og = (uint4*)(P.out + row00 * D_ + c3 * 128) + (lane & 15);
    if (wid == 8) {
      delay(clk(), CDELAY);
      uint32_t k;
      for (int it = 0;; it++) { k = ld_rlx(&G.cand[c3 * 32 + lane]); if (!__any_sync(~0u, k == SENT)) break; SPINCHK(it, 12); }
      const uint32_t m1 = __reduce_max_sync(~0u, k), m2 = __reduce_max_sync(~0u, k == m1 ? 0 : k);
      const uint32_t miss = ((m1 ^ pick.x) | (m2 ^ pick.y)) & 2047;
      if (miss && (k == m1 || k == m2)) {
        float2 pr;
        route(ld_rlx4(&G.st2[2047 - (k & 2047)]), sw, 0, pr);
        sts4(sm + OFF_MSC + 48 + (k == m2) * 16, k, 32 + lane, __float_as_uint(pr.x), __float_as_uint(pr.y));
      }
      if (lane == 0) sts1(sm + OFF_MSC + 80, miss);
      __syncwarp();
      if (lane == 0) { mbar_arrive(mb + B_SEL2); PTS(13); }
      const uint32_t kc = __float_as_uint(rr ? cf.y : cf.x);
      const int c = rr ? cand1 : cand0;
      if (kc != m1 && kc != m2) og[(c + (c & 64)) * 128] = norm(lds4(sm + HST + c * 256 + (((lane & 15) ^ (c & 7)) << 4)), lds2f(sm + OFF_LNP + c * 8));
    }
#pragma unroll 1
    for (int t0 = wid == 8 ? 120 : (11 - wid) * 8; t0 < (wid == 8 ? 128 : 120) * !NOOUT; t0 += 24) {
      uint4 v[4];
      float2 pr[4];
      const uint32_t ad = sm + HST + t0 * 256 + lane * 16;
      static_for<0, 4>([&](auto ic) { constexpr int i = decltype(ic)::value; v[i] = lds4_o<i * 512>(ad ^ (rr << 4) ^ (i << 5)); pr[i] = lds2f_o<i * 16>(sm + OFF_LNP + (t0 + rr) * 8); });
#pragma unroll
      for (int i = 0; i < 4; i++) v[i] = norm(v[i], pr[i]);
      if (t0 >= OHOLD) wait3(63);
#pragma unroll
      for (int i = 0; i < 4; i++) {
        const int tr = t0 + rr + 2 * i;
        if (tr != cand0 && tr != cand1) {
          if (OUTEF) asm volatile("st.global.L2::cache_hint.v4.u32 [%0], {%1,%2,%3,%4}, %5;" :: "l"(og + (tr + (tr & 64)) * 128), "r"(v[i].x), "r"(v[i].y), "r"(v[i].z), "r"(v[i].w), "l"(l2_stream()) : "memory");
          else og[(tr + (tr & 64)) * 128] = v[i];
        }
      }
    }
    if (wid == 11 && lane == 0) PTS(31);
  } else {
    asm volatile("setmaxnreg.inc.sync.aligned.u32 224;");
    const int t128 = tid & 127, warp = wid & 3, g = lane >> 2, t = lane & 3;
    const int mb3 = rb * 4 + wg * 2 + hf;
    uint32_t pq[2][16];
    float acc[64];
    {
      float acc0[96], acc1[96];
#pragma unroll
      for (int i = 0; i < 96; i++) { asm volatile("" : "=f"(acc0[i])); asm volatile("" : "=f"(acc1[i])); }
      const uint32_t xo0 = dlo(sb, 16) + hf * 512, xo1 = dlo(sb, 16) + (hf ^ 1) * 512;
      const uint32_t eb0 = (t128 << 24) + bars + B_EMPTY;
#pragma unroll 1
      for (int kb = 0; kb < 12; kb++) {
        const int s = kb & 3;
        mbar_wait(mb + B_FULL + 8 * s, (kb >> 2) & 1);
        if (LOCK) bar_sync(13, 256);
        if (kb == 0) TS(1);
        const uint32_t xs = xoff(s, wg) >> 4, ws = dlo(sb + woff(s), WSTR);
        pin(acc0); pin(acc1);
        wg_fence();
#pragma unroll
        for (int k = 0; k < 4; k++) {
          const uint64_t db = dsc<1024, 1>(ws + k * 128);
          const int sd = k == 0 ? kb : 1;
          wgmma_n192_ss<0, 1, 0>(acc0, dsc<1024, 1>(xs + xo0 + k * 2), db, sd);
          wgmma_n192_ss<0, 1, 0>(acc1, dsc<1024, 1>(xs + xo1 + k * 2), db, sd);
          if (k == RELK || k == 3) wg_commit();
          if (k == RELK) {
            wg_wait<1>();
            if (kb > 0 && t128 < 2) mbar_arrive_rem(eb0 + 8 * ((kb - 1) & 3));
          }
        }
        pin(acc0); pin(acc1);
      }
      float qa0[32], qa1[32], kv0[64], kv1[64];
#pragma unroll
      for (int i = 0; i < 96; i++) { if (i < 32) { qa0[i] = acc0[i]; qa1[i] = acc1[i]; } else { kv0[i - 32] = acc0[i]; kv1[i - 32] = acc1[i]; } }
      uint2 st[2][2];
      uint4 am;
      auto center = [&](float (&q)[32], float (&kv)[64], const uint2 (&v)[2]) {
        const uint32_t n0 = v[0].x & (t == 0 ? ~255u : 0u), n1 = v[1].x & (t == 0 ? ~255u : 0u);
        am = make_uint4(__byte_perm(n0, 0, 0x3232), __byte_perm(n1, 0, 0x3232),
                        __byte_perm(__float_as_uint(__uint_as_float(n0) - bf_hi(n0)), 0, 0x3232), __byte_perm(__float_as_uint(__uint_as_float(n1) - bf_hi(n1)), 0, 0x3232));
        wg_fence();
        wgmma_n64_rs<1, 0>(q, am.x, am.y, am.z, am.w, dsc<32, 0>(dlo(sb + OFF_COLSUM, 0)), 1);
        wgmma_n128_rs<1, 0>(kv, am.x, am.y, am.z, am.w, dsc<32, 0>(dlo(sb + OFF_COLSUM + 256, 0)), 1);
      };
      auto load_st = [&]() {
        mbar_wait(mb + B_AUX, 0);
#pragma unroll
        for (int i = 0; i < 4; i++) st[i >> 1][i & 1] = ld_rlx2((const uint2*)G.st1 + ((rb * 4 + wg * 2 + ((i >> 1) ^ hf)) * 2 + (warp >> 1)) * 96 + (warp & 1) * 16 + (i & 1) * 8 + g);
      };
      if (!wg) {
        wg_wait<0>();
        if (t128 < 2) mbar_arrive_rem(eb0 + 24);
        load_st();
#pragma unroll 1
        for (int s = 0; s < 4; s++) mbar_wait(mb + B_FULL + 8 * s, 1);
        bar_sync(6, 256);
      }
      static_for<0, 4>([&](auto sc) {
        constexpr int s = decltype(sc)::value;
        if (wg) mbar_wait(mb + B_FULL + 8 * s, 1);
        const uint32_t xs = (wg ? xoff(s, 1) : xoff(s, 0)) >> 4, ws = dlo(sb + woff(s) + WSTR, WSTR);
        pin(kv0); pin(kv1); pin(qa0); pin(qa1);
        wg_fence();
#pragma unroll
        for (int k = 0; k < 4; k++) {
          const uint64_t db = dsc<1024, 1>(ws + k * 128);
          wgmma_n128_ss<0, 1, 0>(kv0, dsc<1024, 1>(xs + xo0 + k * 2), db, 1);
          wgmma_n128_ss<0, 1, 0>(kv1, dsc<1024, 1>(xs + xo1 + k * 2), db, 1);
          if (k == 3 || (k == 2 && s == 0)) wg_commit();
          if (k == (s ? 3 : 2) && s < 3) {
            wg_wait<1>();
            if (s == 0) { if (wg && t128 < 2) mbar_arrive_rem(eb0 + 24); }
            else if (!wg) bar_arrive(8 + s, 256);
          }
        }
        if (s == STLD && wg) load_st();
      });
      center(qa0, kv0, st[0]);
      wg_commit();
      if (wg) bar_arrive(6, 256);
      float rl[2][2];
      uint32_t r2[2][2];
#pragma unroll
      for (int i = 0; i < 4; i++) { const float r = __uint_as_float(st[i >> 1][i & 1].y & ~255u); r2[i >> 1][i & 1] = pack2(r, r); rl[i >> 1][i & 1] = r * 1.4426950408889634f; }
      const uint32_t sad = sm + (wg ? 11 : 2) * SLOT_B + (warp * 16 + (lane & 15)) * 128 + (((lane >> 4) ^ (lane & 7)) << 4);
      wg_wait<0>();
      pin(kv0); pin(kv1); pin(qa0); pin(qa1); pin4(am);
      center(qa1, kv1, st[1]);
      wg_commit();
      if (wg) bar_arrive(11, 256);
      if (CUTS & 1) cut(zero);
      TS(2);
      auto phi8 = [&](const float* a, int m) {
        return make_uint4(phi2(a[0], a[1], r2[m][0], rl[m][0]), phi2(a[2], a[3], r2[m][1], rl[m][1]), phi2(a[4], a[5], r2[m][0], rl[m][0]), phi2(a[6], a[7], r2[m][1], rl[m][1]));
      };
      auto stage = [&](float (&a)[64], auto mc) {
        constexpr int m = decltype(mc)::value;
        uint4 r[4];
#pragma unroll
        for (int j = 0; j < 4; j++) r[j] = phi8(a + j * 8, m);
        if (m == 0 || wg) bar_sync(wg ? 9 + m : 11, 256 + (r[SBAR].x & zero));
#pragma unroll
        for (int j = 0; j < 4; j++) {
          const int v = 32 + j * 8;
          stsm4_o<WSTR + m * 8192>(sad ^ (j << 5), hmul2(pack2(a[v], a[v + 1]), r2[m][0]), hmul2(pack2(a[v + 2], a[v + 3]), r2[m][1]),
                                                   hmul2(pack2(a[v + 4], a[v + 5]), r2[m][0]), hmul2(pack2(a[v + 6], a[v + 7]), r2[m][1]));
        }
#pragma unroll
        for (int j = 0; j < 4; j++) stsm4_o<m * 8192>(sad ^ (j << 5), r[j].x, r[j].y, r[j].z, r[j].w);
      };
      stage(kv0, std::integral_constant<int, 0>{});
      wg_wait<0>();
      pin(kv1); pin(qa1); pin4(am);
      stage(kv1, std::integral_constant<int, 1>{});
      fence_async_smem();
      TS(3);
      uint32_t xr[8][4], done = 0;
      auto load_xr = [&]() {
        const uint32_t xa = sm + hf * 8192 + (warp * 16 + (lane & 15)) * 128 + (((lane >> 4) ^ (lane & 7)) << 4);
#pragma unroll
        for (int q = 0; q < 8; q++) { ldsm4_o<0>((xa ^ ((q & 3) << 5)) + xoff(rank * 2 + (q >> 2), wg), xr[q][0], xr[q][1], xr[q][2], xr[q][3]); done |= xr[q][3]; }
      };
      if (!wg) { bar_arrive(4, 256); load_xr(); }
      else {
        float ka[36];
#pragma unroll
        for (int i = 0; i < 36; i++) ka[i] = 0.f;
        auto kv_mma = [&](auto ic) {
          constexpr int i = decltype(ic)::value;
          constexpr uint32_t o = sb + (i < 8 ? 11 : 2) * SLOT_B + (i & 7) * 2048;
          wgmma_n72_ss<1, 1, 0>(ka, dsc<1024, 1>(dlo(o, 8192)), dsc<1024, 1>(dlo(o + WSTR, sb + OFF_STATS - o - WSTR)), i);
        };
        mbar_wait(mb + B_LATE, 0);
        bar_sync(3, 128);
        wg_fence();
        static_for<0, 8>(kv_mma);
        wg_commit();
        uint4* dst = &G.kvp[cg * 2304 + rb * 32];
        if (CUTS & 4) cut(zero);
        load_xr();
        bar_sync(4, 256);
        static_for<8, 16>(kv_mma);
        wg_commit();
        if (QHOLD == 1) bar_arrive(8, 256);
        wg_wait<0>();
        pin(ka);
        if (QHOLD == 2) bar_arrive(8, 256);
        TS(4);
        if (warp < 2) {
          st_rlx4(dst + warp * 512 + lane, make_uint4(pack2(ka[0], ka[1]), pack2(ka[4], ka[5]), pack2(ka[8], ka[9]), pack2(ka[12], ka[13])));
          st_rlx4(dst + warp * 512 + 256 + lane, make_uint4(pack2(ka[2], ka[3]), pack2(ka[6], ka[7]), pack2(ka[10], ka[11]), pack2(ka[14], ka[15])));
        } else {
          st_rlx4(dst + warp * 512 + lane, make_uint4(pack2(ka[16], ka[17]), pack2(ka[20], ka[21]), pack2(ka[24], ka[25]), pack2(ka[28], ka[29])));
          st_rlx4(dst + warp * 512 + 256 + lane, make_uint4(pack2(ka[18], ka[19]), pack2(ka[22], ka[23]), pack2(ka[26], ka[27]), pack2(ka[30], ka[31])));
        }
        st_rlx((uint32_t*)(dst + 2048) + t128, pack2(ka[32], ka[34]));
        if (QHOLD == 3) bar_arrive(8, 256);
        if (t128 == 0) mbar_arrive(sm + bar3(60));
      }
      TS(5);
      auto q_half = [&](float (&q)[32], uint32_t xo, auto mc) {
        constexpr int m = decltype(mc)::value;
        bar_sync(wg ? 7 : 8, 256 + (done & zero));
#pragma unroll 1
        for (int s = 0; s < 4; s++) {
          const uint32_t xs = (xoff(s, wg) >> 4) + xo, ws = dlo(sb + woff(s), 8192);
          pin(q);
          wg_fence();
#pragma unroll
          for (int k = 0; k < 4; k++) wgmma_n64_ss<0, 1, 0>(q, dsc<1024, 1>(xs + k * 2), dsc<1024, 1>(ws + k * 128), 1);
          wg_commit();
        }
        if (m || !wg) bar_arrive(wg ? 8 : 7, 256);
        wg_wait<0>();
        pin(q);
        if (m == 0) {
          if (t128 == 0) mbar_arrive(mb + B_EMPTY + 8 * wg);
          if (wg && lane == 0) mbar_arrive_rem(sb + bar3(48));
          if (CUTS & 2) cut(zero);
          TS(29);
        }
#pragma unroll
        for (int j = 0; j < 4; j++) {
          const uint4 r = phi8(q + j * 8, m);
          pq[m][j * 4] = r.x; pq[m][j * 4 + 1] = r.y; pq[m][j * 4 + 2] = r.z; pq[m][j * 4 + 3] = r.w;
          done |= r.x | r.w;
        }
      };
      q_half(qa1, xo1, std::integral_constant<int, 1>{});
      q_half(qa0, xo0, std::integral_constant<int, 0>{});
#pragma unroll
      for (int q = 0; q < 32; q++) { asm volatile("" : "+r"(xr[q >> 2][q & 3])); acc[q * 2] = bf_lo(xr[q >> 2][q & 3]); acc[q * 2 + 1] = bf_hi(xr[q >> 2][q & 3]); }
#pragma unroll
      for (int i = 0; i < 16; i++) asm volatile("" : "+r"(pq[0][i]), "+r"(pq[1][i]) :: "memory");
      pin(acc);
      TS(6);
      if (!wg) {
        uint4 a[2], v[2][8];
        uint32_t z[8], zs;
        const uint4* src = &G.kvp[cg * 2304 + warp * 512 + lane];
        const uint32_t* zsrc = (const uint32_t*)&G.kvp[cg * 2304 + 2048] + t128;
        mbar_wait(mb + B_KVL, 0);
        static_for<0, 16>([&](auto ic) { constexpr int i = decltype(ic)::value; v[i >> 3][i & 7] = lds4_o<sb + 11 * SLOT_B + i * 512>(own + (warp + (warp & 2)) * 8192 + lane * 16); });
#pragma unroll
        for (int i = 0; i < 8; i++) z[i] = lds1(sm + 2 * SLOT_B + i * 512 + t128 * 4);
#pragma unroll 1
        for (int it = 0;; it++) {
          zs = hadd2(hadd2(hadd2(z[0], z[1]), hadd2(z[2], z[3])), hadd2(hadd2(z[4], z[5]), hadd2(z[6], z[7])));
#pragma unroll
          for (int h = 0; h < 2; h++) a[h] = hadd8(hadd8(hadd8(v[h][0], v[h][1]), hadd8(v[h][2], v[h][3])), hadd8(hadd8(v[h][4], v[h][5]), hadd8(v[h][6], v[h][7])));
          const uint4 c = hadd8(a[0], a[1]);
          TSV(20, it + 1);
          if (!__any_sync(~0u, hnan(hadd2(hadd2(hadd2(c.x, c.y), hadd2(c.z, c.w)), zs)))) break;
          uint32_t mm = 0;
#pragma unroll
          for (int i = 0; i < 8; i++) {
            const uint32_t m = max4(max4(z[i], v[0][i]), v[1][i]);
            if (m == SENT) { v[0][i] = ld_rlx4(src + i * 32); v[1][i] = ld_rlx4(src + 256 + i * 32); z[i] = ld_rlx(zsrc + i * 128); }
            mm = max(mm, m);
          }
          if (!__any_sync(~0u, mm == SENT)) break;
          SPINCHK(it, 4);
        }
        TS(23);
        const uint32_t kb0 = sm + OFF_KVB + warp * 2048 + (lane & 7) * 128;
#pragma unroll
        for (int h = 0; h < 2; h++) stsm4(kb0 + h * 1024 + (((lane >> 3) ^ (lane & 7)) << 4), a[h].x, a[h].y, a[h].z, a[h].w);
        asm volatile("stmatrix.sync.aligned.m8n8.x2.shared.b16 [%0], {%1,%2};" :: "r"(kb0 + (lane & 8) * 128 + ((4 ^ (lane & 7)) << 4)), "r"(zs), "r"(zs >> 16) : "memory");
        fence_async_smem();
        bar_arrive(12, 256);
      }
      bar_sync(wg ? 12 : 2, wg ? 256 : 128);
    }
    TS(7);
    const int tid2 = __shfl_sync(~0u, tid, lane);
    {
    const int t128 = tid2 & 127, lane = tid2 & 31, g = lane >> 2, t = lane & 3;
    uint4 abuf[4][4], ost[2][4];
    uint4* const od0 = &G.obuf[(mb3 * 64 + cg * 4) * 128 + t128];
    uint4* const od1 = &G.obuf[((mb3 ^ 1) * 64 + hf * 32 + c3) * 128 + t128];
    uint32_t to;
    {
      float oa[4][20];
#pragma unroll
      for (int i = 0; i < 80; i++) oa[i / 20][i % 20] = 0.f;
      auto o_mma = [&](int i) {
#pragma unroll
        for (int ks = 0; ks < 2; ks++) {
          const uint32_t* a = pq[i >> 1] + (i & 1) * 8 + ks * 4;
          wgmma_n40_rs<1, 0>(oa[i], a[0], a[1], a[2], a[3], dsc<1024, 1>(dlo(sb + OFF_KVB + (i & 1) * 4096 + ks * 2048, 8192)), ks);
        }
      };
      auto o_norm = [&](int i) {
        const float (&d)[20] = oa[i];
        const float i0 = rcp(d[16] + 1e-6f), i1 = rcp(d[18] + 1e-6f);
#pragma unroll
        for (int k2 = 0; k2 < 2; k2++)
          ost[i >> 1][(i & 1) * 2 + k2] = make_uint4(pack2(d[k2 * 8] * i0, d[k2 * 8 + 1] * i0), pack2(d[k2 * 8 + 2] * i1, d[k2 * 8 + 3] * i1),
                                                     pack2(d[k2 * 8 + 4] * i0, d[k2 * 8 + 5] * i0), pack2(d[k2 * 8 + 6] * i1, d[k2 * 8 + 7] * i1));
      };
      if (lane == 0) mbar_arrive_rem((wg << 24) + sb + bar3(48));
      to = clk();
      wg_fence();
      o_mma(2);
      wg_commit();
      o_mma(0);
      wg_commit();
      wg_wait<1>();
      pin(oa[2]);
      o_norm(2);
      st_rlx4(od1, ost[1][0]); st_rlx4(od1 + 1024, ost[1][1]);
      wg_fence();
      o_mma(1); o_mma(3);
      wg_commit();
      wg_wait<0>();
      pin(oa[0]); pin(oa[1]); pin(oa[3]);
#pragma unroll
      for (int i = 0; i < 16; i++) asm volatile("" : "+r"(pq[0][i]), "+r"(pq[1][i]) :: "memory");
      o_norm(0); o_norm(1); o_norm(3);
#pragma unroll
      for (int i = 0; i < 4; i++) abuf[0][i] = ost[0][i];
    }
    TS(8);
    {
      const uint32_t la = own + wg * 8192 + t128 * 16, fa = sm + wg * 256;
#pragma unroll
      for (int i = 4; i < 16; i++) abuf[i >> 2][i & 3] = make_uint4(0, 0, 0, 0);
#pragma unroll 1
      for (int pp = 0; pp < 16; pp += 4) {
        static_for<0, 4>([&](auto jc) {
          constexpr int j = decltype(jc)::value;
          constexpr uint32_t ro = sb + (10 + ((j + 1) & 3)) * SLOT_B;
          const int p = pp + j;
          const uint32_t o1 = ((p + 1) >> 3) * 128 + ((p + 1) & 7) * 8;
          uint4 (&a)[4] = abuf[j];
          uint4 (&n)[4] = abuf[(j + 1) & 3];
          auto fetch = [&]() {
            mbar_wait(fa + bar3(0) + o1, 0);
            n[0] = lds4_o<ro>(la); n[1] = lds4_o<ro + 2048>(la); n[2] = lds4_o<ro + 4096>(la); n[3] = lds4_o<ro + 6144>(la);
          };
          const bool early = j == 3 ? pp < 12 : (j > 0 || pp > 0);
          const uint32_t bs = dlo(sb, 8192) + ((WO_SLOTS >> (4 * p)) & 15) * (SLOT_B >> 4);
          mbar_wait(mb + B_FULL3 + 8 * p, 0);
          if (early) fetch();
          if (p == 1) TS(28);
          if (p == 2) TS(9);
          pin(acc);
          wg_fence();
#pragma unroll
          for (int k = 0; k < 4; k++) wgmma_n128_rs<1, 0>(acc, a[k].x, a[k].y, a[k].z, a[k].w, dsc<1024, 1>(bs + k * 128), 1);
          wg_commit();
          if (pp == 0) {
            if (j == 0) {
              delay(to, BDELAY);
#pragma unroll
              for (int k = 2; k < 4; k++) st_rlx4(od1 + k * 1024, ost[1][k]);
            }
            if (j == ((jp >> 1) & 1) + W0OFF) {
#pragma unroll
              for (int k = 0; k < 4; k++) st_rlx4(od0 + k * 128, ost[0][k]);
            }
            if (j == 0) { TS(24); fetch(); TS(27); }
          }
          if (__any_sync(~0u, max(max4(max4(0, n[0]), n[1]), max4(max4(0, n[2]), n[3])) == SENT)) {
            int pl = p + 1; asm volatile("" : "+r"(pl));
            const uint4* q = &G.obuf[(mb3 * 64 + chunk_of(pl) * 4) * 128 + t128];
#pragma unroll 1
            for (int it = 0;; it++) {
#pragma unroll
              for (int i = 0; i < 4; i++) n[i] = ld_rlx4(q + i * 128);
              TSV(21, _ts + 1);
              if (!__any_sync(~0u, max(max4(max4(0, n[0]), n[1]), max4(max4(0, n[2]), n[3])) == SENT)) break;
              SPINCHK(it, 5);
            }
          }
          if (lane == 0 && p < 11) mbar_arrive_rem((wg << 24) + sb + bar3(48) + o1);
          wg_wait<1>();
          pin(acc);
#pragma unroll
          for (int i = 0; i < 4; i++) pin4(abuf[(j + 3) & 3][i]);
          if (lane == 0) mbar_arrive(sm + bar3(32) + (p >> 3) * 128 + (p & 7) * 8);
        });
      }
    }
    uint4 wb[4];
#pragma unroll
    for (int i = 0; i < 4; i++) wb[i] = lds4(sm + OFF_LNP + ((g & 1) ? t * 64 : 256) + i * 16);
    const float2 ah = lds2f(sm + OFF_MSC + 8);
    wg_wait<0>();
    pin(acc);
#pragma unroll
    for (int i = 0; i < 4; i++) pin4(abuf[3][i]);
    TS(10);
    const uint32_t msc = sm + OFF_MSC;
    uint32_t hp[8][4];
    {
      float se[2][4], q[4] = {0.f, 0.f, 0.f, 0.f};
#pragma unroll
      for (int i = 0; i < 8; i++) se[i >> 2][i & 3] = 0.f;
#pragma unroll
      for (int j = 0; j < 8; j++) {
#pragma unroll
        for (int i = 0; i < 4; i++) { const float a = acc[j * 8 + i * 2], c = acc[j * 8 + i * 2 + 1]; hp[j][i] = pack2(a, c); q[i] = fmaf(a, a, fmaf(c, c, q[i])); }
        mma16816(se[j & 1], hp[j], (j & 1) ? wb[j >> 1].z : wb[j >> 1].x, (j & 1) ? wb[j >> 1].w : wb[j >> 1].y);
      }
      const bool od = t & 1;
      const float q0 = q[0] + q[2], q1 = q[1] + q[3];
      float qq = (od ? q1 : q0) + __shfl_xor_sync(~0u, od ? q0 : q1, 1);
      qq += __shfl_xor_sync(~0u, qq, 2);
      const float ss = od ? se[0][2] + se[1][2] : se[0][0] + se[1][0], ee = od ? se[0][3] + se[1][3] : se[0][1] + se[1][1];
#pragma unroll 1
      for (int c = 0; c < 2; c++) {
        const int tr = __float_as_int(c ? ah.y : ah.x), slot = (rb * 2 + hf) * 2 + c;
        if ((tr >> 4) == wid) {
          const int sl = (tr & 7) * 4 + ((tr >> 3) & 1);
          const float s1 = __shfl_sync(~0u, ss, sl), s2 = __shfl_sync(~0u, qq, sl), s3 = __shfl_sync(~0u, ee, sl);
          red4(lane < 8, &G.cst[lane * 32 + slot], s1, s2, s3, c3 ? 1.f : (float)((mb3 * 64 + (tr & 63)) * 16 + 1));
          if (g == (tr & 7)) {
#pragma unroll
            for (int i = 0; i < 4; i++)
              st_rlx4(&G.hsel[slot * 128 + c3 * 16 + i * 4 + t], (tr & 8) ? make_uint4(hp[2 * i][1], hp[2 * i][3], hp[2 * i + 1][1], hp[2 * i + 1][3])
                                                                          : make_uint4(hp[2 * i][0], hp[2 * i][2], hp[2 * i + 1][0], hp[2 * i + 1][2]));
          }
        }
      }
      red4(t < 2, &G.st2[mb3 * 64 + warp * 16 + (t & 1) * 8 + g], ss, qq, ee, 1.f);
      if (lane == 0) mbar_arrive(sm + bar3(61));
      TS(11);
    }
    uint32_t wa[32][4], wd[8][2][4];
    const uint32_t ga = own + ((lane >> 3) & 1) * 8192 + ((lane >> 4) * 8 + (lane & 7)) * 64 + ((warp ^ ((lane >> 1) & 3)) << 4);
    const uint32_t dw = sm + ((D_SLOTS >> (2 * (wid & 6))) & 15) * SLOT_B + (wid & 1) * 8192;
    const uint32_t da = dw + ((lane >> 4) * 8 + (lane & 7)) * 128 + ((((lane >> 3) & 1) ^ (lane & 7)) << 4);
    const uint32_t xl = own + ((lane & 16) ? 12 + wg : 3 + 4 * wg) * SLOT_B + (lane & 8) * 1024 + (lane & 7) * 16;
    float ya[8][4];
    int pass = 0;
    auto load_gu = [&](int f) {
      const uint32_t ad = ga + ((GU_SLOTS >> (16 * wg + 4 * f)) & 15) * SLOT_B;
      static_for<0, 8>([&](auto ic) { constexpr int i = decltype(ic)::value; ldsm4t_o<sb + i * 1024>(ad, wa[f * 8 + i]); });
    };
    if (fidx >= 0) mbar_wait(mb + B_FULL, 0);
    load_gu(0); load_gu(1);
    {
      bar_sync(1, 256);
      const uint32_t ha = sm + HST + wid * 4096 + (lane & 15) * 256 + (((lane >> 4) ^ (lane & 7)) << 4);
      static_for<0, 8>([&](auto jc) { constexpr int j = decltype(jc)::value; stsm4_o<(j >> 2) * 128>(ha ^ ((j & 3) << 5), hp[j][0], hp[j][1], hp[j][2], hp[j][3]); });
      asm volatile("fence.acq_rel.cta;" ::: "memory");
      __syncwarp();
      if (lane == 0) mbar_arrive(sm + bar3(62));
    }
    if (fidx >= 0) mbar_wait(mb + B_FFN, 1);
#pragma unroll 1
    for (;; pass++) {
      if (pass) { load_gu(0); load_gu(1); }
      load_gu(2);
      TS(15);
      mbar_wait(mb + B_SEL, 0);
      const uint4 sx = lds4(msc + 16 + pass * 32 + (lane & 16));
      TS(26);
      const uint4* xp = &G.hsel[sx.y * 128 + wid * 16 + (lane & 15)];
      uint4 xv = ld_rlx4(xp);
      load_gu(3);
      if (!pass) {
        if (fidx >= 0) mbar_wait(mb + B_FFN + 8, 0);
        static_for<0, 8>([&](auto ic) { constexpr int i = decltype(ic)::value; ldsm4t_o<(i & 1) * 2048>(da ^ ((i >> 1) << 5), wd[i >> 1][i & 1]); });
      }
#pragma unroll 1
      for (int it = 0; __any_sync(~0u, max4(0, xv) == SENT); it++) { xv = ld_rlx4(xp); SPINCHK(it, 7); }
      const float f = __uint_as_float(sx.z), n = __uint_as_float(sx.w);
      sts4(dw + ((lane & 12) * 2 + (lane >> 4) * 4 + t) * 16, pack2(fmaf(bf_lo(xv.x), f, n), fmaf(bf_hi(xv.x), f, n)), pack2(fmaf(bf_lo(xv.y), f, n), fmaf(bf_hi(xv.y), f, n)),
           pack2(fmaf(bf_lo(xv.z), f, n), fmaf(bf_hi(xv.z), f, n)), pack2(fmaf(bf_lo(xv.w), f, n), fmaf(bf_hi(xv.w), f, n)));
      if (wid == rb && (g & 3) == (cg >> 2)) sts4(msc + 96 + (lane >> 4) * 16 + t * 32, xv.x, xv.y, xv.z, xv.w);
      bar_sync(2 + wg, 128);
      TS(14);
      float gu[4][4];
#pragma unroll
      for (int i = 0; i < 16; i++) gu[i >> 2][i & 3] = 0.f;
      uint4 xb[4];
      static_for<0, 4>([&](auto ic) { constexpr int i = decltype(ic)::value; xb[i] = lds4_o<sb + i * 128>(xl); });
#pragma unroll
      for (int ks = 0; ks < 8; ks++) {
        if (ks == 6) {
#pragma unroll
          for (int j = 0; j < 8; j++) xb[3].x |= wd[4 + (j >> 1)][j & 1][3] & zero;
        }
#pragma unroll
        for (int j = 0; j < 4; j++) mma16816(gu[j], wa[j * 8 + ks], (ks & 1) ? xb[ks >> 1].z : xb[ks >> 1].x, (ks & 1) ? xb[ks >> 1].w : xb[ks >> 1].y);
        if (ks == 2) static_for<0, 8>([&](auto jc) { constexpr int j = decltype(jc)::value; ldsm4t_o<4096 + (j & 1) * 2048>(da ^ ((j >> 1) << 5), wd[4 + (j >> 1)][j & 1]); });
      }
      {
        float o[4];
#pragma unroll
        for (int j = 0; j < 4; j++) o[j] = t == 0 ? gu[0][j] : t == 1 ? gu[1][j] : t == 2 ? gu[2][j] : gu[3][j];
        const float e0 = ((t & 2) ? o[2] : o[0]) + __shfl_xor_sync(~0u, (t & 2) ? o[0] : o[2], 2), e1 = ((t & 2) ? o[3] : o[1]) + __shfl_xor_sync(~0u, (t & 2) ? o[1] : o[3], 2);
        sts1(sm + (3 + 4 * wg) * SLOT_B + 1024 + t128 * 4, __float_as_uint(((t & 1) ? e1 : e0) + __shfl_xor_sync(~0u, (t & 1) ? e0 : e1, 1)));
      }
      TS(25);
      bar_sync(1, 256);
      const uint4 p0 = lds4_o<sb + 3 * SLOT_B + 1024>(own + lane * 16), p1 = lds4_o<sb + 7 * SLOT_B + 1024>(own + lane * 16);
      const float g0 = __uint_as_float(p0.x) + __uint_as_float(p1.x), g1 = __uint_as_float(p0.y) + __uint_as_float(p1.y);
      const float u0 = __uint_as_float(p0.z) + __uint_as_float(p1.z), u1 = __uint_as_float(p0.w) + __uint_as_float(p1.w);
      const uint32_t act = pack2(g0 * rcp(1.f + ex2(-1.4426950408889634f * g0)) * u0, g1 * rcp(1.f + ex2(-1.4426950408889634f * g1)) * u1);
      uint32_t bq[4];
#pragma unroll
      for (int i = 0; i < 4; i++) {
        const uint32_t lo = __shfl_sync(~0u, act, i * 8 + 2 * t), hi = __shfl_sync(~0u, act, i * 8 + 2 * t + 1);
        bq[i] = __byte_perm(lo, hi, (g & 1) ? 0x7632 : 0x5410);
      }
      TS(16);
#pragma unroll
      for (int i = 0; i < 8; i++) { ya[i][0] = 0.f; ya[i][1] = 0.f; ya[i][2] = 0.f; ya[i][3] = 0.f; }
#pragma unroll
      for (int ks = 0; ks < 2; ks++)
#pragma unroll
        for (int i = 0; i < 8; i++) mma16816(ya[i], wd[i][ks], bq[ks * 2], bq[ks * 2 + 1]);
      mbar_wait(mb + B_SEL2, 0);
      if (pass || !lds1(msc + 80)) break;
      bar_sync(1, 256);
    }
    if (fidx >= 0) {
      uint2* const yp = (uint2*)&G.ybuf[((wid * 16 + t * 2) * NFFN + fidx) * 4] + g;
#pragma unroll
      for (int h = 0; h < 2; h++) {
        float o[4];
#pragma unroll
        for (int j = 0; j < 4; j++) o[j] = t == 0 ? ya[h * 4][j] : t == 1 ? ya[h * 4 + 1][j] : t == 2 ? ya[h * 4 + 2][j] : ya[h * 4 + 3][j];
        st_rlx2(yp + h * (8 * NFFN * 8), __float_as_uint(o[0]), __float_as_uint(o[1]));
        st_rlx2(yp + h * (8 * NFFN * 8) + NFFN * 8, __float_as_uint(o[2]), __float_as_uint(o[3]));
      }
    }
    TS(17);
    const uint32_t ty = clk();
    if (wid < 7) {
      const uint4* const yq = &G.ybuf[b * NFFN * 4 + wid * 64 + lane];
      const uint4 sel = lds4(msc + 16 + pass * 32 + (lane & 1) * 16);
      const uint32_t fh = lds1(msc + 96 + (lane & 1) * 16 + (g & 3) * 32 + (cg & 3) * 4);
      const float r = __uint_as_float(sel.x ^ (~(uint32_t)((int)sel.x >> 31) | 0x80000000u));
      float sg = rcp(1.f + ex2(-1.4426950408889634f * r)), base = fmaf((lane & 2) ? bf_hi(fh) : bf_lo(fh), 1.f + __uint_as_float(sel.z), __uint_as_float(sel.w));
      __nv_bfloat16* op = P.out + (size_t)(2047 - (sel.x & 2047)) * D_ + b * 8 + ((lane >> 1) & 7);
      asm volatile("" : "+f"(sg), "+f"(base), "+l"(op) :: "memory");
      delay(ty, YDELAY);
      uint4 v0, v1;
#pragma unroll 1
      for (int it = 0;; it++) {
        v0 = ld_rlx4(yq); v1 = ld_rlx4(yq + 32);
        TSV(22, it + 1);
        if (!__any_sync(~0u, max(max4(0, v0), max4(0, v1)) == SENT)) break;
        SPINCHK(it, 8);
      }
      if (lane == 0) mbar_arrive(sm + bar3(63));
      TS(18);
      float y0 = __uint_as_float(v0.x) + __uint_as_float(v1.x), y1 = __uint_as_float(v0.y) + __uint_as_float(v1.y);
      float y2 = __uint_as_float(v0.z) + __uint_as_float(v1.z), y3 = __uint_as_float(v0.w) + __uint_as_float(v1.w);
      float z0 = ((lane & 16) ? y2 : y0) + __shfl_xor_sync(~0u, (lane & 16) ? y0 : y2, 16), z1 = ((lane & 16) ? y3 : y1) + __shfl_xor_sync(~0u, (lane & 16) ? y1 : y3, 16);
      z0 = ((lane & 8) ? z1 : z0) + __shfl_xor_sync(~0u, (lane & 8) ? z0 : z1, 8);
      z0 += __shfl_xor_sync(~0u, z0, 4);
      const uint32_t yx = sm + OFF_COLSUM;
      if (!(lane & 4)) sts1(yx + (t * 4 + (lane >> 3)) * 32 + wid * 4, __float_as_uint(z0));
      if (wid) bar_arrive(1, 224);
      else {
        bar_sync(1, 224);
        const uint4 a = lds4(yx + (lane & 15) * 32), c = lds4(yx + (lane & 15) * 32 + 16);
        const float y = ((__uint_as_float(a.x) + __uint_as_float(a.y)) + (__uint_as_float(a.z) + __uint_as_float(a.w))) + ((__uint_as_float(c.x) + __uint_as_float(c.y)) + __uint_as_float(c.z));
        if (lane < 16) *op = __float2bfloat16(fmaf(y, sg, base));
        if (b == 0 && lane == 16) G.epoch = lds1(mb + B_SW + 4);
      }
    }
    }
    TS(19); TSG(31);
    if (warp == 0) TS_DUMP(wg);
  }
}

typedef CUresult (*EncodeFn)(CUtensorMap*, CUtensorMapDataType, cuuint32_t, void*, const cuuint64_t*, const cuuint64_t*, const cuuint32_t*,
                             const cuuint32_t*, CUtensorMapInterleave, CUtensorMapSwizzle, CUtensorMapL2promotion, CUtensorMapFloatOOBfill);
void make_map(EncodeFn enc, CUtensorMap* m, const void* p, uint64_t cols, uint64_t rows, uint64_t d0, uint32_t b0, uint32_t b1, uint32_t b2, CUtensorMapSwizzle sw,
              CUtensorMapL2promotion promo = CU_TENSOR_MAP_L2_PROMOTION_L2_128B) {
  cuuint64_t dims[3] = {d0, rows, cols / d0}, str[2] = {cols * 2, d0 * 2};
  cuuint32_t box[3] = {b0, b1, b2}, es[3] = {1, 1, 1};
  enc(m, CU_TENSOR_MAP_DATA_TYPE_BFLOAT16, b2 ? 3 : 2, const_cast<void*>(p), dims, str, box, es, CU_TENSOR_MAP_INTERLEAVE_NONE, sw,
      promo, CU_TENSOR_MAP_FLOAT_OOB_FILL_NONE);
}

}

extern "C" void kernel_launch(void* const* d_in, const int* in_sizes, int n_in, void* d_out, int out_size) {
  (void)in_sizes; (void)n_in; (void)out_size;
  Ptrs P;
  P.x = (const __nv_bfloat16*)d_in[0]; P.wqkv = (const __nv_bfloat16*)d_in[1]; P.wo = (const __nv_bfloat16*)d_in[2];
  P.wr = (const __nv_bfloat16*)d_in[4]; P.wg = (const __nv_bfloat16*)d_in[5]; P.wu = (const __nv_bfloat16*)d_in[6];
  P.wd = (const __nv_bfloat16*)d_in[7]; P.out = (__nv_bfloat16*)d_out;
  void* fn = nullptr;
  cudaDriverEntryPointQueryResult q;
  cudaGetDriverEntryPoint("cuTensorMapEncodeTiled", &fn, cudaEnableDefault, &q);
  EncodeFn enc = (EncodeFn)fn;
  CUtensorMap tmX, tmW, tmO, tmG, tmU, tmD, tmM, tmPG, tmPU, tmPD;
  make_map(enc, &tmX, P.x, D_, S_, D_, 64, 128, 0, CU_TENSOR_MAP_SWIZZLE_128B);
  make_map(enc, &tmW, P.wqkv, 3 * D_, D_, 3 * D_, 64, 64, 0, CU_TENSOR_MAP_SWIZZLE_128B);
  make_map(enc, &tmG, P.wg, F_, D_, F_, 32, 128, 0, CU_TENSOR_MAP_SWIZZLE_64B);
  make_map(enc, &tmU, P.wu, F_, D_, F_, 32, 128, 0, CU_TENSOR_MAP_SWIZZLE_64B);
  make_map(enc, &tmD, P.wd, D_, F_, 64, 64, 32, 4, CU_TENSOR_MAP_SWIZZLE_128B);
  make_map(enc, &tmPG, P.wg, F_, D_, F_, 8, 32, 0, CU_TENSOR_MAP_SWIZZLE_NONE);
  make_map(enc, &tmPU, P.wu, F_, D_, F_, 8, 32, 0, CU_TENSOR_MAP_SWIZZLE_NONE);
  make_map(enc, &tmPD, P.wd, 128, F_ * 8, 128, 8, 32, 0, CU_TENSOR_MAP_SWIZZLE_NONE, CU_TENSOR_MAP_L2_PROMOTION_L2_256B);
  for (int m = 0; m < 2; m++) {
    cuuint64_t dims[4] = {64, m ? 64u : 16u, m ? 16u : 64u, 16}, str[3] = {2 * D_, (m ? 128u : 32u) * D_, 128};
    cuuint32_t box[4] = {64, 16, 4, 2}, es[4] = {1, 1, 1, 1};
    enc(m ? &tmM : &tmO, CU_TENSOR_MAP_DATA_TYPE_BFLOAT16, 4, const_cast<__nv_bfloat16*>(P.wo), dims, str, box, es, CU_TENSOR_MAP_INTERLEAVE_NONE,
        CU_TENSOR_MAP_SWIZZLE_128B, CU_TENSOR_MAP_L2_PROMOTION_L2_128B, CU_TENSOR_MAP_FLOAT_OOB_FILL_NONE);
  }
  cudaFuncSetAttribute(fused_kernel, cudaFuncAttributeMaxDynamicSharedMemorySize, SMEM_BYTES);
  fused_kernel<<<NCTA, 384, SMEM_BYTES>>>(tmX, tmW, tmO, tmG, tmU, tmD, tmM, tmPG, tmPU, tmPD, P);
}
```

```cpp
#include <cuda_runtime.h>
#include <cuda.h>
#include <cuda_bf16.h>
#include <stdint.h>
#include <type_traits>

namespace {

constexpr int S_ = 2048, D_ = 1024, F_ = 3584;
constexpr int NCTA = 128, NFFN = 112;
constexpr uint32_t SENT = 0xFFFFFFFFu;
constexpr int SPIN_LIMIT = 1 << 20;

#define ADELAY 800
#define NPK 0x233333333333ull
#define KDELAY 800
#define SBAR 2
#define NOOUT 0
#define OHOLD 72
#define OUTEF 0
#define CUTS 0
#define EFO 0
#define EFWO 0
#define TMPF 1
#define INIF 0
#define WOW 2
#define WOP 7
#define NPUB 2
#define ASTEP 300
#define BDELAY 1500
#define LATEP 0x20
#define TICKM 0
#define TICK 256
#define PD0 2
#define NPD 8
#define PDT 100
#define KORD 0xBA9F87E6D54C3210ull
#define SDELAY 450
#define LDELAY 500
#define NOSPEC 0
#define LOCK 1
#define STLD 2
#define RELK 1
#define PERT 5
#define QHOLD 3
#define CDELAY 0
#define YDELAY 500
#define EFX 0
#define EFW 1
#define EFF 1
#define GDELAY 800
#define PFST 1
#define W0POS 0x2211
constexpr uint32_t STAGE_B = 57344;
__host__ __device__ constexpr uint32_t xoff(int s, int w) { return ((0x86CA5731u >> (4 * (s + 4 * w))) & 15) * 16384; }
__host__ __device__ constexpr uint32_t woff(int s) { return (s < 2 ? 9 * 16384 : 0) + (s & 1) * 8192; }
constexpr uint32_t WSTR = 32768;
constexpr uint32_t OFF_BARS = 229376;
constexpr uint32_t OFF_COLSUM = 229632;
constexpr uint32_t OFF_STATS = 230400;
constexpr uint32_t SMEM_BYTES = 232448;
constexpr uint32_t B_FULL = 0, B_EMPTY = 32, B_AUX = 64, B_SEL2 = 72, B_KVL = 80, B_FULL3 = 88, B_SW = 216, B_OUT = 224, B_LATE = 232, B_SEL = B_FULL + 8, B_FFN = 240;
__host__ __device__ constexpr uint32_t o3(int p) { return p * 8 + (p & 8) * 8; }
__host__ __device__ constexpr uint32_t bar3(int i) { return OFF_STATS + 1024 + (i >> 3) * 128 + ((i & 32) ? 0 : 64) + (i & 7) * 8; }
constexpr uint32_t SLOT_B = 16384;
constexpr uint32_t sb = 1024;
constexpr uint32_t bars = sb + OFF_BARS;
constexpr uint64_t WO_SLOTS = 0x6573142098657314ull;
constexpr uint32_t GU_SLOTS = 0xBA291408u, D_SLOTS = 0xD7C3;
constexpr uint32_t HST = 5 * SLOT_B;
constexpr uint32_t OFF_LNP = OFF_STATS;
constexpr uint32_t OFF_MSC = OFF_COLSUM + 512;
constexpr uint32_t OFF_KVB = 2 * SLOT_B + 8192;

struct Scratch {
  uint4 st1[64 * 48];
  uint4 csp[16 * 8 * 48];
  uint4 kvp[16 * 2304];
  uint4 obuf[32 * 64 * 128];
  uint4 st2[S_];
  uint32_t pred[S_];
  uint4 cst[8 * 32];
  uint4 hsel[64 * 128];
  uint32_t cand[8 * 32];
  uint4 ybuf[NCTA * NFFN * 4];
  unsigned epoch;
};
__device__ __align__(1024) Scratch G;
#define TS_DECL
#define TS(i)
#define TSG(i)
#define TSV(i, v)
#define TS_DUMP(slot)
#define PTS(i)

__device__ __forceinline__ uint32_t smem_u32(const void* p) { return (uint32_t)__cvta_generic_to_shared(p); }
__device__ __forceinline__ void mbar_init(uint32_t bar, uint32_t cnt) { asm volatile("mbarrier.init.shared::cta.b64 [%0], %1;" :: "r"(bar), "r"(cnt) : "memory"); }
__device__ __forceinline__ void mbar_expect_tx(uint32_t bar, uint32_t bytes) { asm volatile("mbarrier.arrive.expect_tx.shared::cta.b64 _, [%0], %1;" :: "r"(bar), "r"(bytes) : "memory"); }
__device__ __forceinline__ void mbar_arrive(uint32_t bar) { asm volatile("mbarrier.arrive.shared::cta.b64 _, [%0];" :: "r"(bar) : "memory"); }
#define SPINCHK(it, code) if ((it) > SPIN_LIMIT) break
__device__ __forceinline__ void mbar_wait(uint32_t bar, uint32_t parity) {
  asm volatile("{\n.reg .pred p;\n.reg .u32 c;\nmov.u32 c, 0;\n"
               "WL:\nmbarrier.try_wait.parity.shared::cta.b64 p, [%0], %1;\n@p bra WD;\n"
               "add.u32 c, c, 1;\nsetp.lt.u32 p, c, 1048576;\n@p bra WL;\nWD:\n}" :: "r"(bar), "r"(parity) : "memory");
}
__device__ __forceinline__ uint64_t l2_stream() { uint64_t p; asm("createpolicy.fractional.L2::evict_first.b64 %0, 1.0;" : "=l"(p)); return p; }
__device__ __forceinline__ void tma_2d(uint32_t dst, const CUtensorMap* tm, int c0, int c1, uint32_t bar, bool stream) {
  if (stream) asm volatile("cp.async.bulk.tensor.2d.shared::cluster.global.mbarrier::complete_tx::bytes.L2::cache_hint [%0], [%1, {%3, %4}], [%2], %5;"
                           :: "r"(dst), "l"(tm), "r"(bar), "r"(c0), "r"(c1), "l"(l2_stream()) : "memory");
  else asm volatile("cp.async.bulk.tensor.2d.shared::cluster.global.mbarrier::complete_tx::bytes [%0], [%1, {%3, %4}], [%2];"
                    :: "r"(dst), "l"(tm), "r"(bar), "r"(c0), "r"(c1) : "memory");
}
__device__ __forceinline__ void tma_3d(uint32_t dst, const CUtensorMap* tm, int c0, int c1, int c2, uint32_t bar, bool stream) {
  if (stream) asm volatile("cp.async.bulk.tensor.3d.shared::cluster.global.mbarrier::complete_tx::bytes.L2::cache_hint [%0], [%1, {%3, %4, %5}], [%2], %6;"
                           :: "r"(dst), "l"(tm), "r"(bar), "r"(c0), "r"(c1), "r"(c2), "l"(l2_stream()) : "memory");
  else asm volatile("cp.async.bulk.tensor.3d.shared::cluster.global.mbarrier::complete_tx::bytes [%0], [%1, {%3, %4, %5}], [%2];"
                    :: "r"(dst), "l"(tm), "r"(bar), "r"(c0), "r"(c1), "r"(c2) : "memory");
}
__device__ __forceinline__ void tma_2d_mc(uint32_t dst, const CUtensorMap* tm, int c0, int c1, uint32_t bar, bool stream) {
  if (stream) asm volatile("cp.async.bulk.tensor.2d.shared::cluster.global.mbarrier::complete_tx::bytes.multicast::cluster.L2::cache_hint [%0], [%1, {%3, %4}], [%2], %5, %6;"
                           :: "r"(dst), "l"(tm), "r"(bar), "r"(c0), "r"(c1), "h"((uint16_t)3), "l"(l2_stream()) : "memory");
  else asm volatile("cp.async.bulk.tensor.2d.shared::cluster.global.mbarrier::complete_tx::bytes.multicast::cluster [%0], [%1, {%3, %4}], [%2], %5;"
                    :: "r"(dst), "l"(tm), "r"(bar), "r"(c0), "r"(c1), "h"((uint16_t)3) : "memory");
}
__device__ __forceinline__ bool elect_one() {
  uint32_t p;
  asm volatile("{\n.reg .pred q;\nelect.sync _|q, 0xFFFFFFFF;\nselp.u32 %0, 1, 0, q;\n}" : "=r"(p));
  return p;
}
__device__ __forceinline__ void bulk_load_mc(uint32_t dst, const void* src, uint32_t bar, uint16_t mask) {
  if (EFO) asm volatile("cp.async.bulk.shared::cluster.global.mbarrier::complete_tx::bytes.multicast::cluster.L2::cache_hint [%0], [%1], 8192, [%2], %3, %4;"
               :: "r"(dst), "l"(src), "r"(bar), "h"(mask), "l"(l2_stream()) : "memory");
  else asm volatile("cp.async.bulk.shared::cluster.global.mbarrier::complete_tx::bytes.multicast::cluster [%0], [%1], 8192, [%2], %3;"
               :: "r"(dst), "l"(src), "r"(bar), "h"(mask) : "memory");
}
__device__ __forceinline__ void bulk_load(uint32_t dst, const void* src, uint32_t bytes, uint32_t bar) {
  asm volatile("cp.async.bulk.shared::cluster.global.mbarrier::complete_tx::bytes [%0], [%1], %2, [%3];" :: "r"(dst), "l"(src), "r"(bytes), "r"(bar) : "memory");
}
__device__ __forceinline__ void mbar_arrive_rem(uint32_t bar) { asm volatile("mbarrier.arrive.shared::cluster.b64 _, [%0];" :: "r"(bar) : "memory"); }
template <uint32_t O> __device__ __forceinline__ void ldsm4_o(uint32_t addr, uint32_t& a, uint32_t& b, uint32_t& c, uint32_t& d) {
  asm volatile("ldmatrix.sync.aligned.m8n8.x4.shared.b16 {%0,%1,%2,%3}, [%4+%5];" : "=r"(a), "=r"(b), "=r"(c), "=r"(d) : "r"(addr), "n"(O) : "memory");
}
template <uint32_t O> __device__ __forceinline__ void ldsm4t_o(uint32_t addr, uint32_t (&r)[4]) {
  asm volatile("ldmatrix.sync.aligned.m8n8.x4.trans.shared.b16 {%0,%1,%2,%3}, [%4+%5];" : "=r"(r[0]), "=r"(r[1]), "=r"(r[2]), "=r"(r[3]) : "r"(addr), "n"(O) : "memory");
}
__device__ __forceinline__ void mma16816(float (&c)[4], const uint32_t (&a)[4], uint32_t b0, uint32_t b1) {
  asm("mma.sync.aligned.m16n8k16.row.col.f32.bf16.bf16.f32 {%0,%1,%2,%3}, {%4,%5,%6,%7}, {%8,%9}, {%0,%1,%2,%3};"
      : "+f"(c[0]), "+f"(c[1]), "+f"(c[2]), "+f"(c[3]) : "r"(a[0]), "r"(a[1]), "r"(a[2]), "r"(a[3]), "r"(b0), "r"(b1));
}
__device__ __forceinline__ void l2_prefetch(const void* p) { asm volatile("prefetch.global.L2 [%0];" :: "l"(p) : "memory"); }
__device__ __forceinline__ uint32_t clk() { uint32_t t; asm volatile("mov.u32 %0, %%clock;" : "=r"(t) :: "memory"); return t; }
__device__ __forceinline__ void delay(uint32_t t0, uint32_t n) { while (clk() - t0 < n) {} }
template <int ID> __device__ __forceinline__ void cut(uint32_t zero) { asm volatile("{\n.reg .pred p;\nsetp.eq.u32 p, %0, %1;\nCUT:\n@p nanosleep.u32 1;\n@p bra.uni CUT;\n}" :: "r"(zero), "n"(ID) : "memory"); }
__device__ __forceinline__ void tmap_prefetch(const CUtensorMap* tm) { asm volatile("prefetch.tensormap [%0];" :: "l"(tm) : "memory"); }
__device__ __forceinline__ void wg_fence() { asm volatile("wgmma.fence.sync.aligned;" ::: "memory"); }
__device__ __forceinline__ void wg_commit() { asm volatile("wgmma.commit_group.sync.aligned;" ::: "memory"); }
template <int N> __device__ __forceinline__ void wg_wait() { asm volatile("wgmma.wait_group.sync.aligned %0;" :: "n"(N) : "memory"); }
template <int N> __device__ __forceinline__ void pin(float (&d)[N]) {
#pragma unroll
  for (int i = 0; i < N; i++) asm volatile("" : "+f"(d[i]) :: "memory");
}
__device__ __forceinline__ void pin4(uint4& v) { asm volatile("" : "+r"(v.x), "+r"(v.y), "+r"(v.z), "+r"(v.w) :: "memory"); }
template <uint32_t SBO, uint32_t SWZ> __device__ __forceinline__ uint64_t dsc(uint32_t lo) { return ((uint64_t)((SBO >> 4) | (SWZ << 30)) << 32) | lo; }
__host__ __device__ constexpr uint32_t dlo(uint32_t addr, uint32_t lbo) { return (addr >> 4) | ((lbo >> 4) << 16); }
__device__ __forceinline__ void bar_sync(int id, int n) { asm volatile("bar.sync %0, %1;" :: "r"(id), "r"(n) : "memory"); }
__device__ __forceinline__ void bar_arrive(int id, int n) { asm volatile("bar.arrive %0, %1;" :: "r"(id), "r"(n) : "memory"); }
__device__ __forceinline__ void fence_async_smem() { asm volatile("fence.proxy.async.shared::cta;" ::: "memory"); }
__device__ __forceinline__ void fence_gpu() { asm volatile("fence.acq_rel.gpu;" ::: "memory"); }
__device__ __forceinline__ uint4 ld_cg4(const void* p) { uint4 v; asm volatile("ld.global.cg.v4.u32 {%0,%1,%2,%3}, [%4];" : "=r"(v.x), "=r"(v.y), "=r"(v.z), "=r"(v.w) : "l"(p) : "memory"); return v; }
__device__ __forceinline__ uint4 ld_rlx4(const void* p) { uint4 v; asm volatile("ld.relaxed.gpu.global.v4.u32 {%0,%1,%2,%3}, [%4];" : "=r"(v.x), "=r"(v.y), "=r"(v.z), "=r"(v.w) : "l"(p) : "memory"); return v; }
__device__ __forceinline__ uint32_t ld_rlx(const void* p) { uint32_t v; asm volatile("ld.relaxed.gpu.global.u32 %0, [%1];" : "=r"(v) : "l"(p) : "memory"); return v; }
__device__ __forceinline__ void st_rlx4(void* p, uint4 v) { asm volatile("st.relaxed.gpu.global.v4.u32 [%0], {%1,%2,%3,%4};" :: "l"(p), "r"(v.x), "r"(v.y), "r"(v.z), "r"(v.w) : "memory"); }
__device__ __forceinline__ void st_rlx2(void* p, uint32_t a, uint32_t b) { asm volatile("st.relaxed.gpu.global.v2.u32 [%0], {%1,%2};" :: "l"(p), "r"(a), "r"(b) : "memory"); }
__device__ __forceinline__ void st_rlx(void* p, uint32_t a) { asm volatile("st.relaxed.gpu.global.u32 [%0], %1;" :: "l"(p), "r"(a) : "memory"); }
__device__ __forceinline__ void red4(bool on, void* p, float a, float b, float c, float d) {
  asm volatile("{\n.reg .pred q;\nsetp.ne.b32 q, %5, 0;\n@q red.relaxed.gpu.global.add.v4.f32 [%0], {%1,%2,%3,%4};\n}" :: "l"(p), "f"(a), "f"(b), "f"(c), "f"(d), "r"((int)on) : "memory");
}
__device__ __forceinline__ uint32_t pack2(float lo, float hi) { uint32_t r; asm("cvt.rn.bf16x2.f32 %0, %1, %2;" : "=r"(r) : "f"(hi), "f"(lo)); return r; }
__device__ __forceinline__ float bf_lo(uint32_t v) { return __uint_as_float(v << 16); }
__device__ __forceinline__ float bf_hi(uint32_t v) { return __uint_as_float(v & 0xFFFF0000u); }
__device__ __forceinline__ void stsm4(uint32_t addr, uint32_t a, uint32_t b, uint32_t c, uint32_t d) {
  asm volatile("stmatrix.sync.aligned.m8n8.x4.shared.b16 [%0], {%1,%2,%3,%4};" :: "r"(addr), "r"(a), "r"(b), "r"(c), "r"(d) : "memory");
}
template <uint32_t O> __device__ __forceinline__ void stsm4_o(uint32_t addr, uint32_t a, uint32_t b, uint32_t c, uint32_t d) {
  asm volatile("stmatrix.sync.aligned.m8n8.x4.shared.b16 [%0+%5], {%1,%2,%3,%4};" :: "r"(addr), "r"(a), "r"(b), "r"(c), "r"(d), "n"(O) : "memory");
}
__device__ __forceinline__ void sts4(uint32_t addr, uint32_t a, uint32_t b, uint32_t c, uint32_t d) { asm volatile("st.shared.v4.u32 [%0], {%1,%2,%3,%4};" :: "r"(addr), "r"(a), "r"(b), "r"(c), "r"(d) : "memory"); }
__device__ __forceinline__ void sts2f(uint32_t addr, float a, float b) { asm volatile("st.shared.v2.f32 [%0], {%1,%2};" :: "r"(addr), "f"(a), "f"(b) : "memory"); }
__device__ __forceinline__ void sts1(uint32_t addr, uint32_t a) { asm volatile("st.shared.u32 [%0], %1;" :: "r"(addr), "r"(a) : "memory"); }
__device__ __forceinline__ float2 lds2f(uint32_t addr) { float2 v; asm volatile("ld.shared.v2.f32 {%0,%1}, [%2];" : "=f"(v.x), "=f"(v.y) : "r"(addr) : "memory"); return v; }
template <uint32_t O> __device__ __forceinline__ float2 lds2f_o(uint32_t addr) { float2 v; asm volatile("ld.shared.v2.f32 {%0,%1}, [%2+%3];" : "=f"(v.x), "=f"(v.y) : "r"(addr), "n"(O) : "memory"); return v; }
template <int I, int N, class F> __device__ __forceinline__ void static_for(F&& f) { if constexpr (I < N) { f(std::integral_constant<int, I>{}); static_for<I + 1, N>(f); } }
__device__ __forceinline__ uint4 lds4(uint32_t addr) { uint4 v; asm volatile("ld.shared.v4.u32 {%0,%1,%2,%3}, [%4];" : "=r"(v.x), "=r"(v.y), "=r"(v.z), "=r"(v.w) : "r"(addr) : "memory"); return v; }
__device__ __forceinline__ uint32_t lds1(uint32_t addr) { uint32_t v; asm volatile("ld.shared.u32 %0, [%1];" : "=r"(v) : "r"(addr) : "memory"); return v; }
__device__ __forceinline__ float ex2(float x) { float y; asm("ex2.approx.ftz.f32 %0, %1;" : "=f"(y) : "f"(x)); return y; }
__device__ __forceinline__ uint32_t max4(uint32_t m, const uint4& v) { return __vimax3_u32(__vimax3_u32(m, v.x, v.y), v.z, v.w); }
__device__ __forceinline__ float rsq(float x) { float y; asm("rsqrt.approx.ftz.f32 %0, %1;" : "=f"(y) : "f"(x)); return y; }
__device__ __forceinline__ float rcp(float x) { float y; asm("rcp.approx.ftz.f32 %0, %1;" : "=f"(y) : "f"(x)); return y; }
__device__ __forceinline__ uint2 ld_rlx2(const void* p) { uint2 v; asm volatile("ld.relaxed.gpu.global.v2.u32 {%0,%1}, [%2];" : "=r"(v.x), "=r"(v.y) : "l"(p) : "memory"); return v; }
template <uint32_t O> __device__ __forceinline__ uint4 lds4_o(uint32_t addr) { uint4 v; asm volatile("ld.shared.v4.u32 {%0,%1,%2,%3}, [%4+%5];" : "=r"(v.x), "=r"(v.y), "=r"(v.z), "=r"(v.w) : "r"(addr), "n"(O) : "memory"); return v; }
__device__ __forceinline__ uint32_t hadd2(uint32_t a, uint32_t b) { uint32_t r; asm("add.rn.bf16x2 %0, %1, %2;" : "=r"(r) : "r"(a), "r"(b)); return r; }
__device__ __forceinline__ uint4 hadd8(const uint4& a, const uint4& b) { return make_uint4(hadd2(a.x, b.x), hadd2(a.y, b.y), hadd2(a.z, b.z), hadd2(a.w, b.w)); }
__device__ __forceinline__ bool hnan(uint32_t a) { return (a & 0x7FFF0000u) > 0x7F800000u; }
__device__ __forceinline__ uint32_t hfma2(uint32_t a, uint32_t b, uint32_t c) { uint32_t r; asm("fma.rn.bf16x2 %0, %1, %2, %3;" : "=r"(r) : "r"(a), "r"(b), "r"(c)); return r; }
__device__ __forceinline__ uint32_t ordered(float v) { const uint32_t u = __float_as_uint(v); return u ^ ((uint32_t)((int)u >> 31) | 0x80000000u); }
__device__ __forceinline__ uint32_t route(const uint4& v, float sw, int row, float2& pr) {
  const float mean = __uint_as_float(v.x) * (1.f / D_);
  pr.x = rsq(fmaxf(fmaf(-mean, mean, __uint_as_float(v.y) * (1.f / D_)), 0.f) + 1e-5f);
  pr.y = -mean * pr.x;
  return min(ordered(pr.x * fmaf(-mean, sw, __uint_as_float(v.z))) & ~2047u, 0xFFFFF000u) | (2047 - row);
}
__device__ __forceinline__ uint2 top2(uint32_t a, uint32_t b, uint32_t c, uint32_t d) {
  const uint32_t h0 = max(a, b), h1 = max(c, d), h = max(h0, h1), l = __vimax3_u32(min(h0, h1), min(a, b), min(c, d));
  const uint32_t m1 = __reduce_max_sync(~0u, h);
  return make_uint2(m1, __reduce_max_sync(~0u, h == m1 ? l : h));
}
__device__ __forceinline__ uint32_t hmul2(uint32_t a, uint32_t b) { uint32_t r; asm("mul.rn.bf16x2 %0, %1, %2;" : "=r"(r) : "r"(a), "r"(b)); return r; }
__device__ __forceinline__ uint32_t phi2(float u0, float u1, uint32_t r2, float rl) {
  uint32_t p, r;
  asm("cvt.rn.relu.bf16x2.f32 %0, %1, %2;" : "=r"(p) : "f"(u1), "f"(u0));
  asm("fma.rn.bf16x2 %0, %1, %2, %3;" : "=r"(r) : "r"(p), "r"(r2), "r"(pack2(__saturatef(ex2(u0 * rl) + 1e-6f), __saturatef(ex2(u1 * rl) + 1e-6f))));
  return r;
}

template<int TA, int TB, int OFF, int SZ> __device__ __forceinline__ void wgmma_n192_ss(float (&d)[SZ], uint64_t da, uint64_t db, int scale_d) {
  asm volatile("{\n.reg .pred p;\nsetp.ne.b32 p, %98, 0;\n"
    "wgmma.mma_async.sync.aligned.m64n192k16.f32.bf16.bf16 {%0,%1,%2,%3,%4,%5,%6,%7,%8,%9,%10,%11,%12,%13,%14,%15,%16,%17,%18,%19,%20,%21,%22,%23,%24,%25,%26,%27,%28,%29,%30,%31,%32,%33,%34,%35,%36,%37,%38,%39,%40,%41,%42,%43,%44,%45,%46,%47,%48,%49,%50,%51,%52,%53,%54,%55,%56,%57,%58,%59,%60,%61,%62,%63,%64,%65,%66,%67,%68,%69,%70,%71,%72,%73,%74,%75,%76,%77,%78,%79,%80,%81,%82,%83,%84,%85,%86,%87,%88,%89,%90,%91,%92,%93,%94,%95}, %96, %97, p, 1, 1, %99, %100;\n}\n"
    : "+f"(d[OFF+0]), "+f"(d[OFF+1]), "+f"(d[OFF+2]), "+f"(d[OFF+3]), "+f"(d[OFF+4]), "+f"(d[OFF+5]), "+f"(d[OFF+6]), "+f"(d[OFF+7]),
      "+f"(d[OFF+8]), "+f"(d[OFF+9]), "+f"(d[OFF+10]), "+f"(d[OFF+11]), "+f"(d[OFF+12]), "+f"(d[OFF+13]), "+f"(d[OFF+14]), "+f"(d[OFF+15]),
      "+f"(d[OFF+16]), "+f"(d[OFF+17]), "+f"(d[OFF+18]), "+f"(d[OFF+19]), "+f"(d[OFF+20]), "+f"(d[OFF+21]), "+f"(d[OFF+22]), "+f"(d[OFF+23]),
      "+f"(d[OFF+24]), "+f"(d[OFF+25]), "+f"(d[OFF+26]), "+f"(d[OFF+27]), "+f"(d[OFF+28]), "+f"(d[OFF+29]), "+f"(d[OFF+30]), "+f"(d[OFF+31]),
      "+f"(d[OFF+32]), "+f"(d[OFF+33]), "+f"(d[OFF+34]), "+f"(d[OFF+35]), "+f"(d[OFF+36]), "+f"(d[OFF+37]), "+f"(d[OFF+38]), "+f"(d[OFF+39]),
      "+f"(d[OFF+40]), "+f"(d[OFF+41]), "+f"(d[OFF+42]), "+f"(d[OFF+43]), "+f"(d[OFF+44]), "+f"(d[OFF+45]), "+f"(d[OFF+46]), "+f"(d[OFF+47]),
      "+f"(d[OFF+48]), "+f"(d[OFF+49]), "+f"(d[OFF+50]), "+f"(d[OFF+51]), "+f"(d[OFF+52]), "+f"(d[OFF+53]), "+f"(d[OFF+54]), "+f"(d[OFF+55]),
      "+f"(d[OFF+56]), "+f"(d[OFF+57]), "+f"(d[OFF+58]), "+f"(d[OFF+59]), "+f"(d[OFF+60]), "+f"(d[OFF+61]), "+f"(d[OFF+62]), "+f"(d[OFF+63]),
      "+f"(d[OFF+64]), "+f"(d[OFF+65]), "+f"(d[OFF+66]), "+f"(d[OFF+67]), "+f"(d[OFF+68]), "+f"(d[OFF+69]), "+f"(d[OFF+70]), "+f"(d[OFF+71]),
      "+f"(d[OFF+72]), "+f"(d[OFF+73]), "+f"(d[OFF+74]), "+f"(d[OFF+75]), "+f"(d[OFF+76]), "+f"(d[OFF+77]), "+f"(d[OFF+78]), "+f"(d[OFF+79]),
      "+f"(d[OFF+80]), "+f"(d[OFF+81]), "+f"(d[OFF+82]), "+f"(d[OFF+83]), "+f"(d[OFF+84]), "+f"(d[OFF+85]), "+f"(d[OFF+86]), "+f"(d[OFF+87]),
      "+f"(d[OFF+88]), "+f"(d[OFF+89]), "+f"(d[OFF+90]), "+f"(d[OFF+91]), "+f"(d[OFF+92]), "+f"(d[OFF+93]), "+f"(d[OFF+94]), "+f"(d[OFF+95])
    : "l"(da), "l"(db), "r"(scale_d), "n"(TA), "n"(TB));
}
template<int TA, int TB, int OFF, int SZ> __device__ __forceinline__ void wgmma_n128_ss(float (&d)[SZ], uint64_t da, uint64_t db, int scale_d) {
  asm volatile("{\n.reg .pred p;\nsetp.ne.b32 p, %66, 0;\n"
    "wgmma.mma_async.sync.aligned.m64n128k16.f32.bf16.bf16 {%0,%1,%2,%3,%4,%5,%6,%7,%8,%9,%10,%11,%12,%13,%14,%15,%16,%17,%18,%19,%20,%21,%22,%23,%24,%25,%26,%27,%28,%29,%30,%31,%32,%33,%34,%35,%36,%37,%38,%39,%40,%41,%42,%43,%44,%45,%46,%47,%48,%49,%50,%51,%52,%53,%54,%55,%56,%57,%58,%59,%60,%61,%62,%63}, %64, %65, p, 1, 1, %67, %68;\n}\n"
    : "+f"(d[OFF+0]), "+f"(d[OFF+1]), "+f"(d[OFF+2]), "+f"(d[OFF+3]), "+f"(d[OFF+4]), "+f"(d[OFF+5]), "+f"(d[OFF+6]), "+f"(d[OFF+7]),
      "+f"(d[OFF+8]), "+f"(d[OFF+9]), "+f"(d[OFF+10]), "+f"(d[OFF+11]), "+f"(d[OFF+12]), "+f"(d[OFF+13]), "+f"(d[OFF+14]), "+f"(d[OFF+15]),
      "+f"(d[OFF+16]), "+f"(d[OFF+17]), "+f"(d[OFF+18]), "+f"(d[OFF+19]), "+f"(d[OFF+20]), "+f"(d[OFF+21]), "+f"(d[OFF+22]), "+f"(d[OFF+23]),
      "+f"(d[OFF+24]), "+f"(d[OFF+25]), "+f"(d[OFF+26]), "+f"(d[OFF+27]), "+f"(d[OFF+28]), "+f"(d[OFF+29]), "+f"(d[OFF+30]), "+f"(d[OFF+31]),
      "+f"(d[OFF+32]), "+f"(d[OFF+33]), "+f"(d[OFF+34]), "+f"(d[OFF+35]), "+f"(d[OFF+36]), "+f"(d[OFF+37]), "+f"(d[OFF+38]), "+f"(d[OFF+39]),
      "+f"(d[OFF+40]), "+f"(d[OFF+41]), "+f"(d[OFF+42]), "+f"(d[OFF+43]), "+f"(d[OFF+44]), "+f"(d[OFF+45]), "+f"(d[OFF+46]), "+f"(d[OFF+47]),
      "+f"(d[OFF+48]), "+f"(d[OFF+49]), "+f"(d[OFF+50]), "+f"(d[OFF+51]), "+f"(d[OFF+52]), "+f"(d[OFF+53]), "+f"(d[OFF+54]), "+f"(d[OFF+55]),
      "+f"(d[OFF+56]), "+f"(d[OFF+57]), "+f"(d[OFF+58]), "+f"(d[OFF+59]), "+f"(d[OFF+60]), "+f"(d[OFF+61]), "+f"(d[OFF+62]), "+f"(d[OFF+63])
    : "l"(da), "l"(db), "r"(scale_d), "n"(TA), "n"(TB));
}
template<int TA, int TB, int OFF, int SZ> __device__ __forceinline__ void wgmma_n64_ss(float (&d)[SZ], uint64_t da, uint64_t db, int scale_d) {
  asm volatile("{\n.reg .pred p;\nsetp.ne.b32 p, %34, 0;\n"
    "wgmma.mma_async.sync.aligned.m64n64k16.f32.bf16.bf16 {%0,%1,%2,%3,%4,%5,%6,%7,%8,%9,%10,%11,%12,%13,%14,%15,%16,%17,%18,%19,%20,%21,%22,%23,%24,%25,%26,%27,%28,%29,%30,%31}, %32, %33, p, 1, 1, %35, %36;\n}\n"
    : "+f"(d[OFF+0]), "+f"(d[OFF+1]), "+f"(d[OFF+2]), "+f"(d[OFF+3]), "+f"(d[OFF+4]), "+f"(d[OFF+5]), "+f"(d[OFF+6]), "+f"(d[OFF+7]),
      "+f"(d[OFF+8]), "+f"(d[OFF+9]), "+f"(d[OFF+10]), "+f"(d[OFF+11]), "+f"(d[OFF+12]), "+f"(d[OFF+13]), "+f"(d[OFF+14]), "+f"(d[OFF+15]),
      "+f"(d[OFF+16]), "+f"(d[OFF+17]), "+f"(d[OFF+18]), "+f"(d[OFF+19]), "+f"(d[OFF+20]), "+f"(d[OFF+21]), "+f"(d[OFF+22]), "+f"(d[OFF+23]),
      "+f"(d[OFF+24]), "+f"(d[OFF+25]), "+f"(d[OFF+26]), "+f"(d[OFF+27]), "+f"(d[OFF+28]), "+f"(d[OFF+29]), "+f"(d[OFF+30]), "+f"(d[OFF+31])
    : "l"(da), "l"(db), "r"(scale_d), "n"(TA), "n"(TB));
}
template<int TB, int OFF, int SZ> __device__ __forceinline__ void wgmma_n64_rs(float (&d)[SZ], uint32_t a0, uint32_t a1, uint32_t a2, uint32_t a3, uint64_t db, int scale_d) {
  asm volatile("{\n.reg .pred p;\nsetp.ne.b32 p, %37, 0;\n"
    "wgmma.mma_async.sync.aligned.m64n64k16.f32.bf16.bf16 {%0,%1,%2,%3,%4,%5,%6,%7,%8,%9,%10,%11,%12,%13,%14,%15,%16,%17,%18,%19,%20,%21,%22,%23,%24,%25,%26,%27,%28,%29,%30,%31}, {%32,%33,%34,%35}, %36, p, 1, 1, %38;\n}\n"
    : "+f"(d[OFF+0]), "+f"(d[OFF+1]), "+f"(d[OFF+2]), "+f"(d[OFF+3]), "+f"(d[OFF+4]), "+f"(d[OFF+5]), "+f"(d[OFF+6]), "+f"(d[OFF+7]),
      "+f"(d[OFF+8]), "+f"(d[OFF+9]), "+f"(d[OFF+10]), "+f"(d[OFF+11]), "+f"(d[OFF+12]), "+f"(d[OFF+13]), "+f"(d[OFF+14]), "+f"(d[OFF+15]),
      "+f"(d[OFF+16]), "+f"(d[OFF+17]), "+f"(d[OFF+18]), "+f"(d[OFF+19]), "+f"(d[OFF+20]), "+f"(d[OFF+21]), "+f"(d[OFF+22]), "+f"(d[OFF+23]),
      "+f"(d[OFF+24]), "+f"(d[OFF+25]), "+f"(d[OFF+26]), "+f"(d[OFF+27]), "+f"(d[OFF+28]), "+f"(d[OFF+29]), "+f"(d[OFF+30]), "+f"(d[OFF+31])
    : "r"(a0), "r"(a1), "r"(a2), "r"(a3), "l"(db), "r"(scale_d), "n"(TB));
}
template<int TA, int TB, int OFF, int SZ> __device__ __forceinline__ void wgmma_n72_ss(float (&d)[SZ], uint64_t da, uint64_t db, int scale_d) {
  asm volatile("{\n.reg .pred p;\nsetp.ne.b32 p, %38, 0;\n"
    "wgmma.mma_async.sync.aligned.m64n72k16.f32.bf16.bf16 {%0,%1,%2,%3,%4,%5,%6,%7,%8,%9,%10,%11,%12,%13,%14,%15,%16,%17,%18,%19,%20,%21,%22,%23,%24,%25,%26,%27,%28,%29,%30,%31,%32,%33,%34,%35}, %36, %37, p, 1, 1, %39, %40;\n}\n"
    : "+f"(d[OFF+0]), "+f"(d[OFF+1]), "+f"(d[OFF+2]), "+f"(d[OFF+3]), "+f"(d[OFF+4]), "+f"(d[OFF+5]), "+f"(d[OFF+6]), "+f"(d[OFF+7]),
      "+f"(d[OFF+8]), "+f"(d[OFF+9]), "+f"(d[OFF+10]), "+f"(d[OFF+11]), "+f"(d[OFF+12]), "+f"(d[OFF+13]), "+f"(d[OFF+14]), "+f"(d[OFF+15]),
      "+f"(d[OFF+16]), "+f"(d[OFF+17]), "+f"(d[OFF+18]), "+f"(d[OFF+19]), "+f"(d[OFF+20]), "+f"(d[OFF+21]), "+f"(d[OFF+22]), "+f"(d[OFF+23]),
      "+f"(d[OFF+24]), "+f"(d[OFF+25]), "+f"(d[OFF+26]), "+f"(d[OFF+27]), "+f"(d[OFF+28]), "+f"(d[OFF+29]), "+f"(d[OFF+30]), "+f"(d[OFF+31]),
      "+f"(d[OFF+32]), "+f"(d[OFF+33]), "+f"(d[OFF+34]), "+f"(d[OFF+35])
    : "l"(da), "l"(db), "r"(scale_d), "n"(TA), "n"(TB));
}
template<int TB, int OFF, int SZ> __device__ __forceinline__ void wgmma_n40_rs(float (&d)[SZ], uint32_t a0, uint32_t a1, uint32_t a2, uint32_t a3, uint64_t db, int scale_d) {
  asm volatile("{\n.reg .pred p;\nsetp.ne.b32 p, %25, 0;\n"
    "wgmma.mma_async.sync.aligned.m64n40k16.f32.bf16.bf16 {%0,%1,%2,%3,%4,%5,%6,%7,%8,%9,%10,%11,%12,%13,%14,%15,%16,%17,%18,%19}, {%20,%21,%22,%23}, %24, p, 1, 1, %26;\n}\n"
    : "+f"(d[OFF+0]), "+f"(d[OFF+1]), "+f"(d[OFF+2]), "+f"(d[OFF+3]), "+f"(d[OFF+4]), "+f"(d[OFF+5]), "+f"(d[OFF+6]), "+f"(d[OFF+7]),
      "+f"(d[OFF+8]), "+f"(d[OFF+9]), "+f"(d[OFF+10]), "+f"(d[OFF+11]), "+f"(d[OFF+12]), "+f"(d[OFF+13]), "+f"(d[OFF+14]), "+f"(d[OFF+15]),
      "+f"(d[OFF+16]), "+f"(d[OFF+17]), "+f"(d[OFF+18]), "+f"(d[OFF+19])
    : "r"(a0), "r"(a1), "r"(a2), "r"(a3), "l"(db), "r"(scale_d), "n"(TB));
}
template<int TB, int OFF, int SZ> __device__ __forceinline__ void wgmma_n128_rs(float (&d)[SZ], uint32_t a0, uint32_t a1, uint32_t a2, uint32_t a3, uint64_t db, int scale_d) {
  asm volatile("{\n.reg .pred p;\nsetp.ne.b32 p, %69, 0;\n"
    "wgmma.mma_async.sync.aligned.m64n128k16.f32.bf16.bf16 {%0,%1,%2,%3,%4,%5,%6,%7,%8,%9,%10,%11,%12,%13,%14,%15,%16,%17,%18,%19,%20,%21,%22,%23,%24,%25,%26,%27,%28,%29,%30,%31,%32,%33,%34,%35,%36,%37,%38,%39,%40,%41,%42,%43,%44,%45,%46,%47,%48,%49,%50,%51,%52,%53,%54,%55,%56,%57,%58,%59,%60,%61,%62,%63}, {%64,%65,%66,%67}, %68, p, 1, 1, %70;\n}\n"
    : "+f"(d[OFF+0]), "+f"(d[OFF+1]), "+f"(d[OFF+2]), "+f"(d[OFF+3]), "+f"(d[OFF+4]), "+f"(d[OFF+5]), "+f"(d[OFF+6]), "+f"(d[OFF+7]),
      "+f"(d[OFF+8]), "+f"(d[OFF+9]), "+f"(d[OFF+10]), "+f"(d[OFF+11]), "+f"(d[OFF+12]), "+f"(d[OFF+13]), "+f"(d[OFF+14]), "+f"(d[OFF+15]),
      "+f"(d[OFF+16]), "+f"(d[OFF+17]), "+f"(d[OFF+18]), "+f"(d[OFF+19]), "+f"(d[OFF+20]), "+f"(d[OFF+21]), "+f"(d[OFF+22]), "+f"(d[OFF+23]),
      "+f"(d[OFF+24]), "+f"(d[OFF+25]), "+f"(d[OFF+26]), "+f"(d[OFF+27]), "+f"(d[OFF+28]), "+f"(d[OFF+29]), "+f"(d[OFF+30]), "+f"(d[OFF+31]),
      "+f"(d[OFF+32]), "+f"(d[OFF+33]), "+f"(d[OFF+34]), "+f"(d[OFF+35]), "+f"(d[OFF+36]), "+f"(d[OFF+37]), "+f"(d[OFF+38]), "+f"(d[OFF+39]),
      "+f"(d[OFF+40]), "+f"(d[OFF+41]), "+f"(d[OFF+42]), "+f"(d[OFF+43]), "+f"(d[OFF+44]), "+f"(d[OFF+45]), "+f"(d[OFF+46]), "+f"(d[OFF+47]),
      "+f"(d[OFF+48]), "+f"(d[OFF+49]), "+f"(d[OFF+50]), "+f"(d[OFF+51]), "+f"(d[OFF+52]), "+f"(d[OFF+53]), "+f"(d[OFF+54]), "+f"(d[OFF+55]),
      "+f"(d[OFF+56]), "+f"(d[OFF+57]), "+f"(d[OFF+58]), "+f"(d[OFF+59]), "+f"(d[OFF+60]), "+f"(d[OFF+61]), "+f"(d[OFF+62]), "+f"(d[OFF+63])
    : "r"(a0), "r"(a1), "r"(a2), "r"(a3), "l"(db), "r"(scale_d), "n"(TB));
}

struct Ptrs { const __nv_bfloat16 *x, *wqkv, *wo, *wr, *wg, *wu, *wd; __nv_bfloat16* out; };

__global__ void __cluster_dims__(2, 1, 1) __launch_bounds__(384, 1) fused_kernel(const __grid_constant__ CUtensorMap tmX, const __grid_constant__ CUtensorMap tmW,
                                                       const __grid_constant__ CUtensorMap tmO, const __grid_constant__ CUtensorMap tmG,
                                                       const __grid_constant__ CUtensorMap tmU, const __grid_constant__ CUtensorMap tmD,
                                                       const __grid_constant__ CUtensorMap tmM, const __grid_constant__ CUtensorMap tmPG,
                                                       const __grid_constant__ CUtensorMap tmPU, const __grid_constant__ CUtensorMap tmPD,
                                                       const Ptrs P) {
  extern __shared__ __align__(1024) uint8_t smem_raw[];
  if (TMPF && threadIdx.x == 0) { tmap_prefetch(&tmX); tmap_prefetch(&tmW); }
  const int tid = threadIdx.x, wid = __shfl_sync(~0u, tid >> 5, 0), wg = __shfl_sync(~0u, tid >> 7, 0), lane = tid & 31;
  const int pj = blockIdx.x >> 1, pi = pj - 36;
  const int b = (pj < 4 ? 32 + pj * 8 : pj < 36 ? pj - 4 : 33 + pi + ((pi * 37) >> 8)) * 2 + (blockIdx.x & 1);
  const int rb = b >> 4, cg = b & 15, hf = cg >> 3, c3 = cg & 7;
  const int jp = cg >> 1;
  const int fidx = jp == rb ? -1 : b - 2 * rb - (jp > rb ? 2 : 0);
  const uint32_t rank = b & 1, own = rank << 24;
  const uint32_t zero = gridDim.y - 1;
  const uint32_t sm = own + sb, mb = own + bars;
  auto chunk_of = [&](int p) { return (int)((0x1765432FEDCBA980ull >> (4 * p)) & 15) ^ (p == 0 || p == 15 ? cg : p < 9 ? cg & 8 : cg & 14); };
  const int kl = (jp & 3) * 256;
  auto k_of = [&](int kb) { return kb >= 12 ? kl + (kb - 12) * 64 : kb * 64 < kl ? kb * 64 : kb * 64 + 256; };
  auto load_w = [&](int kb) {
#pragma unroll
    for (int i = 0; i < 3; i++) tma_2d(sm + woff(kb & 3) + i * WSTR, &tmW, i * D_ + cg * 64, k_of(kb), mb + B_FULL + 8 * (kb & 3), EFW);
  };
  TS_DECL; TS(0); TSG(30);
  if (wid == 8) {
    if (elect_one()) {
      if (smem_u32(smem_raw) != sm) {
#pragma unroll
        for (int i = 0; i < PERT; i++) sts1(mb, lds1(mb));
        asm volatile("trap;");
      }
#pragma unroll
      for (int s = 0; s < 4; s++) mbar_init(mb + B_FULL + 8 * s, 1);
      asm volatile("fence.mbarrier_init.release.cluster;" ::: "memory");
      if (INIF) fence_async_smem();
    }
  } else if (wid == 9) {
    if (elect_one()) {
#pragma unroll
      for (int i = 4; i < 32; i++)
        if (i != 27) mbar_init(mb + 8 * i, i < 8 ? 8 : i == 8 ? 64 : i == 26 ? 2 : i == 29 ? 4 : 1);
      asm volatile("fence.mbarrier_init.release.cluster;" ::: "memory");
      if (INIF) fence_async_smem();
    }
  }
  __syncwarp();
  asm volatile("barrier.cluster.arrive.relaxed.aligned;" ::: "memory");
  if (wid == 8) {
    if (elect_one()) {
      mbar_expect_tx(mb + B_FULL, STAGE_B);
      tma_2d(sm + xoff(0, 0), &tmX, k_of(0), rb * 256, mb + B_FULL, EFX);
      tma_2d(sm + xoff(0, 1), &tmX, k_of(0), rb * 256 + 128, mb + B_FULL, EFX);
      load_w(0);
    }
    __syncwarp();
  }
  asm volatile("barrier.cluster.wait.aligned;" ::: "memory");

  if (wg == 2) {
    asm volatile("setmaxnreg.dec.sync.aligned.u32 56;");
    auto wait3 = [&](int i) { mbar_wait(sm + bar3(i), 0); };
    if (wid == 8) {
      if (elect_one()) {
        int np = fidx >= 0 ? 0 : 32;
        if (fidx >= 0) mbar_expect_tx(mb + B_FFN, 32 * 512);
#pragma unroll 1
        for (int kb = 1; kb < 16; kb++) {
          const uint32_t fb = mb + B_FULL + 8 * (kb & 3);
          mbar_wait(fb + B_EMPTY, ((kb >> 2) & 1) ^ 1);
          mbar_expect_tx(fb, STAGE_B);
          tma_2d_mc(sm + xoff(kb & 3, rank), &tmX, k_of(kb), rb * 256 + rank * 128, fb, EFX);
          load_w(kb);
          if (kb >= 12) asm volatile("mbarrier.arrive.shared::cta.b64 _, [%0], 7;" :: "r"(fb + B_EMPTY) : "memory");
#pragma unroll 1
          for (int n = ((NPK << 16) >> (4 * kb)) & 15; n > 0 && np < 32; n--, np++)
            tma_2d(sm + OFF_STATS + 512, (np & 1) ? &tmPU : &tmPG, (fidx >> 1) * 64, (np >> 1) * 64 + rank * 32, mb + B_FFN, false);
        }
        if (fidx >= 0) { mbar_wait(mb + B_FFN, 0); mbar_expect_tx(mb + B_FFN, 65536 + NPD * 512); mbar_expect_tx(mb + B_FFN + 8, 65536); }
#pragma unroll
        for (int p = 4; p < 8; p++) sts4(sm + OFF_STATS + p * 144, 0x3F803F80u, 0x3F803F80u, 0x3F803F80u, 0x3F803F80u);
        fence_async_smem();
        mbar_arrive(mb + B_LATE);
        PTS(2);
        mbar_expect_tx(mb + B_KVL, 36864);
        mbar_wait(mb + B_LATE, 0);
        wait3(60);
        delay(clk(), KDELAY);
        bulk_load(sm + 11 * SLOT_B, &G.kvp[cg * 2304], SLOT_B, mb + B_KVL);
        bulk_load(sm + 13 * SLOT_B, &G.kvp[cg * 2304 + 1024], SLOT_B, mb + B_KVL);
        bulk_load(sm + 2 * SLOT_B, &G.kvp[cg * 2304 + 2048], 4096, mb + B_KVL);
        PTS(3);
        const uint4* src = &G.obuf[(rb * 4 + rank * 2 + hf) * 64 * 128];
        wait3(48);
        const uint32_t t1 = clk();
#pragma unroll
        for (int p = 1; p < 5; p++) {
          delay(t1, ADELAY + (p - 1) * ASTEP);
          bulk_load_mc(sm + (10 + (p & 3)) * SLOT_B + rank * 8192, src + ((hf ^ 1) * 8 + p - 1) * 512, sm + bar3(p) + rank * 256, 3);
        }
        PTS(7);
#pragma unroll 1
        for (int i = 5; i < 17; i++) {
          const int p = min(i, 15);
          const uint32_t d = sm + (10 + (p & 3)) * SLOT_B + rank * 8192, fb = sm + bar3(0) + o3(p) + rank * 256;
          const uint4* q = src + chunk_of(i & 15) * 512;
          mbar_wait(sm + bar3(48) + o3(p - 4 + ((LATEP >> p) & 1)), 0);
          bulk_load_mc(d, q, fb, i < 15 ? 3 : 1 << ((i ^ rank ^ 1) & 1));
        }
        PTS(15);
      }
    } else {
      const int r4 = lane >> 3, c8 = lane & 7;
      const uint32_t eb = (lane << 24) + bars + B_EMPTY;
      auto tagged = [](float v, uint32_t tag) { return ((__float_as_uint(v) + 128) & ~255u) | tag; };
      auto gather = [&](uint32_t tag) {
        const int q = (wid - 9) * 24 + lane;
        const uint4* cp = lane < 24 ? &G.csp[cg * 8 * 48 + q] : &G.st1[rb * 8 * 48 + (wid - 9) * 8 + lane - 24];
        uint4 v[8];
        delay(clk(), GDELAY);
#pragma unroll 1
        for (int it = 0;; it++) {
#pragma unroll
          for (int i = 0; i < 8; i++) v[i] = ld_rlx4(cp + i * 48);
          uint32_t x = 0;
#pragma unroll
          for (int i = 0; i < 8; i++) { v[i].x ^= tag; v[i].y ^= tag; v[i].z ^= tag; v[i].w ^= tag; x |= v[i].x | v[i].y | v[i].z | v[i].w; }
          if (!__any_sync(~0u, (x & 255) != 0)) break;
          SPINCHK(it, 3);
        }
        float c[4] = {0.f, 0.f, 0.f, 0.f};
#pragma unroll
        for (int i = 0; i < 8; i++) { c[0] += __uint_as_float(v[i].x); c[1] += __uint_as_float(v[i].y); c[2] += __uint_as_float(v[i].z); c[3] += __uint_as_float(v[i].w); }
        const uint32_t h0 = pack2(c[0], c[1]), h1 = pack2(c[2], c[3]), ca = sm + OFF_COLSUM + (q >> 1) * 32 + (q & 1) * 8;
        if (lane < 24) {
          sts2f(ca, __uint_as_float(h0), __uint_as_float(h1));
          sts2f(ca + 16, __uint_as_float(pack2(c[0] - bf_lo(h0), c[1] - bf_hi(h0))), __uint_as_float(pack2(c[2] - bf_lo(h1), c[3] - bf_hi(h1))));
        }
        fence_async_smem();
        mbar_arrive(mb + B_AUX);
      };
      const int r2 = lane >> 4, c16 = lane & 15;
      float a[12];
#pragma unroll
      for (int i = 0; i < 12; i++) a[i] = 0.f;
      auto kb_of = [](int it) { return (int)(KORD >> (4 * it)) & 15; };
      if (wid == 9) {
        const uint32_t a0 = sm + rb * 1024 + r2 * 128 + (((c16 >> 1) ^ r2) << 4) + (c16 & 1) * 8;
        const uint2* gw = (const uint2*)(P.wqkv + (kl + rb * 8 + r2) * 3072 + cg * 64) + c16;
#pragma unroll 1
        for (int it = 0; it < 16; it++) {
          uint2 w[12];
          const int kb = kb_of(it);
          if (kb >= 12) {
#pragma unroll
            for (int j = 0; j < 12; j++) w[j] = ld_rlx2(gw + (j >> 2) * 256 + (j & 3) * 1536);
            gw += 64 * 768;
          } else {
            const uint32_t so = a0 + woff(kb & 3);
            mbar_wait(mb + B_FULL + 8 * (kb & 3), (kb >> 2) & 1);
            static_for<0, 12>([&](auto ic) { constexpr int i = decltype(ic)::value;
              const float2 v = lds2f_o<(i >> 2) * WSTR + (i & 3) * 256>(so ^ ((i & 3) << 5)); w[i] = make_uint2(__float_as_uint(v.x), __float_as_uint(v.y)); });
            uint32_t done = 0;
#pragma unroll
            for (int i = 0; i < 12; i++) done |= w[i].y;
            if (lane < 2) mbar_arrive_rem(eb + 8 * (kb & 3) + (done & zero));
          }
#pragma unroll
          for (int i = 0; i < 12; i++) { float* q = a + (i >> 2) * 4; q[0] += bf_lo(w[i].x); q[1] += bf_hi(w[i].x); q[2] += bf_lo(w[i].y); q[3] += bf_hi(w[i].y); }
        }
        if (lane == 0) PTS(8);
        float c[6];
#pragma unroll
        for (int i = 0; i < 6; i++) {
          const int o = (i >> 1) * 4 + (i & 1);
          c[i] = (r2 ? a[o + 2] : a[o]) + __shfl_xor_sync(~0u, r2 ? a[o] : a[o + 2], 16);
        }
        bar_sync(5, 96);
        if (lane == 0) PTS(5);
        const uint32_t tag = lds1(mb + B_SW + 4) & 255;
#pragma unroll
        for (int sg = 0; sg < 3; sg++) st_rlx2((uint2*)&G.csp[(cg * 8 + rb) * 48] + sg * 32 + c16 * 2 + r2, tagged(c[sg * 2], tag), tagged(c[sg * 2 + 1], tag));
      } else {
       if (wid == 10) {
        if (lane < 24 && (lane & 28) != 4) sts4(sm + OFF_STATS + (lane < 16 ? lane * 128 + c8 * 16 : c8 * 16), 0x3F803F80u, 0x3F803F80u, 0x3F803F80u, 0x3F803F80u);
       } else {
        mbar_wait(mb + B_FULL + 8 * PFST, 0);
        const uint32_t ep = ld_rlx(&G.epoch);
        uint4 v[4];
#pragma unroll
        for (int i = 0; i < 4; i++) v[i] = ld_cg4((const uint4*)P.wr + lane + i * 32);
        if (elect_one()) { tmap_prefetch(&tmO); tmap_prefetch(&tmG); tmap_prefetch(&tmU); tmap_prefetch(&tmD); tmap_prefetch(&tmPD); tmap_prefetch(&tmM); }
        __syncwarp();
        const uint4 sv = make_uint4(SENT, SENT, SENT, SENT);
#pragma unroll 1
        for (int i = 0; i < 9; i++) {
          uint4* q = i < 8 ? &G.obuf[((rb * 4 + (i >> 1)) * 64 + cg * 4) * 128 + (i & 1) * 256 + lane] : &G.kvp[cg * 2304 + rb * 288 + lane];
#pragma unroll
          for (int j = 0; j < 8; j++) q[j * 32] = sv;
          if (i == 8) q[256] = sv;
          else if (lane < ((i & 1) ? 24 : 16)) l2_prefetch((i & 1) ? P.wqkv + (kl + (i >> 1) * 64 + rb * 8 + c8) * 3072 + r4 * 1024 + cg * 64 : P.x + (b * 16 + lane) * D_ + kl + i * 32);
        }
        float s = 0.f;
#pragma unroll 1
        for (int i = 0; i < 4; i++) {
          s += (bf_lo(v[0].x) + bf_hi(v[0].x)) + (bf_lo(v[0].y) + bf_hi(v[0].y)) + (bf_lo(v[0].z) + bf_hi(v[0].z)) + (bf_lo(v[0].w) + bf_hi(v[0].w));
          v[0] = v[1]; v[1] = v[2]; v[2] = v[3];
        }
#pragma unroll
        for (int o = 16; o; o >>= 1) s += __shfl_xor_sync(~0u, s, o);
        if (lane == 0) sts2f(mb + B_SW, s, __uint_as_float(ep + 1));
       }
        const uint32_t xa = sm + (c3 * 16 + r4) * 128 + ((c8 ^ r4) << 4);
        const uint4* gx = (const uint4*)(P.x + (b * 16 + r4) * D_ + kl) + c8;
        uint32_t e[4] = {0, 0, 0, 0};
        uint4 wq;
#pragma unroll 1
        for (int kb = wid == 10 ? 0 : 12; kb < (wid == 10 ? 12 : 16); kb++) {
          uint4 v[4];
          if (!(kb & 3)) wq = ld_cg4((const uint4*)(P.wr + k_of(kb + r4)) + c8);
          if (kb >= 12) {
#pragma unroll
            for (int j = 0; j < 4; j++) v[j] = ld_cg4(gx + j * 512);
            gx += 8;
          } else {
            const uint32_t so = xa + xoff(kb & 3, hf);
            mbar_wait(mb + B_FULL + 8 * (kb & 3), (kb >> 2) & 1);
            v[0] = lds4_o<0>(so); v[1] = lds4_o<512>(so ^ 64); v[2] = lds4_o<1024>(so); v[3] = lds4_o<1536>(so ^ 64);
            if (lane < 2) mbar_arrive_rem(eb + 8 * (kb & 3) + ((v[0].x | v[1].x | v[2].x | v[3].x) & zero));
          }
#pragma unroll
          for (int j = 0; j < 16; j++) {
            const uint32_t u = (j & 3) == 0 ? v[j >> 2].x : (j & 3) == 1 ? v[j >> 2].y : (j & 3) == 2 ? v[j >> 2].z : v[j >> 2].w;
            const float d0 = bf_lo(u), d1 = bf_hi(u);
            a[j >> 2] += d0 + d1; a[4 + (j >> 2)] = fmaf(d0, d0, fmaf(d1, d1, a[4 + (j >> 2)]));
          }
          cut<1>(zero);
          const int sl = (kb & 3) * 8 + c8;
          const uint4 wn = make_uint4(__shfl_sync(~0u, wq.x, sl), __shfl_sync(~0u, wq.y, sl), __shfl_sync(~0u, wq.z, sl), __shfl_sync(~0u, wq.w, sl));
#pragma unroll
          for (int j = 0; j < 4; j++) e[j] = hfma2(v[j].x, wn.x, hfma2(v[j].y, wn.y, hfma2(v[j].z, wn.z, hfma2(v[j].w, wn.w, e[j]))));
        }
        float mean, pd;
#pragma unroll 1
        for (int h = 0; h < 2; h++) {
          float u[4], v[2];
#pragma unroll
          for (int i = 0; i < 4; i++) u[i] = ((lane & 4) ? a[4 + i] : a[i]) + __shfl_xor_sync(~0u, (lane & 4) ? a[i] : a[4 + i], 4);
#pragma unroll
          for (int i = 0; i < 2; i++) v[i] = ((lane & 2) ? u[2 + i] : u[i]) + __shfl_xor_sync(~0u, (lane & 2) ? u[i] : u[2 + i], 2);
          mean = pd;
          pd = ((lane & 1) ? v[1] : v[0]) + __shfl_xor_sync(~0u, (lane & 1) ? v[0] : v[1], 1);
#pragma unroll
          for (int j = 0; j < 4; j++) { a[j] = bf_lo(e[j]); a[4 + j] = bf_hi(e[j]); }
        }
        if (wid == 11) {
          sts2f(sm + OFF_COLSUM + 512 + lane * 8, mean, pd);
          fence_gpu();
          bar_arrive(5, 96); PTS(0);
          if (elect_one()) {
#pragma unroll 1
            for (int p = 0; p < 16; p++) {
              const uint32_t ad = sm + bar3(0) + o3(p);
              mbar_init(ad, 1); mbar_init(ad + 256, 1); mbar_init(ad + 448, 8); mbar_init(ad + 704, p == 0 ? 2 : p == 12 ? 1 : p == 15 ? 7 : 8);
              mbar_expect_tx(ad, 8192); mbar_expect_tx(ad + 256, 8192); mbar_expect_tx(mb + B_FULL3 + 8 * p, SLOT_B);
            }
            asm volatile("fence.mbarrier_init.release.cluster;" ::: "memory");
            fence_async_smem();
            mbar_arrive_rem(bars + B_LATE); mbar_arrive_rem((1u << 24) + bars + B_LATE);
          }
          __syncwarp();
        } else {
          if (lane == 0) PTS(1);
          bar_sync(5, 96);
          const float2 u = lds2f(sm + OFF_COLSUM + 512 + lane * 8), sw = lds2f(mb + B_SW);
          mean = (mean + u.x) * (1.f / D_);
          pd += u.y;
          pd += __shfl_xor_sync(~0u, pd, 4);
          const float var = fmaxf(fmaf(-mean, mean, __shfl_xor_sync(~0u, mean, 4)), 0.f);
          const uint32_t tag = __float_as_uint(sw.y) & 255;
          if (c8 < 4) {
            st_rlx2((uint2*)G.st1 + (b >> 1) * 96 + rank * 16 + r4 + 4 * c8, tagged(-mean, tag), tagged(rsq(var + 1e-5f), tag));
            st_rlx(&G.pred[b * 16 + r4 + 4 * c8], (ordered(fmaf(-mean, sw.x, pd)) & ~255u) | tag);
          }
        }
      }
      if (wid < 11) gather(lds1(mb + B_SW + 4) & 255);
      if (wid == 9) {
        if (lane == 0) PTS(6);
        {
          const uint4 sv = make_uint4(SENT, SENT, SENT, SENT);
          uint4* y = &G.ybuf[b * NFFN * 4 + lane];
#pragma unroll
          for (int i = 0; i < 14; i++) y[i * 32] = sv;
          if (lane < 16) G.st2[b * 16 + lane] = make_uint4(0, 0, 0, 0);
          G.hsel[b * 64 + lane] = sv; G.hsel[b * 64 + 32 + lane] = sv;
          if (b < 8) { G.cand[b * 32 + lane] = SENT; G.cst[b * 32 + lane] = make_uint4(0, 0, 0, 0); }
          fence_gpu();
          __syncwarp();
          if (lane == 0) mbar_arrive(mb + B_LATE);
        }
      } else if (wid == 10) {
        {
          mbar_wait(mb + B_FULL + 24, 1);
#pragma unroll 1
          for (int r = -4; r < (fidx >= 0 ? 16 : 0); r++) {
            l2_prefetch((r < 0 ? (const char*)P.wo + (b + 1) * 16384 : (const char*)P.wd + fidx * 65536) + r * 4096 + lane * 128);
            delay(clk(), PDT);
          }
          PTS(4);
        }
      }
      mbar_wait(mb + B_LATE, 0);
      if (wid == 9) {
        if (elect_one()) {
          wait3(60);
#pragma unroll 1
          for (int p = 0; p < 16; p++) {
            const bool mix = (unsigned)(p - 1) < 8;
            const int c1 = mix ? ((p - 1) >> 1) * 16 : 0, c2 = mix ? (hf ^ 1) * 8 + ((p - 1) & 1) * 4 : chunk_of(p) * 4;
            const uint32_t d = sm + (uint32_t)((WO_SLOTS >> (4 * p)) & 15) * SLOT_B;
            if (((0xFE22 | 1 << WOP) >> p) & 1) mbar_wait(p == WOP ? sm + bar3(WOW) : p < 9 ? mb + B_EMPTY + 8 * (p >> 2) : sm + bar3(32) + 8 * (p - 9), p < 9 && p != WOP);
            if ((TICKM >> p) & 1) {
              uint32_t g0, g1;
              asm volatile("mov.u32 %0, %%globaltimer_lo;" : "=r"(g0) :: "memory");
              for (int it = 0; it < 4096; it++) { asm volatile("mov.u32 %0, %%globaltimer_lo;" : "=r"(g1) :: "memory"); if ((g0 ^ g1) >= TICK) break; }
            }
            if (EFWO) asm volatile("cp.async.bulk.tensor.4d.shared::cluster.global.mbarrier::complete_tx::bytes.L2::cache_hint [%0], [%1, {0, %3, %4, %5}], [%2], %6;"
                         :: "r"(d), "l"(mix ? &tmM : &tmO), "r"(mb + B_FULL3 + 8 * p), "r"(c1), "r"(c2), "r"(c3 * 2), "l"(l2_stream()) : "memory");
            else asm volatile("cp.async.bulk.tensor.4d.shared::cluster.global.mbarrier::complete_tx::bytes [%0], [%1, {0, %3, %4, %5}], [%2];"
                         :: "r"(d), "l"(mix ? &tmM : &tmO), "r"(mb + B_FULL3 + 8 * p), "r"(c1), "r"(c2), "r"(c3 * 2) : "memory");
            if (p >= 10) PTS(7 + p);
          }
          if (fidx >= 0) {
            mbar_expect_tx(mb + B_FULL, 65536);
#pragma unroll 1
            for (int i = 0; i < 8; i++) {
              const int f = (0x76325140 >> (4 * i)) & 15;
              const uint32_t d = sm + ((GU_SLOTS >> (4 * f)) & 15) * SLOT_B, fb = mb + (i < 4 ? B_FULL : B_FFN);
              mbar_wait(sm + bar3(32) + o3(7 + i - (i > 5)), 0);
              tma_2d(d, &tmG, fidx * 32, f * 128, fb, EFF);
              tma_2d(d + 8192, &tmU, fidx * 32, f * 128, fb, EFF);
              PTS(23 + i);
            }
#pragma unroll 1
            for (int i = 0; i < 4; i++) {
              mbar_wait(sm + bar3(32) + o3(13 + ((i + 1) >> 1)), 0);
              tma_3d(sm + ((D_SLOTS >> (4 * i)) & 15) * SLOT_B, &tmD, 0, fidx * 32, i * 4, mb + B_FFN + 8, EFF);
            }
          }
        }
      } else if (wid == 11) {
        const uint2 w = ld_rlx2((const uint2*)(P.wr + c3 * 128) + lane);
        wait3(36);
        sts1(sm + OFF_LNP + (lane & 1) * 128 + (lane >> 1) * 4, w.x); sts1(sm + OFF_LNP + (lane & 1) * 128 + 64 + (lane >> 1) * 4, w.y);
        if (lane < 16) sts1(sm + OFF_LNP + 256 + lane * 4, 0x3F803F80u);
        const uint32_t tag = lds1(mb + B_SW + 4) & 255;
        uint4 k;
        for (int it = 0;; it++) {
          k = ld_rlx4((const uint4*)&G.pred[rb * 256 + hf * 64 + r2 * 128] + c16);
          k.x ^= tag; k.y ^= tag; k.z ^= tag; k.w ^= tag;
          if (!__any_sync(~0u, (k.x | k.y | k.z | k.w) & 255)) break;
          SPINCHK(it, 13);
        }
        const uint2 ahead = top2(k.x | (lane * 4), k.y | (lane * 4 + 1), k.z | (lane * 4 + 2), k.w | (lane * 4 + 3));
        if (lane == 0) sts2f(sm + OFF_MSC + 8, __uint_as_float((ahead.x & 127) ^ NOSPEC), __uint_as_float((ahead.y & 127) ^ NOSPEC));
        __syncwarp();
        if (lane == 0) mbar_arrive(mb + B_FULL3 + 8 * 15);
      } else if (fidx >= 0 && elect_one()) {
#pragma unroll 1
        for (int i = 0; i < NPD; i++) { mbar_wait(sm + bar3(32) + o3(PD0 + i), 0); tma_2d(sm + OFF_COLSUM, &tmPD, 0, fidx * 256 + i * 32, mb + B_FFN, false); }
      }
    }
    __syncwarp();
    const float sw = __uint_as_float(lds1(mb + B_SW));
    const int rr = lane >> 4, row00 = rb * 256 + hf * 64;
    uint2 pick;
    if (wid == 8) {
      wait3(61);
      delay(clk(), SDELAY);
      uint4 v;
      int id;
      for (int it = 0;; it++) {
        v = ld_rlx4(&G.cst[jp * 32 + lane]);
        id = __float2int_rn(__uint_as_float(v.w));
        if (!__any_sync(~0u, (id & 15) != 8)) break;
        SPINCHK(it, 14);
      }
      float2 pr;
      const uint32_t k = route(v, sw, id >> 4, pr);
      pick.x = __reduce_max_sync(~0u, k); pick.y = __reduce_max_sync(~0u, k == pick.x ? 0 : k);
      if (k == pick.x || k == pick.y) sts4(sm + OFF_MSC + 16 + (k == pick.y) * 16, k, lane, __float_as_uint(pr.x), __float_as_uint(pr.y));
      __syncwarp();
      if (lane == 0) { mbar_arrive(mb + B_SEL); PTS(16); }
    } else if (wid == 9) {
      wait3(61);
      delay(clk(), LDELAY);
      uint4 v[4];
      for (int it = 0;; it++) {
#pragma unroll
        for (int i = 0; i < 4; i++) v[i] = ld_rlx4(&G.st2[row00 + (i >> 1) * 128 + (i & 1) * 32 + lane]);
        if (!__any_sync(~0u, (v[0].w & v[1].w & v[2].w & v[3].w) != 0x41000000u)) break;
        SPINCHK(it, 6);
      }
      uint32_t k[4];
#pragma unroll
      for (int i = 0; i < 4; i++) {
        float2 pr;
        k[i] = route(v[i], sw, row00 + (i >> 1) * 128 + (i & 1) * 32 + lane, pr);
        const float nm = __uint_as_float(v[i].x) * (-1.f / D_);
        sts2f(sm + OFF_LNP + (i * 32 + lane) * 8, __uint_as_float(pack2(pr.x, pr.x)), __uint_as_float(pack2(nm, nm)));
      }
      const uint2 m = top2(k[0], k[1], k[2], k[3]);
      if (lane == 0) { st_rlx2(&G.cand[c3 * 32 + (rb * 2 + hf) * 2], m.x, m.y); sts2f(sm + OFF_MSC + 0, __uint_as_float(m.x), __uint_as_float(m.y)); }
      wait3(62);
      __syncwarp();
      if (lane == 0) { mbar_arrive(mb + B_OUT); PTS(12); }
      const int ca = 2047 - (((lane & 4) ? m.y : m.x) & 2047), ta = ((ca >> 1) & 64) + (ca & 63);
      uint32_t h0, h1, h2, h3;
      ldsm4_o<0>(sm + HST + ta * 256 + ((((lane & 3) * 4 + (lane >> 3)) ^ (ta & 7)) << 4), h0, h1, h2, h3);
      st_rlx4(&G.hsel[(32 + (rb * 2 + hf) * 2 + rr) * 128 + c3 * 16 + (lane & 15)], make_uint4(h0, h1, h2, h3));
    }
    mbar_wait(mb + B_OUT, 0);
    const float2 cf = lds2f(sm + OFF_MSC + 0);
    const int ca0 = ~__float_as_int(cf.x), ca1 = ~__float_as_int(cf.y), cand0 = ((ca0 >> 1) & 64) + (ca0 & 63), cand1 = ((ca1 >> 1) & 64) + (ca1 & 63);
    auto norm = [](const uint4& v, const float2& pr) {
      const uint32_t r = __float_as_uint(pr.x), m = __float_as_uint(pr.y);
      return make_uint4(hfma2(hadd2(v.x, m), r, v.x), hfma2(hadd2(v.y, m), r, v.y), hfma2(hadd2(v.z, m), r, v.z), hfma2(hadd2(v.w, m), r, v.w));
    };
    uint4* const og = (uint4*)(P.out + row00 * D_ + c3 * 128) + (lane & 15);
    if (wid == 8) {
      delay(clk(), CDELAY);
      uint32_t k;
      for (int it = 0;; it++) { k = ld_rlx(&G.cand[c3 * 32 + lane]); if (!__any_sync(~0u, k == SENT)) break; SPINCHK(it, 12); }
      const uint32_t m1 = __reduce_max_sync(~0u, k), m2 = __reduce_max_sync(~0u, k == m1 ? 0 : k);
      const uint32_t miss = ((m1 ^ pick.x) | (m2 ^ pick.y)) & 2047;
      if (miss && (k == m1 || k == m2)) {
        float2 pr;
        route(ld_rlx4(&G.st2[2047 - (k & 2047)]), sw, 0, pr);
        sts4(sm + OFF_MSC + 48 + (k == m2) * 16, k, 32 + lane, __float_as_uint(pr.x), __float_as_uint(pr.y));
      }
      if (lane == 0) sts1(sm + OFF_MSC + 80, miss);
      __syncwarp();
      if (lane == 0) { mbar_arrive(mb + B_SEL2); PTS(13); }
      const uint32_t kc = __float_as_uint(rr ? cf.y : cf.x);
      const int c = rr ? cand1 : cand0;
      if (kc != m1 && kc != m2) og[(c + (c & 64)) * 128] = norm(lds4(sm + HST + c * 256 + (((lane & 15) ^ (c & 7)) << 4)), lds2f(sm + OFF_LNP + c * 8));
    }
#pragma unroll 1
    for (int t0 = wid == 8 ? 120 : (11 - wid) * 8; t0 < (wid == 8 ? 128 : 120) * !NOOUT; t0 += 24) {
      uint4 v[4];
      float2 pr[4];
      const uint32_t ad = sm + HST + t0 * 256 + lane * 16;
      static_for<0, 4>([&](auto ic) { constexpr int i = decltype(ic)::value; v[i] = lds4_o<i * 512>(ad ^ (rr << 4) ^ (i << 5)); pr[i] = lds2f_o<i * 16>(sm + OFF_LNP + (t0 + rr) * 8); });
#pragma unroll
      for (int i = 0; i < 4; i++) v[i] = norm(v[i], pr[i]);
      if (t0 >= OHOLD) wait3(63);
#pragma unroll
      for (int i = 0; i < 4; i++) {
        const int tr = t0 + rr + 2 * i;
        if (tr != cand0 && tr != cand1) {
          if (OUTEF) asm volatile("st.global.L2::cache_hint.v4.u32 [%0], {%1,%2,%3,%4}, %5;" :: "l"(og + (tr + (tr & 64)) * 128), "r"(v[i].x), "r"(v[i].y), "r"(v[i].z), "r"(v[i].w), "l"(l2_stream()) : "memory");
          else og[(tr + (tr & 64)) * 128] = v[i];
        }
      }
    }
    if (wid == 11 && lane == 0) PTS(31);
  } else {
    asm volatile("setmaxnreg.inc.sync.aligned.u32 224;");
    const int t128 = tid & 127, warp = wid & 3, g = lane >> 2, t = lane & 3;
    const int mb3 = rb * 4 + wg * 2 + hf;
    float acc[64];
    uint4 abuf[4][4];
    uint32_t to;
    int tid2;
    {
      float acc0[96], acc1[96];
#pragma unroll
      for (int i = 0; i < 96; i++) { asm volatile("" : "=f"(acc0[i])); asm volatile("" : "=f"(acc1[i])); }
      const uint32_t xo0 = dlo(sb, 16) + hf * 512, xo1 = dlo(sb, 16) + (hf ^ 1) * 512;
      const uint32_t eb0 = (t128 << 24) + bars + B_EMPTY;
#pragma unroll 1
      for (int kb = 0; kb < 12; kb++) {
        const int s = kb & 3;
        mbar_wait(mb + B_FULL + 8 * s, (kb >> 2) & 1);
        if (LOCK) bar_sync(13, 256);
        if (kb == 0) TS(1);
        const uint32_t xs = xoff(s, wg) >> 4, ws = dlo(sb + woff(s), WSTR);
        pin(acc0); pin(acc1);
        wg_fence();
#pragma unroll
        for (int k = 0; k < 4; k++) {
          const uint64_t db = dsc<1024, 1>(ws + k * 128);
          const int sd = k == 0 ? kb : 1;
          wgmma_n192_ss<0, 1, 0>(acc0, dsc<1024, 1>(xs + xo0 + k * 2), db, sd);
          wgmma_n192_ss<0, 1, 0>(acc1, dsc<1024, 1>(xs + xo1 + k * 2), db, sd);
          if (k == RELK || k == 3) wg_commit();
          if (k == RELK) {
            wg_wait<1>();
            if (kb > 0 && t128 < 2) mbar_arrive_rem(eb0 + 8 * ((kb - 1) & 3));
          }
        }
        pin(acc0); pin(acc1);
      }
      float qa0[32], qa1[32], kv0[64], kv1[64];
#pragma unroll
      for (int i = 0; i < 96; i++) { if (i < 32) { qa0[i] = acc0[i]; qa1[i] = acc1[i]; } else { kv0[i - 32] = acc0[i]; kv1[i - 32] = acc1[i]; } }
      uint2 st[2][2];
      uint4 am;
      auto center = [&](float (&q)[32], float (&kv)[64], const uint2 (&v)[2]) {
        const uint32_t n0 = v[0].x & (t == 0 ? ~255u : 0u), n1 = v[1].x & (t == 0 ? ~255u : 0u);
        am = make_uint4(__byte_perm(n0, 0, 0x3232), __byte_perm(n1, 0, 0x3232),
                        __byte_perm(__float_as_uint(__uint_as_float(n0) - bf_hi(n0)), 0, 0x3232), __byte_perm(__float_as_uint(__uint_as_float(n1) - bf_hi(n1)), 0, 0x3232));
        wg_fence();
        wgmma_n64_rs<1, 0>(q, am.x, am.y, am.z, am.w, dsc<32, 0>(dlo(sb + OFF_COLSUM, 0)), 1);
        wgmma_n128_rs<1, 0>(kv, am.x, am.y, am.z, am.w, dsc<32, 0>(dlo(sb + OFF_COLSUM + 256, 0)), 1);
      };
      auto load_st = [&]() {
        mbar_wait(mb + B_AUX, 0);
#pragma unroll
        for (int i = 0; i < 4; i++) st[i >> 1][i & 1] = ld_rlx2((const uint2*)G.st1 + ((rb * 4 + wg * 2 + ((i >> 1) ^ hf)) * 2 + (warp >> 1)) * 96 + (warp & 1) * 16 + (i & 1) * 8 + g);
      };
      if (!wg) {
        wg_wait<0>();
        if (t128 < 2) mbar_arrive_rem(eb0 + 24);
        load_st();
#pragma unroll 1
        for (int s = 0; s < 4; s++) mbar_wait(mb + B_FULL + 8 * s, 1);
        bar_sync(6, 256);
      }
      static_for<0, 4>([&](auto sc) {
        constexpr int s = decltype(sc)::value;
        if (wg) mbar_wait(mb + B_FULL + 8 * s, 1);
        const uint32_t xs = (wg ? xoff(s, 1) : xoff(s, 0)) >> 4, ws = dlo(sb + woff(s) + WSTR, WSTR);
        pin(kv0); pin(kv1); pin(qa0); pin(qa1);
        wg_fence();
#pragma unroll
        for (int k = 0; k < 4; k++) {
          const uint64_t db = dsc<1024, 1>(ws + k * 128);
          wgmma_n128_ss<0, 1, 0>(kv0, dsc<1024, 1>(xs + xo0 + k * 2), db, 1);
          wgmma_n128_ss<0, 1, 0>(kv1, dsc<1024, 1>(xs + xo1 + k * 2), db, 1);
          if (k == 3 || (k == 2 && s == 0)) wg_commit();
          if (k == (s ? 3 : 2) && s < 3) {
            wg_wait<1>();
            if (s == 0) { if (wg && t128 < 2) mbar_arrive_rem(eb0 + 24); }
            else if (!wg) bar_arrive(8 + s, 256);
          }
        }
        if (s == STLD && wg) load_st();
      });
      center(qa0, kv0, st[0]);
      wg_commit();
      if (wg) bar_arrive(6, 256);
      float rl[2][2];
      uint32_t r2[2][2];
#pragma unroll
      for (int i = 0; i < 4; i++) { const float r = __uint_as_float(st[i >> 1][i & 1].y & ~255u); r2[i >> 1][i & 1] = pack2(r, r); rl[i >> 1][i & 1] = r * 1.4426950408889634f; }
      const uint32_t sad = sm + (wg ? 11 : 2) * SLOT_B + (warp * 16 + (lane & 15)) * 128 + (((lane >> 4) ^ (lane & 7)) << 4);
      wg_wait<0>();
      pin(kv0); pin(kv1); pin(qa0); pin(qa1); pin4(am);
      center(qa1, kv1, st[1]);
      wg_commit();
      if (wg) bar_arrive(11, 256);
      if (CUTS & 1) cut<2>(zero);
      TS(2);
      auto phi8 = [&](const float* a, int m) {
        return make_uint4(phi2(a[0], a[1], r2[m][0], rl[m][0]), phi2(a[2], a[3], r2[m][1], rl[m][1]), phi2(a[4], a[5], r2[m][0], rl[m][0]), phi2(a[6], a[7], r2[m][1], rl[m][1]));
      };
      auto stage = [&](float (&a)[64], auto mc) {
        constexpr int m = decltype(mc)::value;
        uint4 r[4];
#pragma unroll
        for (int j = 0; j < 4; j++) r[j] = phi8(a + j * 8, m);
        if (m == 0 || wg) bar_sync(wg ? 9 + m : 11, 256 + (r[SBAR].x & zero));
#pragma unroll
        for (int j = 0; j < 4; j++) {
          const int v = 32 + j * 8;
          stsm4_o<WSTR + m * 8192>(sad ^ (j << 5), hmul2(pack2(a[v], a[v + 1]), r2[m][0]), hmul2(pack2(a[v + 2], a[v + 3]), r2[m][1]),
                                                   hmul2(pack2(a[v + 4], a[v + 5]), r2[m][0]), hmul2(pack2(a[v + 6], a[v + 7]), r2[m][1]));
        }
#pragma unroll
        for (int j = 0; j < 4; j++) stsm4_o<m * 8192>(sad ^ (j << 5), r[j].x, r[j].y, r[j].z, r[j].w);
      };
      stage(kv0, std::integral_constant<int, 0>{});
      wg_wait<0>();
      pin(kv1); pin(qa1); pin4(am);
      stage(kv1, std::integral_constant<int, 1>{});
      fence_async_smem();
      TS(3);
      uint32_t xr[8][4];
      auto load_xr = [&]() {
        const uint32_t xa = sm + hf * 8192 + (warp * 16 + (lane & 15)) * 128 + (((lane >> 4) ^ (lane & 7)) << 4);
#pragma unroll
        for (int q = 0; q < 8; q++) ldsm4_o<0>((xa ^ ((q & 3) << 5)) + xoff(rank * 2 + (q >> 2), wg), xr[q][0], xr[q][1], xr[q][2], xr[q][3]);
      };
      if (!wg) { bar_arrive(4, 256); load_xr(); }
      else {
        float ka[36];
#pragma unroll
        for (int i = 0; i < 36; i++) ka[i] = 0.f;
        auto kv_mma = [&](auto ic) {
          constexpr int i = decltype(ic)::value;
          constexpr uint32_t o = sb + (i < 8 ? 11 : 2) * SLOT_B + (i & 7) * 2048;
          wgmma_n72_ss<1, 1, 0>(ka, dsc<1024, 1>(dlo(o, 8192)), dsc<1024, 1>(dlo(o + WSTR, sb + OFF_STATS - o - WSTR)), i);
        };
        mbar_wait(mb + B_LATE, 0);
        bar_sync(3, 128);
        wg_fence();
        static_for<0, 8>(kv_mma);
        wg_commit();
        uint4* dst = &G.kvp[cg * 2304 + rb * 32];
        if (CUTS & 4) cut<3>(zero);
        load_xr();
        bar_sync(4, 256);
        static_for<8, 16>(kv_mma);
        wg_commit();
        if (QHOLD == 1) bar_arrive(8, 256);
        wg_wait<0>();
        pin(ka);
        if (QHOLD == 2) bar_arrive(8, 256);
        TS(4);
        if (warp < 2) {
          st_rlx4(dst + warp * 512 + lane, make_uint4(pack2(ka[0], ka[1]), pack2(ka[4], ka[5]), pack2(ka[8], ka[9]), pack2(ka[12], ka[13])));
          st_rlx4(dst + warp * 512 + 256 + lane, make_uint4(pack2(ka[2], ka[3]), pack2(ka[6], ka[7]), pack2(ka[10], ka[11]), pack2(ka[14], ka[15])));
        } else {
          st_rlx4(dst + warp * 512 + lane, make_uint4(pack2(ka[16], ka[17]), pack2(ka[20], ka[21]), pack2(ka[24], ka[25]), pack2(ka[28], ka[29])));
          st_rlx4(dst + warp * 512 + 256 + lane, make_uint4(pack2(ka[18], ka[19]), pack2(ka[22], ka[23]), pack2(ka[26], ka[27]), pack2(ka[30], ka[31])));
        }
        st_rlx((uint32_t*)(dst + 2048) + t128, pack2(ka[32], ka[34]));
        if (QHOLD == 3) bar_arrive(8, 256);
        if (t128 == 0) mbar_arrive(sm + bar3(60));
      }
      TS(5);
      uint32_t pq[16];
      auto q_mma = [&](float (&q)[32], uint32_t xo, int next) {
#pragma unroll 1
        for (int s = 0; s < 4; s++) {
          const uint32_t xs = (xoff(s, wg) >> 4) + xo, ws = dlo(sb + woff(s), 8192);
          pin(q);
          wg_fence();
#pragma unroll
          for (int k = 0; k < 4; k++) wgmma_n64_ss<0, 1, 0>(q, dsc<1024, 1>(xs + k * 2), dsc<1024, 1>(ws + k * 128), 1);
          wg_commit();
        }
        if (next) bar_arrive(next, 256);
        wg_wait<0>();
        pin(q);
      };
      auto q_phi = [&](float (&q)[32], int m) {
#pragma unroll
        for (int j = 0; j < 4; j++) { const uint4 r = phi8(q + j * 8, m); pq[j * 4] = r.x; pq[j * 4 + 1] = r.y; pq[j * 4 + 2] = r.z; pq[j * 4 + 3] = r.w; }
      };
      auto o_of = [&](uint4 (&o)[4], uint4* first, bool pub) {
        float oa[2][20];
#pragma unroll
        for (int i = 0; i < 40; i++) oa[i / 20][i % 20] = 0.f;
        wg_fence();
#pragma unroll
        for (int ks = 0; ks < 4; ks++) {
          wgmma_n40_rs<1, 0>(oa[ks >> 1], pq[ks * 4], pq[ks * 4 + 1], pq[ks * 4 + 2], pq[ks * 4 + 3], dsc<1024, 1>(dlo(sb + OFF_KVB + ks * 2048, 8192)), ks & 1);
          if (ks & 1) wg_commit();
        }
#pragma unroll
        for (int h = 0; h < 2; h++) {
          if (h) wg_wait<0>(); else wg_wait<1>();
          pin(oa[h]);
          const float (&d)[20] = oa[h];
          const float i0 = rcp(d[16] + 1e-6f), i1 = rcp(d[18] + 1e-6f);
#pragma unroll
          for (int k2 = 0; k2 < 2; k2++) {
            o[h * 2 + k2] = make_uint4(pack2(d[k2 * 8] * i0, d[k2 * 8 + 1] * i0), pack2(d[k2 * 8 + 2] * i1, d[k2 * 8 + 3] * i1),
                                       pack2(d[k2 * 8 + 4] * i0, d[k2 * 8 + 5] * i0), pack2(d[k2 * 8 + 6] * i1, d[k2 * 8 + 7] * i1));
            if (pub && h * 2 + k2 < NPUB) st_rlx4(first + (h * 2 + k2) * 1024, o[h * 2 + k2]);
          }
        }
#pragma unroll
        for (int i = 0; i < 16; i++) asm volatile("" : "+r"(pq[i]) :: "memory");
      };
      bar_sync(wg ? 7 : 8, 256);
      q_mma(qa1, xo1, wg ? 8 : 7);
      q_phi(qa1, 1);
      tid2 = __shfl_sync(~0u, tid, lane);
      uint32_t done = 0;
#pragma unroll
      for (int j = 0; j < 8; j++) done |= pq[2 * j] | pq[2 * j + 1] | xr[j][3];
      bar_sync(wg ? 7 : 8, 256 + (done & zero));
      q_mma(qa0, xo0, wg ? 0 : 7);
      if (t128 == 0) mbar_arrive(mb + B_EMPTY + 8 * wg);
      TS(6);
      {
        uint4 a, v[8];
        uint32_t z[8], zs;
        const int blk = warp * 2 + wg;
        mbar_wait(mb + B_KVL, 0);
        static_for<0, 8>([&](auto ic) { constexpr int i = decltype(ic)::value; v[i] = lds4_o<sb + 11 * SLOT_B + i * 512>(own + (blk + (blk & 4)) * 4096 + lane * 16); });
#pragma unroll
        for (int i = 0; i < 8; i++) z[i] = lds1(sm + 2 * SLOT_B + i * 512 + t128 * 4);
#pragma unroll 1
        for (int it = 0;; it++) {
          zs = hadd2(hadd2(hadd2(z[0], z[1]), hadd2(z[2], z[3])), hadd2(hadd2(z[4], z[5]), hadd2(z[6], z[7])));
          a = hadd8(hadd8(hadd8(v[0], v[1]), hadd8(v[2], v[3])), hadd8(hadd8(v[4], v[5]), hadd8(v[6], v[7])));
          TSV(20, it + 1);
          if (!__any_sync(~0u, hnan(hadd2(hadd2(hadd2(a.x, a.y), hadd2(a.z, a.w)), zs)))) break;
          uint32_t mm = 0;
#pragma unroll
          for (int i = 0; i < 8; i++) mm = max4(max(mm, z[i]), v[i]);
          if (!__any_sync(~0u, mm == SENT)) break;
#pragma unroll
          for (int i = 0; i < 8; i++) { v[i] = ld_rlx4(&G.kvp[cg * 2304 + blk * 256 + i * 32 + lane]); z[i] = ld_rlx((const uint32_t*)&G.kvp[cg * 2304 + 2048 + i * 32] + t128); }
          SPINCHK(it, 4);
        }
        TS(23);
        const uint32_t kb0 = sm + OFF_KVB + blk * 1024 + (lane & 7) * 128;
        stsm4(kb0 + (((lane >> 3) ^ (lane & 7)) << 4), a.x, a.y, a.z, a.w);
        asm volatile("stmatrix.sync.aligned.m8n8.x1.shared.b16 [%0], {%1};" :: "r"(kb0 + ((4 ^ (lane & 7)) << 4)), "r"(zs >> (16 * wg)) : "memory");
        fence_async_smem();
        bar_sync(12, 256);
      }
      TS(7);
      if (t128 == 0) mbar_arrive_rem((wg << 24) + sb + bar3(48));
      to = clk();
      o_of(abuf[1], &G.obuf[((mb3 ^ 1) * 64 + hf * 32 + c3) * 128 + (tid2 & 127)], true);
      TS(29);
      cut<4>(zero);
      pin(qa0);
      q_phi(qa0, 0);
      o_of(abuf[0], nullptr, false);
#pragma unroll
      for (int q = 0; q < 32; q++) { asm volatile("" : "+r"(xr[q >> 2][q & 3])); acc[q * 2] = bf_lo(xr[q >> 2][q & 3]); acc[q * 2 + 1] = bf_hi(xr[q >> 2][q & 3]); }
      pin(acc);
    }
    {
    const int t128 = tid2 & 127, lane = tid2 & 31, g = lane >> 2, t = lane & 3;
    uint4* const od0 = &G.obuf[(mb3 * 64 + cg * 4) * 128 + t128];
    TS(8);
    {
      const uint32_t la = own + wg * 8192 + t128 * 16, fa = sm + wg * 256;
#pragma unroll
      for (int i = 8; i < 16; i++) abuf[i >> 2][i & 3] = make_uint4(0, 0, 0, 0);
#pragma unroll 1
      for (int pp = 0; pp < 16; pp += 4) {
        static_for<0, 4>([&](auto jc) {
          constexpr int j = decltype(jc)::value;
          constexpr uint32_t ro = sb + (10 + ((j + 1) & 3)) * SLOT_B;
          const int p = pp + j;
          const uint32_t o1 = ((p + 1) >> 3) * 128 + ((p + 1) & 7) * 8;
          uint4 (&a)[4] = abuf[j];
          uint4 (&n)[4] = abuf[(j + 1) & 3];
          auto fetch = [&]() {
            mbar_wait(fa + bar3(0) + o1, 0);
            n[0] = lds4_o<ro>(la); n[1] = lds4_o<ro + 2048>(la); n[2] = lds4_o<ro + 4096>(la); n[3] = lds4_o<ro + 6144>(la);
          };
          const bool early = j == 3 ? pp < 12 : (j > 1 || pp > 0);
          const uint32_t bs = dlo(sb, 8192) + ((WO_SLOTS >> (4 * p)) & 15) * (SLOT_B >> 4);
          mbar_wait(mb + B_FULL3 + 8 * p, 0);
          if (early) fetch();
          if (p == 1) TS(28);
          if (p == 2) TS(9);
          pin(acc);
          wg_fence();
#pragma unroll
          for (int k = 0; k < 4; k++) wgmma_n128_rs<1, 0>(acc, a[k].x, a[k].y, a[k].z, a[k].w, dsc<1024, 1>(bs + k * 128), 1);
          wg_commit();
          if (j < 2 && pp == 0) {
            if (j == 0 && NPUB < 4) {
              delay(to, BDELAY);
#pragma unroll
              for (int k = NPUB; k < 4; k++) st_rlx4(&G.obuf[((mb3 ^ 1) * 64 + hf * 32 + c3) * 128 + t128 + k * 1024], n[k]);
            }
            if (j == 0) TS(24);
            fetch();
            if (j == 0) TS(27);
          }
          if (__any_sync(~0u, max(max4(max4(0, n[0]), n[1]), max4(max4(0, n[2]), n[3])) == SENT)) {
            int pl = p + 1; asm volatile("" : "+r"(pl));
            const uint4* q = &G.obuf[(mb3 * 64 + chunk_of(pl) * 4) * 128 + t128];
#pragma unroll 1
            for (int it = 0;; it++) {
#pragma unroll
              for (int i = 0; i < 4; i++) n[i] = ld_rlx4(q + i * 128);
              TSV(21, _ts | 1 << pl);
              if (!__any_sync(~0u, max(max4(max4(0, n[0]), n[1]), max4(max4(0, n[2]), n[3])) == SENT)) break;
              SPINCHK(it, 5);
            }
          }
          if (lane == 0 && p < 11) mbar_arrive_rem((wg << 24) + sb + bar3(48) + o1);
          wg_wait<1>();
          pin(acc);
#pragma unroll
          for (int i = 0; i < 4; i++) pin4(abuf[(j + 3) & 3][i]);
          if (j < 3 && pp == 0) {
#pragma unroll
            for (int k = 0; k < 4; k++) if (((W0POS >> (4 * k)) & 15) == j) st_rlx4(od0 + k * 128, abuf[0][k]);
          }
          if (lane == 0) mbar_arrive(sm + bar3(32) + (p >> 3) * 128 + (p & 7) * 8);
        });
      }
    }
    uint4 wb[4];
#pragma unroll
    for (int i = 0; i < 4; i++) wb[i] = lds4(sm + OFF_LNP + ((g & 1) ? t * 64 : 256) + i * 16);
    const float2 ah = lds2f(sm + OFF_MSC + 8);
    wg_wait<0>();
    pin(acc);
#pragma unroll
    for (int i = 0; i < 4; i++) pin4(abuf[3][i]);
    TS(10);
    const uint32_t msc = sm + OFF_MSC;
    uint32_t hp[8][4];
    {
      float se[2][4], q[4] = {0.f, 0.f, 0.f, 0.f};
#pragma unroll
      for (int i = 0; i < 8; i++) se[i >> 2][i & 3] = 0.f;
#pragma unroll
      for (int j = 0; j < 8; j++) {
#pragma unroll
        for (int i = 0; i < 4; i++) { const float a = acc[j * 8 + i * 2], c = acc[j * 8 + i * 2 + 1]; hp[j][i] = pack2(a, c); q[i] = fmaf(a, a, fmaf(c, c, q[i])); }
        mma16816(se[j & 1], hp[j], (j & 1) ? wb[j >> 1].z : wb[j >> 1].x, (j & 1) ? wb[j >> 1].w : wb[j >> 1].y);
      }
      const bool od = t & 1;
      const float q0 = q[0] + q[2], q1 = q[1] + q[3];
      float qq = (od ? q1 : q0) + __shfl_xor_sync(~0u, od ? q0 : q1, 1);
      qq += __shfl_xor_sync(~0u, qq, 2);
      const float ss = od ? se[0][2] + se[1][2] : se[0][0] + se[1][0], ee = od ? se[0][3] + se[1][3] : se[0][1] + se[1][1];
#pragma unroll 1
      for (int c = 0; c < 2; c++) {
        const int tr = __float_as_int(c ? ah.y : ah.x), slot = (rb * 2 + hf) * 2 + c;
        if ((tr >> 4) == wid) {
          const int sl = (tr & 7) * 4 + ((tr >> 3) & 1);
          const float s1 = __shfl_sync(~0u, ss, sl), s2 = __shfl_sync(~0u, qq, sl), s3 = __shfl_sync(~0u, ee, sl);
          red4(lane < 8, &G.cst[lane * 32 + slot], s1, s2, s3, c3 ? 1.f : (float)((mb3 * 64 + (tr & 63)) * 16 + 1));
          if (g == (tr & 7)) {
#pragma unroll
            for (int i = 0; i < 4; i++)
              st_rlx4(&G.hsel[slot * 128 + c3 * 16 + i * 4 + t], (tr & 8) ? make_uint4(hp[2 * i][1], hp[2 * i][3], hp[2 * i + 1][1], hp[2 * i + 1][3])
                                                                          : make_uint4(hp[2 * i][0], hp[2 * i][2], hp[2 * i + 1][0], hp[2 * i + 1][2]));
          }
        }
      }
      red4(t < 2, &G.st2[mb3 * 64 + warp * 16 + (t & 1) * 8 + g], ss, qq, ee, 1.f);
      if (lane == 0) mbar_arrive(sm + bar3(61));
      TS(11);
    }
    uint32_t wa[32][4], wd[8][2][4];
    const uint32_t ga = own + ((lane >> 3) & 1) * 8192 + ((lane >> 4) * 8 + (lane & 7)) * 64 + ((warp ^ ((lane >> 1) & 3)) << 4);
    const uint32_t dw = sm + ((D_SLOTS >> (2 * (wid & 6))) & 15) * SLOT_B + (wid & 1) * 8192;
    const uint32_t da = dw + ((lane >> 4) * 8 + (lane & 7)) * 128 + ((((lane >> 3) & 1) ^ (lane & 7)) << 4);
    const uint32_t xl = own + ((lane & 16) ? 12 + wg : 3 + 4 * wg) * SLOT_B + (lane & 8) * 1024 + (lane & 7) * 16;
    float ya[8][4];
    int pass = 0;
    auto load_gu = [&](int f) {
      const uint32_t ad = ga + ((GU_SLOTS >> (16 * wg + 4 * f)) & 15) * SLOT_B;
      static_for<0, 8>([&](auto ic) { constexpr int i = decltype(ic)::value; ldsm4t_o<sb + i * 1024>(ad, wa[f * 8 + i]); });
    };
    if (fidx >= 0) mbar_wait(mb + B_FULL, 0);
    load_gu(0); load_gu(1);
    {
      bar_sync(1, 256);
      const uint32_t ha = sm + HST + wid * 4096 + (lane & 15) * 256 + (((lane >> 4) ^ (lane & 7)) << 4);
      static_for<0, 8>([&](auto jc) { constexpr int j = decltype(jc)::value; stsm4_o<(j >> 2) * 128>(ha ^ ((j & 3) << 5), hp[j][0], hp[j][1], hp[j][2], hp[j][3]); });
      asm volatile("fence.acq_rel.cta;" ::: "memory");
      __syncwarp();
      if (lane == 0) mbar_arrive(sm + bar3(62));
    }
    if (fidx >= 0) mbar_wait(mb + B_FFN, 1);
#pragma unroll 1
    for (;; pass++) {
      if (pass) { load_gu(0); load_gu(1); }
      load_gu(2);
      TS(15);
      mbar_wait(mb + B_SEL, 0);
      const uint4 sx = lds4(msc + 16 + pass * 32 + (lane & 16));
      TS(26);
      const uint4* xp = &G.hsel[sx.y * 128 + wid * 16 + (lane & 15)];
      uint4 xv = ld_rlx4(xp);
      load_gu(3);
      if (!pass) {
        if (fidx >= 0) mbar_wait(mb + B_FFN + 8, 0);
        static_for<0, 8>([&](auto ic) { constexpr int i = decltype(ic)::value; ldsm4t_o<(i & 1) * 2048>(da ^ ((i >> 1) << 5), wd[i >> 1][i & 1]); });
      }
#pragma unroll 1
      for (int it = 0; __any_sync(~0u, max4(0, xv) == SENT); it++) { xv = ld_rlx4(xp); SPINCHK(it, 7); }
      const float f = __uint_as_float(sx.z), n = __uint_as_float(sx.w);
      sts4(dw + ((lane & 12) * 2 + (lane >> 4) * 4 + t) * 16, pack2(fmaf(bf_lo(xv.x), f, n), fmaf(bf_hi(xv.x), f, n)), pack2(fmaf(bf_lo(xv.y), f, n), fmaf(bf_hi(xv.y), f, n)),
           pack2(fmaf(bf_lo(xv.z), f, n), fmaf(bf_hi(xv.z), f, n)), pack2(fmaf(bf_lo(xv.w), f, n), fmaf(bf_hi(xv.w), f, n)));
      if (wid == rb && (g & 3) == (cg >> 2)) sts4(msc + 96 + (lane >> 4) * 16 + t * 32, xv.x, xv.y, xv.z, xv.w);
      bar_sync(2 + wg, 128);
      TS(14);
      float gu[4][4];
#pragma unroll
      for (int i = 0; i < 16; i++) gu[i >> 2][i & 3] = 0.f;
      uint4 xb[4];
      static_for<0, 4>([&](auto ic) { constexpr int i = decltype(ic)::value; xb[i] = lds4_o<sb + i * 128>(xl); });
#pragma unroll
      for (int ks = 0; ks < 8; ks++) {
        if (ks == 6) {
#pragma unroll
          for (int j = 0; j < 8; j++) xb[3].x |= wd[4 + (j >> 1)][j & 1][3] & zero;
        }
#pragma unroll
        for (int j = 0; j < 4; j++) mma16816(gu[j], wa[j * 8 + ks], (ks & 1) ? xb[ks >> 1].z : xb[ks >> 1].x, (ks & 1) ? xb[ks >> 1].w : xb[ks >> 1].y);
        if (ks == 2) static_for<0, 8>([&](auto jc) { constexpr int j = decltype(jc)::value; ldsm4t_o<4096 + (j & 1) * 2048>(da ^ ((j >> 1) << 5), wd[4 + (j >> 1)][j & 1]); });
      }
      {
        float o[4];
#pragma unroll
        for (int j = 0; j < 4; j++) o[j] = t == 0 ? gu[0][j] : t == 1 ? gu[1][j] : t == 2 ? gu[2][j] : gu[3][j];
        const float e0 = ((t & 2) ? o[2] : o[0]) + __shfl_xor_sync(~0u, (t & 2) ? o[0] : o[2], 2), e1 = ((t & 2) ? o[3] : o[1]) + __shfl_xor_sync(~0u, (t & 2) ? o[1] : o[3], 2);
        sts1(sm + (3 + 4 * wg) * SLOT_B + 1024 + t128 * 4, __float_as_uint(((t & 1) ? e1 : e0) + __shfl_xor_sync(~0u, (t & 1) ? e0 : e1, 1)));
      }
      TS(25);
      bar_sync(1, 256);
      const uint4 p0 = lds4_o<sb + 3 * SLOT_B + 1024>(own + lane * 16), p1 = lds4_o<sb + 7 * SLOT_B + 1024>(own + lane * 16);
      const float g0 = __uint_as_float(p0.x) + __uint_as_float(p1.x), g1 = __uint_as_float(p0.y) + __uint_as_float(p1.y);
      const float u0 = __uint_as_float(p0.z) + __uint_as_float(p1.z), u1 = __uint_as_float(p0.w) + __uint_as_float(p1.w);
      const uint32_t act = pack2(g0 * rcp(1.f + ex2(-1.4426950408889634f * g0)) * u0, g1 * rcp(1.f + ex2(-1.4426950408889634f * g1)) * u1);
      uint32_t bq[4];
#pragma unroll
      for (int i = 0; i < 4; i++) {
        const uint32_t lo = __shfl_sync(~0u, act, i * 8 + 2 * t), hi = __shfl_sync(~0u, act, i * 8 + 2 * t + 1);
        bq[i] = __byte_perm(lo, hi, (g & 1) ? 0x7632 : 0x5410);
      }
      TS(16);
#pragma unroll
      for (int i = 0; i < 8; i++) { ya[i][0] = 0.f; ya[i][1] = 0.f; ya[i][2] = 0.f; ya[i][3] = 0.f; }
#pragma unroll
      for (int ks = 0; ks < 2; ks++)
#pragma unroll
        for (int i = 0; i < 8; i++) mma16816(ya[i], wd[i][ks], bq[ks * 2], bq[ks * 2 + 1]);
      mbar_wait(mb + B_SEL2, 0);
      if (pass || !lds1(msc + 80)) break;
      bar_sync(1, 256);
    }
    if (fidx >= 0) {
      uint2* const yp = (uint2*)&G.ybuf[((wid * 16 + t * 2) * NFFN + fidx) * 4] + g;
#pragma unroll
      for (int h = 0; h < 2; h++) {
        float o[4];
#pragma unroll
        for (int j = 0; j < 4; j++) o[j] = t == 0 ? ya[h * 4][j] : t == 1 ? ya[h * 4 + 1][j] : t == 2 ? ya[h * 4 + 2][j] : ya[h * 4 + 3][j];
        st_rlx2(yp + h * (8 * NFFN * 8), __float_as_uint(o[0]), __float_as_uint(o[1]));
        st_rlx2(yp + h * (8 * NFFN * 8) + NFFN * 8, __float_as_uint(o[2]), __float_as_uint(o[3]));
      }
    }
    TS(17);
    const uint32_t ty = clk();
    if (wid < 7) {
      const uint4* const yq = &G.ybuf[b * NFFN * 4 + wid * 64 + lane];
      const uint4 sel = lds4(msc + 16 + pass * 32 + (lane & 1) * 16);
      const uint32_t fh = lds1(msc + 96 + (lane & 1) * 16 + (g & 3) * 32 + (cg & 3) * 4);
      const float r = __uint_as_float(sel.x ^ (~(uint32_t)((int)sel.x >> 31) | 0x80000000u));
      float sg = rcp(1.f + ex2(-1.4426950408889634f * r)), base = fmaf((lane & 2) ? bf_hi(fh) : bf_lo(fh), 1.f + __uint_as_float(sel.z), __uint_as_float(sel.w));
      __nv_bfloat16* op = P.out + (size_t)(2047 - (sel.x & 2047)) * D_ + b * 8 + ((lane >> 1) & 7);
      asm volatile("" : "+f"(sg), "+f"(base), "+l"(op) :: "memory");
      delay(ty, YDELAY);
      uint4 v0, v1;
#pragma unroll 1
      for (int it = 0;; it++) {
        v0 = ld_rlx4(yq); v1 = ld_rlx4(yq + 32);
        TSV(22, it + 1);
        if (!__any_sync(~0u, max(max4(0, v0), max4(0, v1)) == SENT)) break;
        SPINCHK(it, 8);
      }
      if (lane == 0) mbar_arrive(sm + bar3(63));
      TS(18);
      float y0 = __uint_as_float(v0.x) + __uint_as_float(v1.x), y1 = __uint_as_float(v0.y) + __uint_as_float(v1.y);
      float y2 = __uint_as_float(v0.z) + __uint_as_float(v1.z), y3 = __uint_as_float(v0.w) + __uint_as_float(v1.w);
      float z0 = ((lane & 16) ? y2 : y0) + __shfl_xor_sync(~0u, (lane & 16) ? y0 : y2, 16), z1 = ((lane & 16) ? y3 : y1) + __shfl_xor_sync(~0u, (lane & 16) ? y1 : y3, 16);
      z0 = ((lane & 8) ? z1 : z0) + __shfl_xor_sync(~0u, (lane & 8) ? z0 : z1, 8);
      z0 += __shfl_xor_sync(~0u, z0, 4);
      const uint32_t yx = sm + OFF_COLSUM;
      if (!(lane & 4)) sts1(yx + (t * 4 + (lane >> 3)) * 32 + wid * 4, __float_as_uint(z0));
      if (wid) bar_arrive(1, 224);
      else {
        bar_sync(1, 224);
        const uint4 a = lds4(yx + (lane & 15) * 32), c = lds4(yx + (lane & 15) * 32 + 16);
        const float y = ((__uint_as_float(a.x) + __uint_as_float(a.y)) + (__uint_as_float(a.z) + __uint_as_float(a.w))) + ((__uint_as_float(c.x) + __uint_as_float(c.y)) + __uint_as_float(c.z));
        if (lane < 16) *op = __float2bfloat16(fmaf(y, sg, base));
        if (b == 0 && lane == 16) G.epoch = lds1(mb + B_SW + 4);
      }
    }
    }
    TS(19); TSG(31);
    if (warp == 0) TS_DUMP(wg);
  }
}

typedef CUresult (*EncodeFn)(CUtensorMap*, CUtensorMapDataType, cuuint32_t, void*, const cuuint64_t*, const cuuint64_t*, const cuuint32_t*,
                             const cuuint32_t*, CUtensorMapInterleave, CUtensorMapSwizzle, CUtensorMapL2promotion, CUtensorMapFloatOOBfill);
void make_map(EncodeFn enc, CUtensorMap* m, const void* p, uint64_t cols, uint64_t rows, uint64_t d0, uint32_t b0, uint32_t b1, uint32_t b2, CUtensorMapSwizzle sw,
              CUtensorMapL2promotion promo = CU_TENSOR_MAP_L2_PROMOTION_L2_128B) {
  cuuint64_t dims[3] = {d0, rows, cols / d0}, str[2] = {cols * 2, d0 * 2};
  cuuint32_t box[3] = {b0, b1, b2}, es[3] = {1, 1, 1};
  enc(m, CU_TENSOR_MAP_DATA_TYPE_BFLOAT16, b2 ? 3 : 2, const_cast<void*>(p), dims, str, box, es, CU_TENSOR_MAP_INTERLEAVE_NONE, sw,
      promo, CU_TENSOR_MAP_FLOAT_OOB_FILL_NONE);
}

}

extern "C" void kernel_launch(void* const* d_in, const int* in_sizes, int n_in, void* d_out, int out_size) {
  (void)in_sizes; (void)n_in; (void)out_size;
  Ptrs P;
  P.x = (const __nv_bfloat16*)d_in[0]; P.wqkv = (const __nv_bfloat16*)d_in[1]; P.wo = (const __nv_bfloat16*)d_in[2];
  P.wr = (const __nv_bfloat16*)d_in[4]; P.wg = (const __nv_bfloat16*)d_in[5]; P.wu = (const __nv_bfloat16*)d_in[6];
  P.wd = (const __nv_bfloat16*)d_in[7]; P.out = (__nv_bfloat16*)d_out;
  void* fn = nullptr;
  cudaDriverEntryPointQueryResult q;
  cudaGetDriverEntryPoint("cuTensorMapEncodeTiled", &fn, cudaEnableDefault, &q);
  EncodeFn enc = (EncodeFn)fn;
  CUtensorMap tmX, tmW, tmO, tmG, tmU, tmD, tmM, tmPG, tmPU, tmPD;
  make_map(enc, &tmX, P.x, D_, S_, D_, 64, 128, 0, CU_TENSOR_MAP_SWIZZLE_128B);
  make_map(enc, &tmW, P.wqkv, 3 * D_, D_, 3 * D_, 64, 64, 0, CU_TENSOR_MAP_SWIZZLE_128B);
  make_map(enc, &tmG, P.wg, F_, D_, F_, 32, 128, 0, CU_TENSOR_MAP_SWIZZLE_64B);
  make_map(enc, &tmU, P.wu, F_, D_, F_, 32, 128, 0, CU_TENSOR_MAP_SWIZZLE_64B);
  make_map(enc, &tmD, P.wd, D_, F_, 64, 64, 32, 4, CU_TENSOR_MAP_SWIZZLE_128B);
  make_map(enc, &tmPG, P.wg, F_, D_, F_, 8, 32, 0, CU_TENSOR_MAP_SWIZZLE_NONE);
  make_map(enc, &tmPU, P.wu, F_, D_, F_, 8, 32, 0, CU_TENSOR_MAP_SWIZZLE_NONE);
  make_map(enc, &tmPD, P.wd, 128, F_ * 8, 128, 8, 32, 0, CU_TENSOR_MAP_SWIZZLE_NONE, CU_TENSOR_MAP_L2_PROMOTION_L2_256B);
  for (int m = 0; m < 2; m++) {
    cuuint64_t dims[4] = {64, m ? 64u : 16u, m ? 16u : 64u, 16}, str[3] = {2 * D_, (m ? 128u : 32u) * D_, 128};
    cuuint32_t box[4] = {64, 16, 4, 2}, es[4] = {1, 1, 1, 1};
    enc(m ? &tmM : &tmO, CU_TENSOR_MAP_DATA_TYPE_BFLOAT16, 4, const_cast<__nv_bfloat16*>(P.wo), dims, str, box, es, CU_TENSOR_MAP_INTERLEAVE_NONE,
        CU_TENSOR_MAP_SWIZZLE_128B, CU_TENSOR_MAP_L2_PROMOTION_L2_128B, CU_TENSOR_MAP_FLOAT_OOB_FILL_NONE);
  }
  cudaFuncSetAttribute(fused_kernel, cudaFuncAttributeMaxDynamicSharedMemorySize, SMEM_BYTES);
  fused_kernel<<<NCTA, 384, SMEM_BYTES>>>(tmX, tmW, tmO, tmG, tmU, tmD, tmM, tmPG, tmPU, tmPD, P);
}
```

```cpp
#include <cuda_runtime.h>
#include <cuda.h>
#include <cuda_bf16.h>
#include <stdint.h>
#include <type_traits>

namespace {

constexpr int S_ = 2048, D_ = 1024, F_ = 3584;
constexpr int NCTA = 128, NFFN = 112;
constexpr uint32_t SENT = 0xFFFFFFFFu;
constexpr int SPIN_LIMIT = 1 << 20;

#define ADELAY 800
#define NPK 0x233333333333ull
#define KDELAY 800
#define SBAR 2
#define NOOUT 0
#define OHOLD 72
#define OUTEF 0
#define CUTS 0
#define EFO 0
#define EFWO 0
#define TMPF 1
#define INIF 0
#define FEV 0xDCCB10FFu
#define NPUB 2
#define ASTEP 300
#define BDELAY 1500
#define LATEP 0x20
#define PD0 2
#define NPD 8
#define PDT 100
#define KORD 0xBA9F87E6D54C3210ull
#define SDELAY 450
#define LDELAY 500
#define NOSPEC 0
#define LOCK 1
#define STLD 2
#define RELK 1
#define PERT 5
#define QHOLD 3
#define CDELAY 0
#define YDELAY 500
#define EFX 0
#define EFW 1
#define EFF 1
#define GDELAY 800
#define PFST 1
#define W0POS 0x2211
constexpr uint32_t STAGE_B = 57344;
__host__ __device__ constexpr uint32_t xoff(int s, int w) { return ((0x87CA3651u >> (4 * (s + 4 * w))) & 15) * 16384; }
__host__ __device__ constexpr uint32_t woff(int s) { return (s < 2 ? 9 * 16384 : 0) + (s & 1) * 8192; }
constexpr uint32_t WSTR = 32768;
constexpr uint32_t OFF_BARS = 229376;
constexpr uint32_t OFF_COLSUM = 229632;
constexpr uint32_t OFF_STATS = 230400;
constexpr uint32_t SMEM_BYTES = 232448;
constexpr uint32_t B_FULL = 0, B_EMPTY = 32, B_AUX = 64, B_SEL2 = 72, B_KVL = 80, B_FULL3 = 88, B_SW = 216, B_OUT = 224, B_LATE = 232, B_SEL = B_FULL + 8, B_FFN = 240;
__host__ __device__ constexpr uint32_t o3(int p) { return p * 8 + (p & 8) * 8; }
__host__ __device__ constexpr uint32_t bar3(int i) { return OFF_STATS + 1024 + (i >> 3) * 128 + ((i & 32) ? 0 : 64) + (i & 7) * 8; }
constexpr uint32_t SLOT_B = 16384;
constexpr uint32_t sb = 1024;
constexpr uint32_t bars = sb + OFF_BARS;
constexpr uint64_t WO_SLOTS = 0x6514736514736514ull;
constexpr uint32_t GU_SLOTS = 0xBA297308u, D_SLOTS = 0xD1C4;
constexpr uint32_t HST = 5 * SLOT_B;
constexpr uint32_t OFF_LNP = OFF_STATS;
constexpr uint32_t OFF_MSC = OFF_COLSUM + 512;
constexpr uint32_t OFF_KVB = 2 * SLOT_B + 8192;

struct Scratch {
  uint4 st1[64 * 48];
  uint4 csp[16 * 8 * 48];
  uint4 kvp[16 * 2304];
  uint4 obuf[32 * 64 * 128];
  uint4 st2[S_];
  uint32_t pred[S_];
  uint4 cst[8 * 32];
  uint4 hsel[64 * 128];
  uint32_t cand[8 * 32];
  uint4 ybuf[NCTA * NFFN * 4];
  unsigned epoch;
};
__device__ __align__(1024) Scratch G;
#define TS_DECL
#define TS(i)
#define TSG(i)
#define TSV(i, v)
#define TS_DUMP(slot)
#define PTS(i)

__device__ __forceinline__ uint32_t smem_u32(const void* p) { return (uint32_t)__cvta_generic_to_shared(p); }
__device__ __forceinline__ void mbar_init(uint32_t bar, uint32_t cnt) { asm volatile("mbarrier.init.shared::cta.b64 [%0], %1;" :: "r"(bar), "r"(cnt) : "memory"); }
__device__ __forceinline__ void mbar_expect_tx(uint32_t bar, uint32_t bytes) { asm volatile("mbarrier.arrive.expect_tx.shared::cta.b64 _, [%0], %1;" :: "r"(bar), "r"(bytes) : "memory"); }
__device__ __forceinline__ void mbar_arrive(uint32_t bar) { asm volatile("mbarrier.arrive.shared::cta.b64 _, [%0];" :: "r"(bar) : "memory"); }
#define SPINCHK(it, code) if ((it) > SPIN_LIMIT) break
__device__ __forceinline__ void mbar_wait(uint32_t bar, uint32_t parity) {
  asm volatile("{\n.reg .pred p;\n.reg .u32 c;\nmov.u32 c, 0;\n"
               "WL:\nmbarrier.try_wait.parity.shared::cta.b64 p, [%0], %1;\n@p bra WD;\n"
               "add.u32 c, c, 1;\nsetp.lt.u32 p, c, 1048576;\n@p bra WL;\nWD:\n}" :: "r"(bar), "r"(parity) : "memory");
}
__device__ __forceinline__ uint64_t l2_stream() { uint64_t p; asm("createpolicy.fractional.L2::evict_first.b64 %0, 1.0;" : "=l"(p)); return p; }
__device__ __forceinline__ void tma_2d(uint32_t dst, const CUtensorMap* tm, int c0, int c1, uint32_t bar, bool stream) {
  if (stream) asm volatile("cp.async.bulk.tensor.2d.shared::cluster.global.mbarrier::complete_tx::bytes.L2::cache_hint [%0], [%1, {%3, %4}], [%2], %5;"
                           :: "r"(dst), "l"(tm), "r"(bar), "r"(c0), "r"(c1), "l"(l2_stream()) : "memory");
  else asm volatile("cp.async.bulk.tensor.2d.shared::cluster.global.mbarrier::complete_tx::bytes [%0], [%1, {%3, %4}], [%2];"
                    :: "r"(dst), "l"(tm), "r"(bar), "r"(c0), "r"(c1) : "memory");
}
__device__ __forceinline__ void tma_3d(uint32_t dst, const CUtensorMap* tm, int c0, int c1, int c2, uint32_t bar, bool stream) {
  if (stream) asm volatile("cp.async.bulk.tensor.3d.shared::cluster.global.mbarrier::complete_tx::bytes.L2::cache_hint [%0], [%1, {%3, %4, %5}], [%2], %6;"
                           :: "r"(dst), "l"(tm), "r"(bar), "r"(c0), "r"(c1), "r"(c2), "l"(l2_stream()) : "memory");
  else asm volatile("cp.async.bulk.tensor.3d.shared::cluster.global.mbarrier::complete_tx::bytes [%0], [%1, {%3, %4, %5}], [%2];"
                    :: "r"(dst), "l"(tm), "r"(bar), "r"(c0), "r"(c1), "r"(c2) : "memory");
}
__device__ __forceinline__ void tma_2d_mc(uint32_t dst, const CUtensorMap* tm, int c0, int c1, uint32_t bar, bool stream) {
  if (stream) asm volatile("cp.async.bulk.tensor.2d.shared::cluster.global.mbarrier::complete_tx::bytes.multicast::cluster.L2::cache_hint [%0], [%1, {%3, %4}], [%2], %5, %6;"
                           :: "r"(dst), "l"(tm), "r"(bar), "r"(c0), "r"(c1), "h"((uint16_t)3), "l"(l2_stream()) : "memory");
  else asm volatile("cp.async.bulk.tensor.2d.shared::cluster.global.mbarrier::complete_tx::bytes.multicast::cluster [%0], [%1, {%3, %4}], [%2], %5;"
                    :: "r"(dst), "l"(tm), "r"(bar), "r"(c0), "r"(c1), "h"((uint16_t)3) : "memory");
}
__device__ __forceinline__ bool elect_one() {
  uint32_t p;
  asm volatile("{\n.reg .pred q;\nelect.sync _|q, 0xFFFFFFFF;\nselp.u32 %0, 1, 0, q;\n}" : "=r"(p));
  return p;
}
__device__ __forceinline__ void bulk_load_mc(uint32_t dst, const void* src, uint32_t bar, uint16_t mask) {
  if (EFO) asm volatile("cp.async.bulk.shared::cluster.global.mbarrier::complete_tx::bytes.multicast::cluster.L2::cache_hint [%0], [%1], 8192, [%2], %3, %4;"
               :: "r"(dst), "l"(src), "r"(bar), "h"(mask), "l"(l2_stream()) : "memory");
  else asm volatile("cp.async.bulk.shared::cluster.global.mbarrier::complete_tx::bytes.multicast::cluster [%0], [%1], 8192, [%2], %3;"
               :: "r"(dst), "l"(src), "r"(bar), "h"(mask) : "memory");
}
__device__ __forceinline__ void bulk_load(uint32_t dst, const void* src, uint32_t bytes, uint32_t bar) {
  asm volatile("cp.async.bulk.shared::cluster.global.mbarrier::complete_tx::bytes [%0], [%1], %2, [%3];" :: "r"(dst), "l"(src), "r"(bytes), "r"(bar) : "memory");
}
__device__ __forceinline__ void mbar_arrive_rem(uint32_t bar) { asm volatile("mbarrier.arrive.shared::cluster.b64 _, [%0];" :: "r"(bar) : "memory"); }
template <uint32_t O> __device__ __forceinline__ void ldsm4_o(uint32_t addr, uint32_t& a, uint32_t& b, uint32_t& c, uint32_t& d) {
  asm volatile("ldmatrix.sync.aligned.m8n8.x4.shared.b16 {%0,%1,%2,%3}, [%4+%5];" : "=r"(a), "=r"(b), "=r"(c), "=r"(d) : "r"(addr), "n"(O) : "memory");
}
template <uint32_t O> __device__ __forceinline__ void ldsm4t_o(uint32_t addr, uint32_t (&r)[4]) {
  asm volatile("ldmatrix.sync.aligned.m8n8.x4.trans.shared.b16 {%0,%1,%2,%3}, [%4+%5];" : "=r"(r[0]), "=r"(r[1]), "=r"(r[2]), "=r"(r[3]) : "r"(addr), "n"(O) : "memory");
}
__device__ __forceinline__ void mma16816(float (&c)[4], const uint32_t (&a)[4], uint32_t b0, uint32_t b1) {
  asm("mma.sync.aligned.m16n8k16.row.col.f32.bf16.bf16.f32 {%0,%1,%2,%3}, {%4,%5,%6,%7}, {%8,%9}, {%0,%1,%2,%3};"
      : "+f"(c[0]), "+f"(c[1]), "+f"(c[2]), "+f"(c[3]) : "r"(a[0]), "r"(a[1]), "r"(a[2]), "r"(a[3]), "r"(b0), "r"(b1));
}
__device__ __forceinline__ void l2_prefetch(const void* p) { asm volatile("prefetch.global.L2 [%0];" :: "l"(p) : "memory"); }
__device__ __forceinline__ uint32_t clk() { uint32_t t; asm volatile("mov.u32 %0, %%clock;" : "=r"(t) :: "memory"); return t; }
__device__ __forceinline__ void delay(uint32_t t0, uint32_t n) { while (clk() - t0 < n) {} }
template <int ID> __device__ __forceinline__ void cut(uint32_t zero) { asm volatile("{\n.reg .pred p;\nsetp.eq.u32 p, %0, %1;\nCUT:\n@p nanosleep.u32 1;\n@p bra.uni CUT;\n}" :: "r"(zero), "n"(ID) : "memory"); }
__device__ __forceinline__ void tmap_prefetch(const CUtensorMap* tm) { asm volatile("prefetch.tensormap [%0];" :: "l"(tm) : "memory"); }
__device__ __forceinline__ void wg_fence() { asm volatile("wgmma.fence.sync.aligned;" ::: "memory"); }
__device__ __forceinline__ void wg_commit() { asm volatile("wgmma.commit_group.sync.aligned;" ::: "memory"); }
template <int N> __device__ __forceinline__ void wg_wait() { asm volatile("wgmma.wait_group.sync.aligned %0;" :: "n"(N) : "memory"); }
template <int N> __device__ __forceinline__ void pin(float (&d)[N]) {
#pragma unroll
  for (int i = 0; i < N; i++) asm volatile("" : "+f"(d[i]) :: "memory");
}
__device__ __forceinline__ void pin4(uint4& v) { asm volatile("" : "+r"(v.x), "+r"(v.y), "+r"(v.z), "+r"(v.w) :: "memory"); }
template <uint32_t SBO, uint32_t SWZ> __device__ __forceinline__ uint64_t dsc(uint32_t lo) { return ((uint64_t)((SBO >> 4) | (SWZ << 30)) << 32) | lo; }
__host__ __device__ constexpr uint32_t dlo(uint32_t addr, uint32_t lbo) { return (addr >> 4) | ((lbo >> 4) << 16); }
__device__ __forceinline__ void bar_sync(int id, int n) { asm volatile("bar.sync %0, %1;" :: "r"(id), "r"(n) : "memory"); }
__device__ __forceinline__ void bar_arrive(int id, int n) { asm volatile("bar.arrive %0, %1;" :: "r"(id), "r"(n) : "memory"); }
__device__ __forceinline__ void fence_async_smem() { asm volatile("fence.proxy.async.shared::cta;" ::: "memory"); }
__device__ __forceinline__ void fence_gpu() { asm volatile("fence.acq_rel.gpu;" ::: "memory"); }
__device__ __forceinline__ uint4 ld_cg4(const void* p) { uint4 v; asm volatile("ld.global.cg.v4.u32 {%0,%1,%2,%3}, [%4];" : "=r"(v.x), "=r"(v.y), "=r"(v.z), "=r"(v.w) : "l"(p) : "memory"); return v; }
__device__ __forceinline__ uint4 ld_rlx4(const void* p) { uint4 v; asm volatile("ld.relaxed.gpu.global.v4.u32 {%0,%1,%2,%3}, [%4];" : "=r"(v.x), "=r"(v.y), "=r"(v.z), "=r"(v.w) : "l"(p) : "memory"); return v; }
__device__ __forceinline__ uint32_t ld_rlx(const void* p) { uint32_t v; asm volatile("ld.relaxed.gpu.global.u32 %0, [%1];" : "=r"(v) : "l"(p) : "memory"); return v; }
__device__ __forceinline__ void st_rlx4(void* p, uint4 v) { asm volatile("st.relaxed.gpu.global.v4.u32 [%0], {%1,%2,%3,%4};" :: "l"(p), "r"(v.x), "r"(v.y), "r"(v.z), "r"(v.w) : "memory"); }
__device__ __forceinline__ void st_rlx2(void* p, uint32_t a, uint32_t b) { asm volatile("st.relaxed.gpu.global.v2.u32 [%0], {%1,%2};" :: "l"(p), "r"(a), "r"(b) : "memory"); }
__device__ __forceinline__ void st_rlx(void* p, uint32_t a) { asm volatile("st.relaxed.gpu.global.u32 [%0], %1;" :: "l"(p), "r"(a) : "memory"); }
__device__ __forceinline__ void red4(bool on, void* p, float a, float b, float c, float d) {
  asm volatile("{\n.reg .pred q;\nsetp.ne.b32 q, %5, 0;\n@q red.relaxed.gpu.global.add.v4.f32 [%0], {%1,%2,%3,%4};\n}" :: "l"(p), "f"(a), "f"(b), "f"(c), "f"(d), "r"((int)on) : "memory");
}
__device__ __forceinline__ uint32_t pack2(float lo, float hi) { uint32_t r; asm("cvt.rn.bf16x2.f32 %0, %1, %2;" : "=r"(r) : "f"(hi), "f"(lo)); return r; }
__device__ __forceinline__ float bf_lo(uint32_t v) { return __uint_as_float(v << 16); }
__device__ __forceinline__ float bf_hi(uint32_t v) { return __uint_as_float(v & 0xFFFF0000u); }
__device__ __forceinline__ void stsm4(uint32_t addr, uint32_t a, uint32_t b, uint32_t c, uint32_t d) {
  asm volatile("stmatrix.sync.aligned.m8n8.x4.shared.b16 [%0], {%1,%2,%3,%4};" :: "r"(addr), "r"(a), "r"(b), "r"(c), "r"(d) : "memory");
}
template <uint32_t O> __device__ __forceinline__ void stsm4_o(uint32_t addr, uint32_t a, uint32_t b, uint32_t c, uint32_t d) {
  asm volatile("stmatrix.sync.aligned.m8n8.x4.shared.b16 [%0+%5], {%1,%2,%3,%4};" :: "r"(addr), "r"(a), "r"(b), "r"(c), "r"(d), "n"(O) : "memory");
}
__device__ __forceinline__ void sts4(uint32_t addr, uint32_t a, uint32_t b, uint32_t c, uint32_t d) { asm volatile("st.shared.v4.u32 [%0], {%1,%2,%3,%4};" :: "r"(addr), "r"(a), "r"(b), "r"(c), "r"(d) : "memory"); }
__device__ __forceinline__ void sts2f(uint32_t addr, float a, float b) { asm volatile("st.shared.v2.f32 [%0], {%1,%2};" :: "r"(addr), "f"(a), "f"(b) : "memory"); }
__device__ __forceinline__ void sts1(uint32_t addr, uint32_t a) { asm volatile("st.shared.u32 [%0], %1;" :: "r"(addr), "r"(a) : "memory"); }
__device__ __forceinline__ float2 lds2f(uint32_t addr) { float2 v; asm volatile("ld.shared.v2.f32 {%0,%1}, [%2];" : "=f"(v.x), "=f"(v.y) : "r"(addr) : "memory"); return v; }
template <uint32_t O> __device__ __forceinline__ float2 lds2f_o(uint32_t addr) { float2 v; asm volatile("ld.shared.v2.f32 {%0,%1}, [%2+%3];" : "=f"(v.x), "=f"(v.y) : "r"(addr), "n"(O) : "memory"); return v; }
template <int I, int N, class F> __device__ __forceinline__ void static_for(F&& f) { if constexpr (I < N) { f(std::integral_constant<int, I>{}); static_for<I + 1, N>(f); } }
__device__ __forceinline__ uint4 lds4(uint32_t addr) { uint4 v; asm volatile("ld.shared.v4.u32 {%0,%1,%2,%3}, [%4];" : "=r"(v.x), "=r"(v.y), "=r"(v.z), "=r"(v.w) : "r"(addr) : "memory"); return v; }
__device__ __forceinline__ uint32_t lds1(uint32_t addr) { uint32_t v; asm volatile("ld.shared.u32 %0, [%1];" : "=r"(v) : "r"(addr) : "memory"); return v; }
__device__ __forceinline__ float ex2(float x) { float y; asm("ex2.approx.ftz.f32 %0, %1;" : "=f"(y) : "f"(x)); return y; }
__device__ __forceinline__ uint32_t max4(uint32_t m, const uint4& v) { return __vimax3_u32(__vimax3_u32(m, v.x, v.y), v.z, v.w); }
__device__ __forceinline__ float rsq(float x) { float y; asm("rsqrt.approx.ftz.f32 %0, %1;" : "=f"(y) : "f"(x)); return y; }
__device__ __forceinline__ float rcp(float x) { float y; asm("rcp.approx.ftz.f32 %0, %1;" : "=f"(y) : "f"(x)); return y; }
__device__ __forceinline__ uint2 ld_rlx2(const void* p) { uint2 v; asm volatile("ld.relaxed.gpu.global.v2.u32 {%0,%1}, [%2];" : "=r"(v.x), "=r"(v.y) : "l"(p) : "memory"); return v; }
template <uint32_t O> __device__ __forceinline__ uint4 lds4_o(uint32_t addr) { uint4 v; asm volatile("ld.shared.v4.u32 {%0,%1,%2,%3}, [%4+%5];" : "=r"(v.x), "=r"(v.y), "=r"(v.z), "=r"(v.w) : "r"(addr), "n"(O) : "memory"); return v; }
__device__ __forceinline__ uint32_t hadd2(uint32_t a, uint32_t b) { uint32_t r; asm("add.rn.bf16x2 %0, %1, %2;" : "=r"(r) : "r"(a), "r"(b)); return r; }
__device__ __forceinline__ uint4 hadd8(const uint4& a, const uint4& b) { return make_uint4(hadd2(a.x, b.x), hadd2(a.y, b.y), hadd2(a.z, b.z), hadd2(a.w, b.w)); }
__device__ __forceinline__ bool hnan(uint32_t a) { return (a & 0x7FFF0000u) > 0x7F800000u; }
__device__ __forceinline__ uint32_t hfma2(uint32_t a, uint32_t b, uint32_t c) { uint32_t r; asm("fma.rn.bf16x2 %0, %1, %2, %3;" : "=r"(r) : "r"(a), "r"(b), "r"(c)); return r; }
__device__ __forceinline__ uint32_t ordered(float v) { const uint32_t u = __float_as_uint(v); return u ^ ((uint32_t)((int)u >> 31) | 0x80000000u); }
__device__ __forceinline__ uint32_t route(const uint4& v, float sw, int row, float2& pr) {
  const float mean = __uint_as_float(v.x) * (1.f / D_);
  pr.x = rsq(fmaxf(fmaf(-mean, mean, __uint_as_float(v.y) * (1.f / D_)), 0.f) + 1e-5f);
  pr.y = -mean * pr.x;
  return min(ordered(pr.x * fmaf(-mean, sw, __uint_as_float(v.z))) & ~2047u, 0xFFFFF000u) | (2047 - row);
}
__device__ __forceinline__ uint2 top2(uint32_t a, uint32_t b, uint32_t c, uint32_t d) {
  const uint32_t h0 = max(a, b), h1 = max(c, d), h = max(h0, h1), l = __vimax3_u32(min(h0, h1), min(a, b), min(c, d));
  const uint32_t m1 = __reduce_max_sync(~0u, h);
  return make_uint2(m1, __reduce_max_sync(~0u, h == m1 ? l : h));
}
__device__ __forceinline__ uint32_t hmul2(uint32_t a, uint32_t b) { uint32_t r; asm("mul.rn.bf16x2 %0, %1, %2;" : "=r"(r) : "r"(a), "r"(b)); return r; }
__device__ __forceinline__ uint32_t phi2(float u0, float u1, uint32_t r2, float rl) {
  uint32_t p, r;
  asm("cvt.rn.relu.bf16x2.f32 %0, %1, %2;" : "=r"(p) : "f"(u1), "f"(u0));
  asm("fma.rn.bf16x2 %0, %1, %2, %3;" : "=r"(r) : "r"(p), "r"(r2), "r"(pack2(__saturatef(ex2(u0 * rl) + 1e-6f), __saturatef(ex2(u1 * rl) + 1e-6f))));
  return r;
}

template<int TA, int TB, int OFF, int SZ> __device__ __forceinline__ void wgmma_n192_ss(float (&d)[SZ], uint64_t da, uint64_t db, int scale_d) {
  asm volatile("{\n.reg .pred p;\nsetp.ne.b32 p, %98, 0;\n"
    "wgmma.mma_async.sync.aligned.m64n192k16.f32.bf16.bf16 {%0,%1,%2,%3,%4,%5,%6,%7,%8,%9,%10,%11,%12,%13,%14,%15,%16,%17,%18,%19,%20,%21,%22,%23,%24,%25,%26,%27,%28,%29,%30,%31,%32,%33,%34,%35,%36,%37,%38,%39,%40,%41,%42,%43,%44,%45,%46,%47,%48,%49,%50,%51,%52,%53,%54,%55,%56,%57,%58,%59,%60,%61,%62,%63,%64,%65,%66,%67,%68,%69,%70,%71,%72,%73,%74,%75,%76,%77,%78,%79,%80,%81,%82,%83,%84,%85,%86,%87,%88,%89,%90,%91,%92,%93,%94,%95}, %96, %97, p, 1, 1, %99, %100;\n}\n"
    : "+f"(d[OFF+0]), "+f"(d[OFF+1]), "+f"(d[OFF+2]), "+f"(d[OFF+3]), "+f"(d[OFF+4]), "+f"(d[OFF+5]), "+f"(d[OFF+6]), "+f"(d[OFF+7]),
      "+f"(d[OFF+8]), "+f"(d[OFF+9]), "+f"(d[OFF+10]), "+f"(d[OFF+11]), "+f"(d[OFF+12]), "+f"(d[OFF+13]), "+f"(d[OFF+14]), "+f"(d[OFF+15]),
      "+f"(d[OFF+16]), "+f"(d[OFF+17]), "+f"(d[OFF+18]), "+f"(d[OFF+19]), "+f"(d[OFF+20]), "+f"(d[OFF+21]), "+f"(d[OFF+22]), "+f"(d[OFF+23]),
      "+f"(d[OFF+24]), "+f"(d[OFF+25]), "+f"(d[OFF+26]), "+f"(d[OFF+27]), "+f"(d[OFF+28]), "+f"(d[OFF+29]), "+f"(d[OFF+30]), "+f"(d[OFF+31]),
      "+f"(d[OFF+32]), "+f"(d[OFF+33]), "+f"(d[OFF+34]), "+f"(d[OFF+35]), "+f"(d[OFF+36]), "+f"(d[OFF+37]), "+f"(d[OFF+38]), "+f"(d[OFF+39]),
      "+f"(d[OFF+40]), "+f"(d[OFF+41]), "+f"(d[OFF+42]), "+f"(d[OFF+43]), "+f"(d[OFF+44]), "+f"(d[OFF+45]), "+f"(d[OFF+46]), "+f"(d[OFF+47]),
      "+f"(d[OFF+48]), "+f"(d[OFF+49]), "+f"(d[OFF+50]), "+f"(d[OFF+51]), "+f"(d[OFF+52]), "+f"(d[OFF+53]), "+f"(d[OFF+54]), "+f"(d[OFF+55]),
      "+f"(d[OFF+56]), "+f"(d[OFF+57]), "+f"(d[OFF+58]), "+f"(d[OFF+59]), "+f"(d[OFF+60]), "+f"(d[OFF+61]), "+f"(d[OFF+62]), "+f"(d[OFF+63]),
      "+f"(d[OFF+64]), "+f"(d[OFF+65]), "+f"(d[OFF+66]), "+f"(d[OFF+67]), "+f"(d[OFF+68]), "+f"(d[OFF+69]), "+f"(d[OFF+70]), "+f"(d[OFF+71]),
      "+f"(d[OFF+72]), "+f"(d[OFF+73]), "+f"(d[OFF+74]), "+f"(d[OFF+75]), "+f"(d[OFF+76]), "+f"(d[OFF+77]), "+f"(d[OFF+78]), "+f"(d[OFF+79]),
      "+f"(d[OFF+80]), "+f"(d[OFF+81]), "+f"(d[OFF+82]), "+f"(d[OFF+83]), "+f"(d[OFF+84]), "+f"(d[OFF+85]), "+f"(d[OFF+86]), "+f"(d[OFF+87]),
      "+f"(d[OFF+88]), "+f"(d[OFF+89]), "+f"(d[OFF+90]), "+f"(d[OFF+91]), "+f"(d[OFF+92]), "+f"(d[OFF+93]), "+f"(d[OFF+94]), "+f"(d[OFF+95])
    : "l"(da), "l"(db), "r"(scale_d), "n"(TA), "n"(TB));
}
template<int TA, int TB, int OFF, int SZ> __device__ __forceinline__ void wgmma_n128_ss(float (&d)[SZ], uint64_t da, uint64_t db, int scale_d) {
  asm volatile("{\n.reg .pred p;\nsetp.ne.b32 p, %66, 0;\n"
    "wgmma.mma_async.sync.aligned.m64n128k16.f32.bf16.bf16 {%0,%1,%2,%3,%4,%5,%6,%7,%8,%9,%10,%11,%12,%13,%14,%15,%16,%17,%18,%19,%20,%21,%22,%23,%24,%25,%26,%27,%28,%29,%30,%31,%32,%33,%34,%35,%36,%37,%38,%39,%40,%41,%42,%43,%44,%45,%46,%47,%48,%49,%50,%51,%52,%53,%54,%55,%56,%57,%58,%59,%60,%61,%62,%63}, %64, %65, p, 1, 1, %67, %68;\n}\n"
    : "+f"(d[OFF+0]), "+f"(d[OFF+1]), "+f"(d[OFF+2]), "+f"(d[OFF+3]), "+f"(d[OFF+4]), "+f"(d[OFF+5]), "+f"(d[OFF+6]), "+f"(d[OFF+7]),
      "+f"(d[OFF+8]), "+f"(d[OFF+9]), "+f"(d[OFF+10]), "+f"(d[OFF+11]), "+f"(d[OFF+12]), "+f"(d[OFF+13]), "+f"(d[OFF+14]), "+f"(d[OFF+15]),
      "+f"(d[OFF+16]), "+f"(d[OFF+17]), "+f"(d[OFF+18]), "+f"(d[OFF+19]), "+f"(d[OFF+20]), "+f"(d[OFF+21]), "+f"(d[OFF+22]), "+f"(d[OFF+23]),
      "+f"(d[OFF+24]), "+f"(d[OFF+25]), "+f"(d[OFF+26]), "+f"(d[OFF+27]), "+f"(d[OFF+28]), "+f"(d[OFF+29]), "+f"(d[OFF+30]), "+f"(d[OFF+31]),
      "+f"(d[OFF+32]), "+f"(d[OFF+33]), "+f"(d[OFF+34]), "+f"(d[OFF+35]), "+f"(d[OFF+36]), "+f"(d[OFF+37]), "+f"(d[OFF+38]), "+f"(d[OFF+39]),
      "+f"(d[OFF+40]), "+f"(d[OFF+41]), "+f"(d[OFF+42]), "+f"(d[OFF+43]), "+f"(d[OFF+44]), "+f"(d[OFF+45]), "+f"(d[OFF+46]), "+f"(d[OFF+47]),
      "+f"(d[OFF+48]), "+f"(d[OFF+49]), "+f"(d[OFF+50]), "+f"(d[OFF+51]), "+f"(d[OFF+52]), "+f"(d[OFF+53]), "+f"(d[OFF+54]), "+f"(d[OFF+55]),
      "+f"(d[OFF+56]), "+f"(d[OFF+57]), "+f"(d[OFF+58]), "+f"(d[OFF+59]), "+f"(d[OFF+60]), "+f"(d[OFF+61]), "+f"(d[OFF+62]), "+f"(d[OFF+63])
    : "l"(da), "l"(db), "r"(scale_d), "n"(TA), "n"(TB));
}
template<int TA, int TB, int OFF, int SZ> __device__ __forceinline__ void wgmma_n64_ss(float (&d)[SZ], uint64_t da, uint64_t db, int scale_d) {
  asm volatile("{\n.reg .pred p;\nsetp.ne.b32 p, %34, 0;\n"
    "wgmma.mma_async.sync.aligned.m64n64k16.f32.bf16.bf16 {%0,%1,%2,%3,%4,%5,%6,%7,%8,%9,%10,%11,%12,%13,%14,%15,%16,%17,%18,%19,%20,%21,%22,%23,%24,%25,%26,%27,%28,%29,%30,%31}, %32, %33, p, 1, 1, %35, %36;\n}\n"
    : "+f"(d[OFF+0]), "+f"(d[OFF+1]), "+f"(d[OFF+2]), "+f"(d[OFF+3]), "+f"(d[OFF+4]), "+f"(d[OFF+5]), "+f"(d[OFF+6]), "+f"(d[OFF+7]),
      "+f"(d[OFF+8]), "+f"(d[OFF+9]), "+f"(d[OFF+10]), "+f"(d[OFF+11]), "+f"(d[OFF+12]), "+f"(d[OFF+13]), "+f"(d[OFF+14]), "+f"(d[OFF+15]),
      "+f"(d[OFF+16]), "+f"(d[OFF+17]), "+f"(d[OFF+18]), "+f"(d[OFF+19]), "+f"(d[OFF+20]), "+f"(d[OFF+21]), "+f"(d[OFF+22]), "+f"(d[OFF+23]),
      "+f"(d[OFF+24]), "+f"(d[OFF+25]), "+f"(d[OFF+26]), "+f"(d[OFF+27]), "+f"(d[OFF+28]), "+f"(d[OFF+29]), "+f"(d[OFF+30]), "+f"(d[OFF+31])
    : "l"(da), "l"(db), "r"(scale_d), "n"(TA), "n"(TB));
}
template<int TB, int OFF, int SZ> __device__ __forceinline__ void wgmma_n64_rs(float (&d)[SZ], uint32_t a0, uint32_t a1, uint32_t a2, uint32_t a3, uint64_t db, int scale_d) {
  asm volatile("{\n.reg .pred p;\nsetp.ne.b32 p, %37, 0;\n"
    "wgmma.mma_async.sync.aligned.m64n64k16.f32.bf16.bf16 {%0,%1,%2,%3,%4,%5,%6,%7,%8,%9,%10,%11,%12,%13,%14,%15,%16,%17,%18,%19,%20,%21,%22,%23,%24,%25,%26,%27,%28,%29,%30,%31}, {%32,%33,%34,%35}, %36, p, 1, 1, %38;\n}\n"
    : "+f"(d[OFF+0]), "+f"(d[OFF+1]), "+f"(d[OFF+2]), "+f"(d[OFF+3]), "+f"(d[OFF+4]), "+f"(d[OFF+5]), "+f"(d[OFF+6]), "+f"(d[OFF+7]),
      "+f"(d[OFF+8]), "+f"(d[OFF+9]), "+f"(d[OFF+10]), "+f"(d[OFF+11]), "+f"(d[OFF+12]), "+f"(d[OFF+13]), "+f"(d[OFF+14]), "+f"(d[OFF+15]),
      "+f"(d[OFF+16]), "+f"(d[OFF+17]), "+f"(d[OFF+18]), "+f"(d[OFF+19]), "+f"(d[OFF+20]), "+f"(d[OFF+21]), "+f"(d[OFF+22]), "+f"(d[OFF+23]),
      "+f"(d[OFF+24]), "+f"(d[OFF+25]), "+f"(d[OFF+26]), "+f"(d[OFF+27]), "+f"(d[OFF+28]), "+f"(d[OFF+29]), "+f"(d[OFF+30]), "+f"(d[OFF+31])
    : "r"(a0), "r"(a1), "r"(a2), "r"(a3), "l"(db), "r"(scale_d), "n"(TB));
}
template<int TA, int TB, int OFF, int SZ> __device__ __forceinline__ void wgmma_n72_ss(float (&d)[SZ], uint64_t da, uint64_t db, int scale_d) {
  asm volatile("{\n.reg .pred p;\nsetp.ne.b32 p, %38, 0;\n"
    "wgmma.mma_async.sync.aligned.m64n72k16.f32.bf16.bf16 {%0,%1,%2,%3,%4,%5,%6,%7,%8,%9,%10,%11,%12,%13,%14,%15,%16,%17,%18,%19,%20,%21,%22,%23,%24,%25,%26,%27,%28,%29,%30,%31,%32,%33,%34,%35}, %36, %37, p, 1, 1, %39, %40;\n}\n"
    : "+f"(d[OFF+0]), "+f"(d[OFF+1]), "+f"(d[OFF+2]), "+f"(d[OFF+3]), "+f"(d[OFF+4]), "+f"(d[OFF+5]), "+f"(d[OFF+6]), "+f"(d[OFF+7]),
      "+f"(d[OFF+8]), "+f"(d[OFF+9]), "+f"(d[OFF+10]), "+f"(d[OFF+11]), "+f"(d[OFF+12]), "+f"(d[OFF+13]), "+f"(d[OFF+14]), "+f"(d[OFF+15]),
      "+f"(d[OFF+16]), "+f"(d[OFF+17]), "+f"(d[OFF+18]), "+f"(d[OFF+19]), "+f"(d[OFF+20]), "+f"(d[OFF+21]), "+f"(d[OFF+22]), "+f"(d[OFF+23]),
      "+f"(d[OFF+24]), "+f"(d[OFF+25]), "+f"(d[OFF+26]), "+f"(d[OFF+27]), "+f"(d[OFF+28]), "+f"(d[OFF+29]), "+f"(d[OFF+30]), "+f"(d[OFF+31]),
      "+f"(d[OFF+32]), "+f"(d[OFF+33]), "+f"(d[OFF+34]), "+f"(d[OFF+35])
    : "l"(da), "l"(db), "r"(scale_d), "n"(TA), "n"(TB));
}
template<int TB, int OFF, int SZ> __device__ __forceinline__ void wgmma_n40_rs(float (&d)[SZ], uint32_t a0, uint32_t a1, uint32_t a2, uint32_t a3, uint64_t db, int scale_d) {
  asm volatile("{\n.reg .pred p;\nsetp.ne.b32 p, %25, 0;\n"
    "wgmma.mma_async.sync.aligned.m64n40k16.f32.bf16.bf16 {%0,%1,%2,%3,%4,%5,%6,%7,%8,%9,%10,%11,%12,%13,%14,%15,%16,%17,%18,%19}, {%20,%21,%22,%23}, %24, p, 1, 1, %26;\n}\n"
    : "+f"(d[OFF+0]), "+f"(d[OFF+1]), "+f"(d[OFF+2]), "+f"(d[OFF+3]), "+f"(d[OFF+4]), "+f"(d[OFF+5]), "+f"(d[OFF+6]), "+f"(d[OFF+7]),
      "+f"(d[OFF+8]), "+f"(d[OFF+9]), "+f"(d[OFF+10]), "+f"(d[OFF+11]), "+f"(d[OFF+12]), "+f"(d[OFF+13]), "+f"(d[OFF+14]), "+f"(d[OFF+15]),
      "+f"(d[OFF+16]), "+f"(d[OFF+17]), "+f"(d[OFF+18]), "+f"(d[OFF+19])
    : "r"(a0), "r"(a1), "r"(a2), "r"(a3), "l"(db), "r"(scale_d), "n"(TB));
}
template<int TB, int OFF, int SZ> __device__ __forceinline__ void wgmma_n128_rs(float (&d)[SZ], uint32_t a0, uint32_t a1, uint32_t a2, uint32_t a3, uint64_t db, int scale_d) {
  asm volatile("{\n.reg .pred p;\nsetp.ne.b32 p, %69, 0;\n"
    "wgmma.mma_async.sync.aligned.m64n128k16.f32.bf16.bf16 {%0,%1,%2,%3,%4,%5,%6,%7,%8,%9,%10,%11,%12,%13,%14,%15,%16,%17,%18,%19,%20,%21,%22,%23,%24,%25,%26,%27,%28,%29,%30,%31,%32,%33,%34,%35,%36,%37,%38,%39,%40,%41,%42,%43,%44,%45,%46,%47,%48,%49,%50,%51,%52,%53,%54,%55,%56,%57,%58,%59,%60,%61,%62,%63}, {%64,%65,%66,%67}, %68, p, 1, 1, %70;\n}\n"
    : "+f"(d[OFF+0]), "+f"(d[OFF+1]), "+f"(d[OFF+2]), "+f"(d[OFF+3]), "+f"(d[OFF+4]), "+f"(d[OFF+5]), "+f"(d[OFF+6]), "+f"(d[OFF+7]),
      "+f"(d[OFF+8]), "+f"(d[OFF+9]), "+f"(d[OFF+10]), "+f"(d[OFF+11]), "+f"(d[OFF+12]), "+f"(d[OFF+13]), "+f"(d[OFF+14]), "+f"(d[OFF+15]),
      "+f"(d[OFF+16]), "+f"(d[OFF+17]), "+f"(d[OFF+18]), "+f"(d[OFF+19]), "+f"(d[OFF+20]), "+f"(d[OFF+21]), "+f"(d[OFF+22]), "+f"(d[OFF+23]),
      "+f"(d[OFF+24]), "+f"(d[OFF+25]), "+f"(d[OFF+26]), "+f"(d[OFF+27]), "+f"(d[OFF+28]), "+f"(d[OFF+29]), "+f"(d[OFF+30]), "+f"(d[OFF+31]),
      "+f"(d[OFF+32]), "+f"(d[OFF+33]), "+f"(d[OFF+34]), "+f"(d[OFF+35]), "+f"(d[OFF+36]), "+f"(d[OFF+37]), "+f"(d[OFF+38]), "+f"(d[OFF+39]),
      "+f"(d[OFF+40]), "+f"(d[OFF+41]), "+f"(d[OFF+42]), "+f"(d[OFF+43]), "+f"(d[OFF+44]), "+f"(d[OFF+45]), "+f"(d[OFF+46]), "+f"(d[OFF+47]),
      "+f"(d[OFF+48]), "+f"(d[OFF+49]), "+f"(d[OFF+50]), "+f"(d[OFF+51]), "+f"(d[OFF+52]), "+f"(d[OFF+53]), "+f"(d[OFF+54]), "+f"(d[OFF+55]),
      "+f"(d[OFF+56]), "+f"(d[OFF+57]), "+f"(d[OFF+58]), "+f"(d[OFF+59]), "+f"(d[OFF+60]), "+f"(d[OFF+61]), "+f"(d[OFF+62]), "+f"(d[OFF+63])
    : "r"(a0), "r"(a1), "r"(a2), "r"(a3), "l"(db), "r"(scale_d), "n"(TB));
}

struct Ptrs { const __nv_bfloat16 *x, *wqkv, *wo, *wr, *wg, *wu, *wd; __nv_bfloat16* out; };

__global__ void __cluster_dims__(2, 1, 1) __launch_bounds__(384, 1) fused_kernel(const __grid_constant__ CUtensorMap tmX, const __grid_constant__ CUtensorMap tmW,
                                                       const __grid_constant__ CUtensorMap tmO, const __grid_constant__ CUtensorMap tmG,
                                                       const __grid_constant__ CUtensorMap tmU, const __grid_constant__ CUtensorMap tmD,
                                                       const __grid_constant__ CUtensorMap tmM, const __grid_constant__ CUtensorMap tmPG,
                                                       const __grid_constant__ CUtensorMap tmPU, const __grid_constant__ CUtensorMap tmPD,
                                                       const Ptrs P) {
  extern __shared__ __align__(1024) uint8_t smem_raw[];
  if (TMPF && threadIdx.x == 0) { tmap_prefetch(&tmX); tmap_prefetch(&tmW); }
  const int tid = threadIdx.x, wid = __shfl_sync(~0u, tid >> 5, 0), wg = __shfl_sync(~0u, tid >> 7, 0), lane = tid & 31;
  const int pj = blockIdx.x >> 1, pi = pj - 36;
  const int b = (pj < 4 ? 32 + pj * 8 : pj < 36 ? pj - 4 : 33 + pi + ((pi * 37) >> 8)) * 2 + (blockIdx.x & 1);
  const int rb = b >> 4, cg = b & 15, hf = cg >> 3, c3 = cg & 7;
  const int jp = cg >> 1;
  const int fidx = jp == rb ? -1 : b - 2 * rb - (jp > rb ? 2 : 0);
  const uint32_t rank = b & 1, own = rank << 24;
  const uint32_t zero = gridDim.y - 1;
  const uint32_t sm = own + sb, mb = own + bars;
  auto chunk_of = [&](int p) { return (int)((0x1765432FEDCBA980ull >> (4 * p)) & 15) ^ (p == 0 || p == 15 ? cg : p < 9 ? cg & 8 : cg & 14); };
  const int kl = (jp & 3) * 256;
  auto k_of = [&](int kb) { return kb >= 12 ? kl + (kb - 12) * 64 : kb * 64 < kl ? kb * 64 : kb * 64 + 256; };
  auto load_w = [&](int kb) {
#pragma unroll
    for (int i = 0; i < 3; i++) tma_2d(sm + woff(kb & 3) + i * WSTR, &tmW, i * D_ + cg * 64, k_of(kb), mb + B_FULL + 8 * (kb & 3), EFW);
  };
  TS_DECL; TS(0); TSG(30);
  if (wid == 8) {
    if (elect_one()) {
      if (smem_u32(smem_raw) != sm) {
#pragma unroll
        for (int i = 0; i < PERT; i++) sts1(mb, lds1(mb));
        asm volatile("trap;");
      }
#pragma unroll
      for (int s = 0; s < 4; s++) mbar_init(mb + B_FULL + 8 * s, 1);
      asm volatile("fence.mbarrier_init.release.cluster;" ::: "memory");
      if (INIF) fence_async_smem();
    }
  } else if (wid == 9) {
    if (elect_one()) {
#pragma unroll
      for (int i = 4; i < 32; i++)
        if (i != 27) mbar_init(mb + 8 * i, i < 8 ? 8 : i == 8 ? 64 : i == 26 ? 2 : i == 29 ? 4 : 1);
      asm volatile("fence.mbarrier_init.release.cluster;" ::: "memory");
      if (INIF) fence_async_smem();
    }
  }
  __syncwarp();
  asm volatile("barrier.cluster.arrive.relaxed.aligned;" ::: "memory");
  if (wid == 8) {
    if (elect_one()) {
      mbar_expect_tx(mb + B_FULL, STAGE_B);
      tma_2d(sm + xoff(0, 0), &tmX, k_of(0), rb * 256, mb + B_FULL, EFX);
      tma_2d(sm + xoff(0, 1), &tmX, k_of(0), rb * 256 + 128, mb + B_FULL, EFX);
      load_w(0);
    }
    __syncwarp();
  }
  asm volatile("barrier.cluster.wait.aligned;" ::: "memory");

  if (wg == 2) {
    asm volatile("setmaxnreg.dec.sync.aligned.u32 56;");
    auto wait3 = [&](int i) { mbar_wait(sm + bar3(i), 0); };
    if (wid == 8) {
      if (elect_one()) {
        int np = fidx >= 0 ? 0 : 32;
        if (fidx >= 0) mbar_expect_tx(mb + B_FFN, 32 * 512);
#pragma unroll 1
        for (int kb = 1; kb < 16; kb++) {
          const uint32_t fb = mb + B_FULL + 8 * (kb & 3);
          mbar_wait(fb + B_EMPTY, ((kb >> 2) & 1) ^ 1);
          mbar_expect_tx(fb, STAGE_B);
          tma_2d_mc(sm + xoff(kb & 3, rank), &tmX, k_of(kb), rb * 256 + rank * 128, fb, EFX);
          load_w(kb);
          if (kb >= 12) asm volatile("mbarrier.arrive.shared::cta.b64 _, [%0], 7;" :: "r"(fb + B_EMPTY) : "memory");
#pragma unroll 1
          for (int n = ((NPK << 16) >> (4 * kb)) & 15; n > 0 && np < 32; n--, np++)
            tma_2d(sm + OFF_STATS + 512, (np & 1) ? &tmPU : &tmPG, (fidx >> 1) * 64, (np >> 1) * 64 + rank * 32, mb + B_FFN, false);
        }
        if (fidx >= 0) { mbar_wait(mb + B_FFN, 0); mbar_expect_tx(mb + B_FFN, 65536 + NPD * 512); mbar_expect_tx(mb + B_FFN + 8, 65536); }
#pragma unroll
        for (int p = 4; p < 8; p++) sts4(sm + OFF_STATS + p * 144, 0x3F803F80u, 0x3F803F80u, 0x3F803F80u, 0x3F803F80u);
        fence_async_smem();
        mbar_arrive(mb + B_LATE);
        PTS(2);
        mbar_expect_tx(mb + B_KVL, 36864);
        mbar_wait(mb + B_LATE, 0);
        wait3(60);
        delay(clk(), KDELAY);
        bulk_load(sm + 11 * SLOT_B, &G.kvp[cg * 2304], SLOT_B, mb + B_KVL);
        bulk_load(sm + 13 * SLOT_B, &G.kvp[cg * 2304 + 1024], SLOT_B, mb + B_KVL);
        bulk_load(sm + 2 * SLOT_B, &G.kvp[cg * 2304 + 2048], 4096, mb + B_KVL);
        PTS(3);
        const uint4* src = &G.obuf[(rb * 4 + rank * 2 + hf) * 64 * 128];
        wait3(48);
        const uint32_t t1 = clk();
#pragma unroll
        for (int p = 1; p < 5; p++) {
          delay(t1, ADELAY + (p - 1) * ASTEP);
          bulk_load_mc(sm + (10 + (p & 3)) * SLOT_B + rank * 8192, src + ((hf ^ 1) * 8 + p - 1) * 512, sm + bar3(p) + rank * 256, 3);
        }
        PTS(7);
#pragma unroll 1
        for (int i = 5; i < 17; i++) {
          const int p = min(i, 15);
          const uint32_t d = sm + (10 + (p & 3)) * SLOT_B + rank * 8192, fb = sm + bar3(0) + o3(p) + rank * 256;
          const uint4* q = src + chunk_of(i & 15) * 512;
          mbar_wait(sm + bar3(48) + o3(p - 4 + ((LATEP >> p) & 1)), 0);
          bulk_load_mc(d, q, fb, i < 15 ? 3 : 1 << ((i ^ rank ^ 1) & 1));
        }
        PTS(15);
      }
    } else {
      const int r4 = lane >> 3, c8 = lane & 7;
      const uint32_t eb = (lane << 24) + bars + B_EMPTY;
      auto tagged = [](float v, uint32_t tag) { return ((__float_as_uint(v) + 128) & ~255u) | tag; };
      auto gather = [&](uint32_t tag) {
        const int q = (wid - 9) * 24 + lane;
        const uint4* cp = lane < 24 ? &G.csp[cg * 8 * 48 + q] : &G.st1[rb * 8 * 48 + (wid - 9) * 8 + lane - 24];
        uint4 v[8];
        delay(clk(), GDELAY);
#pragma unroll 1
        for (int it = 0;; it++) {
#pragma unroll
          for (int i = 0; i < 8; i++) v[i] = ld_rlx4(cp + i * 48);
          uint32_t x = 0;
#pragma unroll
          for (int i = 0; i < 8; i++) { v[i].x ^= tag; v[i].y ^= tag; v[i].z ^= tag; v[i].w ^= tag; x |= v[i].x | v[i].y | v[i].z | v[i].w; }
          if (!__any_sync(~0u, (x & 255) != 0)) break;
          SPINCHK(it, 3);
        }
        float c[4] = {0.f, 0.f, 0.f, 0.f};
#pragma unroll
        for (int i = 0; i < 8; i++) { c[0] += __uint_as_float(v[i].x); c[1] += __uint_as_float(v[i].y); c[2] += __uint_as_float(v[i].z); c[3] += __uint_as_float(v[i].w); }
        const uint32_t h0 = pack2(c[0], c[1]), h1 = pack2(c[2], c[3]), ca = sm + OFF_COLSUM + (q >> 1) * 32 + (q & 1) * 8;
        if (lane < 24) {
          sts2f(ca, __uint_as_float(h0), __uint_as_float(h1));
          sts2f(ca + 16, __uint_as_float(pack2(c[0] - bf_lo(h0), c[1] - bf_hi(h0))), __uint_as_float(pack2(c[2] - bf_lo(h1), c[3] - bf_hi(h1))));
        }
        fence_async_smem();
        mbar_arrive(mb + B_AUX);
      };
      const int r2 = lane >> 4, c16 = lane & 15;
      float a[12];
#pragma unroll
      for (int i = 0; i < 12; i++) a[i] = 0.f;
      auto kb_of = [](int it) { return (int)(KORD >> (4 * it)) & 15; };
      if (wid == 9) {
        const uint32_t a0 = sm + rb * 1024 + r2 * 128 + (((c16 >> 1) ^ r2) << 4) + (c16 & 1) * 8;
        const uint2* gw = (const uint2*)(P.wqkv + (kl + rb * 8 + r2) * 3072 + cg * 64) + c16;
#pragma unroll 1
        for (int it = 0; it < 16; it++) {
          uint2 w[12];
          const int kb = kb_of(it);
          if (kb >= 12) {
#pragma unroll
            for (int j = 0; j < 12; j++) w[j] = ld_rlx2(gw + (j >> 2) * 256 + (j & 3) * 1536);
            gw += 64 * 768;
          } else {
            const uint32_t so = a0 + woff(kb & 3);
            mbar_wait(mb + B_FULL + 8 * (kb & 3), (kb >> 2) & 1);
            static_for<0, 12>([&](auto ic) { constexpr int i = decltype(ic)::value;
              const float2 v = lds2f_o<(i >> 2) * WSTR + (i & 3) * 256>(so ^ ((i & 3) << 5)); w[i] = make_uint2(__float_as_uint(v.x), __float_as_uint(v.y)); });
            uint32_t done = 0;
#pragma unroll
            for (int i = 0; i < 12; i++) done |= w[i].y;
            if (lane < 2) mbar_arrive_rem(eb + 8 * (kb & 3) + (done & zero));
          }
#pragma unroll
          for (int i = 0; i < 12; i++) { float* q = a + (i >> 2) * 4; q[0] += bf_lo(w[i].x); q[1] += bf_hi(w[i].x); q[2] += bf_lo(w[i].y); q[3] += bf_hi(w[i].y); }
        }
        if (lane == 0) PTS(8);
        float c[6];
#pragma unroll
        for (int i = 0; i < 6; i++) {
          const int o = (i >> 1) * 4 + (i & 1);
          c[i] = (r2 ? a[o + 2] : a[o]) + __shfl_xor_sync(~0u, r2 ? a[o] : a[o + 2], 16);
        }
        bar_sync(5, 96);
        if (lane == 0) PTS(5);
        const uint32_t tag = lds1(mb + B_SW + 4) & 255;
#pragma unroll
        for (int sg = 0; sg < 3; sg++) st_rlx2((uint2*)&G.csp[(cg * 8 + rb) * 48] + sg * 32 + c16 * 2 + r2, tagged(c[sg * 2], tag), tagged(c[sg * 2 + 1], tag));
      } else {
       if (wid == 10) {
        if (lane < 24 && (lane & 28) != 4) sts4(sm + OFF_STATS + (lane < 16 ? lane * 128 + c8 * 16 : c8 * 16), 0x3F803F80u, 0x3F803F80u, 0x3F803F80u, 0x3F803F80u);
       } else {
        mbar_wait(mb + B_FULL + 8 * PFST, 0);
        const uint32_t ep = ld_rlx(&G.epoch);
        uint4 v[4];
#pragma unroll
        for (int i = 0; i < 4; i++) v[i] = ld_cg4((const uint4*)P.wr + lane + i * 32);
        if (elect_one()) { tmap_prefetch(&tmO); tmap_prefetch(&tmG); tmap_prefetch(&tmU); tmap_prefetch(&tmD); tmap_prefetch(&tmPD); tmap_prefetch(&tmM); }
        __syncwarp();
        const uint4 sv = make_uint4(SENT, SENT, SENT, SENT);
#pragma unroll 1
        for (int i = 0; i < 9; i++) {
          uint4* q = i < 8 ? &G.obuf[((rb * 4 + (i >> 1)) * 64 + cg * 4) * 128 + (i & 1) * 256 + lane] : &G.kvp[cg * 2304 + rb * 288 + lane];
#pragma unroll
          for (int j = 0; j < 8; j++) q[j * 32] = sv;
          if (i == 8) q[256] = sv;
          else if (lane < ((i & 1) ? 24 : 16)) l2_prefetch((i & 1) ? P.wqkv + (kl + (i >> 1) * 64 + rb * 8 + c8) * 3072 + r4 * 1024 + cg * 64 : P.x + (b * 16 + lane) * D_ + kl + i * 32);
        }
        float s = 0.f;
#pragma unroll 1
        for (int i = 0; i < 4; i++) {
          s += (bf_lo(v[0].x) + bf_hi(v[0].x)) + (bf_lo(v[0].y) + bf_hi(v[0].y)) + (bf_lo(v[0].z) + bf_hi(v[0].z)) + (bf_lo(v[0].w) + bf_hi(v[0].w));
          v[0] = v[1]; v[1] = v[2]; v[2] = v[3];
        }
#pragma unroll
        for (int o = 16; o; o >>= 1) s += __shfl_xor_sync(~0u, s, o);
        if (lane == 0) sts2f(mb + B_SW, s, __uint_as_float(ep + 1));
       }
        const uint32_t xa = sm + (c3 * 16 + r4) * 128 + ((c8 ^ r4) << 4);
        const uint4* gx = (const uint4*)(P.x + (b * 16 + r4) * D_ + kl) + c8;
        uint32_t e[4] = {0, 0, 0, 0};
        uint4 wq;
#pragma unroll 1
        for (int kb = wid == 10 ? 0 : 12; kb < (wid == 10 ? 12 : 16); kb++) {
          uint4 v[4];
          if (!(kb & 3)) wq = ld_cg4((const uint4*)(P.wr + k_of(kb + r4)) + c8);
          if (kb >= 12) {
#pragma unroll
            for (int j = 0; j < 4; j++) v[j] = ld_cg4(gx + j * 512);
            gx += 8;
          } else {
            const uint32_t so = xa + xoff(kb & 3, hf);
            mbar_wait(mb + B_FULL + 8 * (kb & 3), (kb >> 2) & 1);
            v[0] = lds4_o<0>(so); v[1] = lds4_o<512>(so ^ 64); v[2] = lds4_o<1024>(so); v[3] = lds4_o<1536>(so ^ 64);
            if (lane < 2) mbar_arrive_rem(eb + 8 * (kb & 3) + ((v[0].x | v[1].x | v[2].x | v[3].x) & zero));
          }
#pragma unroll
          for (int j = 0; j < 16; j++) {
            const uint32_t u = (j & 3) == 0 ? v[j >> 2].x : (j & 3) == 1 ? v[j >> 2].y : (j & 3) == 2 ? v[j >> 2].z : v[j >> 2].w;
            const float d0 = bf_lo(u), d1 = bf_hi(u);
            a[j >> 2] += d0 + d1; a[4 + (j >> 2)] = fmaf(d0, d0, fmaf(d1, d1, a[4 + (j >> 2)]));
          }
          cut<1>(zero);
          const int sl = (kb & 3) * 8 + c8;
          const uint4 wn = make_uint4(__shfl_sync(~0u, wq.x, sl), __shfl_sync(~0u, wq.y, sl), __shfl_sync(~0u, wq.z, sl), __shfl_sync(~0u, wq.w, sl));
#pragma unroll
          for (int j = 0; j < 4; j++) e[j] = hfma2(v[j].x, wn.x, hfma2(v[j].y, wn.y, hfma2(v[j].z, wn.z, hfma2(v[j].w, wn.w, e[j]))));
        }
        float mean, pd;
#pragma unroll 1
        for (int h = 0; h < 2; h++) {
          float u[4], v[2];
#pragma unroll
          for (int i = 0; i < 4; i++) u[i] = ((lane & 4) ? a[4 + i] : a[i]) + __shfl_xor_sync(~0u, (lane & 4) ? a[i] : a[4 + i], 4);
#pragma unroll
          for (int i = 0; i < 2; i++) v[i] = ((lane & 2) ? u[2 + i] : u[i]) + __shfl_xor_sync(~0u, (lane & 2) ? u[i] : u[2 + i], 2);
          mean = pd;
          pd = ((lane & 1) ? v[1] : v[0]) + __shfl_xor_sync(~0u, (lane & 1) ? v[0] : v[1], 1);
#pragma unroll
          for (int j = 0; j < 4; j++) { a[j] = bf_lo(e[j]); a[4 + j] = bf_hi(e[j]); }
        }
        if (wid == 11) {
          sts2f(sm + OFF_COLSUM + 512 + lane * 8, mean, pd);
          fence_gpu();
          bar_arrive(5, 96); PTS(0);
          if (elect_one()) {
#pragma unroll 1
            for (int p = 0; p < 16; p++) {
              const uint32_t ad = sm + bar3(0) + o3(p);
              mbar_init(ad, 1); mbar_init(ad + 256, 1); mbar_init(ad + 448, 8); mbar_init(ad + 704, p == 0 ? 2 : p == 12 ? 1 : p == 15 ? 7 : 8);
              mbar_expect_tx(ad, 8192); mbar_expect_tx(ad + 256, 8192); mbar_expect_tx(mb + B_FULL3 + 8 * p, SLOT_B);
            }
            asm volatile("fence.mbarrier_init.release.cluster;" ::: "memory");
            fence_async_smem();
            mbar_arrive_rem(bars + B_LATE); mbar_arrive_rem((1u << 24) + bars + B_LATE);
          }
          __syncwarp();
        } else {
          if (lane == 0) PTS(1);
          bar_sync(5, 96);
          const float2 u = lds2f(sm + OFF_COLSUM + 512 + lane * 8), sw = lds2f(mb + B_SW);
          mean = (mean + u.x) * (1.f / D_);
          pd += u.y;
          pd += __shfl_xor_sync(~0u, pd, 4);
          const float var = fmaxf(fmaf(-mean, mean, __shfl_xor_sync(~0u, mean, 4)), 0.f);
          const uint32_t tag = __float_as_uint(sw.y) & 255;
          if (c8 < 4) {
            st_rlx2((uint2*)G.st1 + (b >> 1) * 96 + rank * 16 + r4 + 4 * c8, tagged(-mean, tag), tagged(rsq(var + 1e-5f), tag));
            st_rlx(&G.pred[b * 16 + r4 + 4 * c8], (ordered(fmaf(-mean, sw.x, pd)) & ~255u) | tag);
          }
        }
      }
      if (wid < 11) gather(lds1(mb + B_SW + 4) & 255);
      if (wid == 9) {
        if (lane == 0) PTS(6);
        {
          const uint4 sv = make_uint4(SENT, SENT, SENT, SENT);
          uint4* y = &G.ybuf[b * NFFN * 4 + lane];
#pragma unroll
          for (int i = 0; i < 14; i++) y[i * 32] = sv;
          if (lane < 16) G.st2[b * 16 + lane] = make_uint4(0, 0, 0, 0);
          G.hsel[b * 64 + lane] = sv; G.hsel[b * 64 + 32 + lane] = sv;
          if (b < 8) { G.cand[b * 32 + lane] = SENT; G.cst[b * 32 + lane] = make_uint4(0, 0, 0, 0); }
          fence_gpu();
          __syncwarp();
          if (lane == 0) mbar_arrive(mb + B_LATE);
        }
      } else if (wid == 10) {
        {
          mbar_wait(mb + B_FULL + 24, 1);
#pragma unroll 1
          for (int r = -4; r < (fidx >= 0 ? 16 : 0); r++) {
            l2_prefetch((r < 0 ? (const char*)P.wo + (b + 1) * 16384 : (const char*)P.wd + fidx * 65536) + r * 4096 + lane * 128);
            delay(clk(), PDT);
          }
          PTS(4);
        }
      }
      mbar_wait(mb + B_LATE, 0);
      if (wid == 9) {
        if (elect_one()) {
          wait3(60);
#pragma unroll 1
          for (int p = 0; p < 16; p++) {
            const bool mix = (unsigned)(p - 1) < 8;
            const int c1 = mix ? ((p - 1) >> 1) * 16 : 0, c2 = mix ? (hf ^ 1) * 8 + ((p - 1) & 1) * 4 : chunk_of(p) * 4;
            const uint32_t d = sm + (uint32_t)((WO_SLOTS >> (4 * p)) & 15) * SLOT_B;
            if ((0xFFE2 >> p) & 1) mbar_wait(p < 6 ? mb + B_EMPTY + 8 * (p >> 2) : sm + bar3(32) + o3(p - 5), p < 6);
            if (EFWO) asm volatile("cp.async.bulk.tensor.4d.shared::cluster.global.mbarrier::complete_tx::bytes.L2::cache_hint [%0], [%1, {0, %3, %4, %5}], [%2], %6;"
                         :: "r"(d), "l"(mix ? &tmM : &tmO), "r"(mb + B_FULL3 + 8 * p), "r"(c1), "r"(c2), "r"(c3 * 2), "l"(l2_stream()) : "memory");
            else asm volatile("cp.async.bulk.tensor.4d.shared::cluster.global.mbarrier::complete_tx::bytes [%0], [%1, {0, %3, %4, %5}], [%2];"
                         :: "r"(d), "l"(mix ? &tmM : &tmO), "r"(mb + B_FULL3 + 8 * p), "r"(c1), "r"(c2), "r"(c3 * 2) : "memory");
            if (p >= 10) PTS(7 + p);
          }
        }
      } else if (wid == 11) {
        const uint2 w = ld_rlx2((const uint2*)(P.wr + c3 * 128) + lane);
        wait3(36);
        sts1(sm + OFF_LNP + (lane & 1) * 128 + (lane >> 1) * 4, w.x); sts1(sm + OFF_LNP + (lane & 1) * 128 + 64 + (lane >> 1) * 4, w.y);
        if (lane < 16) sts1(sm + OFF_LNP + 256 + lane * 4, 0x3F803F80u);
        const uint32_t tag = lds1(mb + B_SW + 4) & 255;
        uint4 k;
        for (int it = 0;; it++) {
          k = ld_rlx4((const uint4*)&G.pred[rb * 256 + hf * 64 + r2 * 128] + c16);
          k.x ^= tag; k.y ^= tag; k.z ^= tag; k.w ^= tag;
          if (!__any_sync(~0u, (k.x | k.y | k.z | k.w) & 255)) break;
          SPINCHK(it, 13);
        }
        const uint2 ahead = top2(k.x | (lane * 4), k.y | (lane * 4 + 1), k.z | (lane * 4 + 2), k.w | (lane * 4 + 3));
        if (lane == 0) sts2f(sm + OFF_MSC + 8, __uint_as_float((ahead.x & 127) ^ NOSPEC), __uint_as_float((ahead.y & 127) ^ NOSPEC));
        __syncwarp();
        if (lane == 0) mbar_arrive(mb + B_FULL3 + 8 * 15);
      } else if (fidx >= 0 && elect_one()) {
        wait3(60);
        mbar_expect_tx(mb + B_FULL, 65536);
#pragma unroll 1
        for (int i = 0; i < 8; i++) {
          if (i == 4) {
#pragma unroll 1
            for (int j = 0; j < NPD; j++) { mbar_wait(sm + bar3(32) + o3(PD0 + j), 0); tma_2d(sm + OFF_COLSUM, &tmPD, 0, fidx * 256 + j * 32, mb + B_FFN, false); }
          }
          const int f = (0x76325140 >> (4 * i)) & 15, ev = (FEV >> (4 * i)) & 15;
          const uint32_t d = sm + ((GU_SLOTS >> (4 * f)) & 15) * SLOT_B, fb = mb + (i < 4 ? B_FULL : B_FFN);
          mbar_wait(ev == 15 ? mb + B_EMPTY + 8 : sm + bar3(32) + o3(ev), ev == 15);
          tma_2d(d, &tmG, fidx * 32, f * 128, fb, EFF);
          tma_2d(d + 8192, &tmU, fidx * 32, f * 128, fb, EFF);
          PTS(23 + i);
        }
#pragma unroll 1
        for (int i = 0; i < 4; i++) {
          mbar_wait(sm + bar3(32) + o3(13 + ((i + 1) >> 1)), 0);
          tma_3d(sm + ((D_SLOTS >> (4 * i)) & 15) * SLOT_B, &tmD, 0, fidx * 32, i * 4, mb + B_FFN + 8, EFF);
        }
      }
    }
    __syncwarp();
    const float sw = __uint_as_float(lds1(mb + B_SW));
    const int rr = lane >> 4, row00 = rb * 256 + hf * 64;
    uint2 pick;
    if (wid == 8) {
      wait3(61);
      delay(clk(), SDELAY);
      uint4 v;
      int id;
      for (int it = 0;; it++) {
        v = ld_rlx4(&G.cst[jp * 32 + lane]);
        id = __float2int_rn(__uint_as_float(v.w));
        if (!__any_sync(~0u, (id & 15) != 8)) break;
        SPINCHK(it, 14);
      }
      float2 pr;
      const uint32_t k = route(v, sw, id >> 4, pr);
      pick.x = __reduce_max_sync(~0u, k); pick.y = __reduce_max_sync(~0u, k == pick.x ? 0 : k);
      if (k == pick.x || k == pick.y) sts4(sm + OFF_MSC + 16 + (k == pick.y) * 16, k, lane, __float_as_uint(pr.x), __float_as_uint(pr.y));
      __syncwarp();
      if (lane == 0) { mbar_arrive(mb + B_SEL); PTS(16); }
    } else if (wid == 9) {
      wait3(61);
      delay(clk(), LDELAY);
      uint4 v[4];
      for (int it = 0;; it++) {
#pragma unroll
        for (int i = 0; i < 4; i++) v[i] = ld_rlx4(&G.st2[row00 + (i >> 1) * 128 + (i & 1) * 32 + lane]);
        if (!__any_sync(~0u, (v[0].w & v[1].w & v[2].w & v[3].w) != 0x41000000u)) break;
        SPINCHK(it, 6);
      }
      uint32_t k[4];
#pragma unroll
      for (int i = 0; i < 4; i++) {
        float2 pr;
        k[i] = route(v[i], sw, row00 + (i >> 1) * 128 + (i & 1) * 32 + lane, pr);
        const float nm = __uint_as_float(v[i].x) * (-1.f / D_);
        sts2f(sm + OFF_LNP + (i * 32 + lane) * 8, __uint_as_float(pack2(pr.x, pr.x)), __uint_as_float(pack2(nm, nm)));
      }
      const uint2 m = top2(k[0], k[1], k[2], k[3]);
      if (lane == 0) { st_rlx2(&G.cand[c3 * 32 + (rb * 2 + hf) * 2], m.x, m.y); sts2f(sm + OFF_MSC + 0, __uint_as_float(m.x), __uint_as_float(m.y)); }
      wait3(62);
      __syncwarp();
      if (lane == 0) { mbar_arrive(mb + B_OUT); PTS(12); }
      const int ca = 2047 - (((lane & 4) ? m.y : m.x) & 2047), ta = ((ca >> 1) & 64) + (ca & 63);
      uint32_t h0, h1, h2, h3;
      ldsm4_o<0>(sm + HST + ta * 256 + ((((lane & 3) * 4 + (lane >> 3)) ^ (ta & 7)) << 4), h0, h1, h2, h3);
      st_rlx4(&G.hsel[(32 + (rb * 2 + hf) * 2 + rr) * 128 + c3 * 16 + (lane & 15)], make_uint4(h0, h1, h2, h3));
    }
    mbar_wait(mb + B_OUT, 0);
    const float2 cf = lds2f(sm + OFF_MSC + 0);
    const int ca0 = ~__float_as_int(cf.x), ca1 = ~__float_as_int(cf.y), cand0 = ((ca0 >> 1) & 64) + (ca0 & 63), cand1 = ((ca1 >> 1) & 64) + (ca1 & 63);
    auto norm = [](const uint4& v, const float2& pr) {
      const uint32_t r = __float_as_uint(pr.x), m = __float_as_uint(pr.y);
      return make_uint4(hfma2(hadd2(v.x, m), r, v.x), hfma2(hadd2(v.y, m), r, v.y), hfma2(hadd2(v.z, m), r, v.z), hfma2(hadd2(v.w, m), r, v.w));
    };
    uint4* const og = (uint4*)(P.out + row00 * D_ + c3 * 128) + (lane & 15);
    if (wid == 8) {
      delay(clk(), CDELAY);
      uint32_t k;
      for (int it = 0;; it++) { k = ld_rlx(&G.cand[c3 * 32 + lane]); if (!__any_sync(~0u, k == SENT)) break; SPINCHK(it, 12); }
      const uint32_t m1 = __reduce_max_sync(~0u, k), m2 = __reduce_max_sync(~0u, k == m1 ? 0 : k);
      const uint32_t miss = ((m1 ^ pick.x) | (m2 ^ pick.y)) & 2047;
      if (miss && (k == m1 || k == m2)) {
        float2 pr;
        route(ld_rlx4(&G.st2[2047 - (k & 2047)]), sw, 0, pr);
        sts4(sm + OFF_MSC + 48 + (k == m2) * 16, k, 32 + lane, __float_as_uint(pr.x), __float_as_uint(pr.y));
      }
      if (lane == 0) sts1(sm + OFF_MSC + 80, miss);
      __syncwarp();
      if (lane == 0) { mbar_arrive(mb + B_SEL2); PTS(13); }
      const uint32_t kc = __float_as_uint(rr ? cf.y : cf.x);
      const int c = rr ? cand1 : cand0;
      if (kc != m1 && kc != m2) og[(c + (c & 64)) * 128] = norm(lds4(sm + HST + c * 256 + (((lane & 15) ^ (c & 7)) << 4)), lds2f(sm + OFF_LNP + c * 8));
    }
#pragma unroll 1
    for (int t0 = wid == 8 ? 120 : (11 - wid) * 8; t0 < (wid == 8 ? 128 : 120) * !NOOUT; t0 += 24) {
      uint4 v[4];
      float2 pr[4];
      const uint32_t ad = sm + HST + t0 * 256 + lane * 16;
      static_for<0, 4>([&](auto ic) { constexpr int i = decltype(ic)::value; v[i] = lds4_o<i * 512>(ad ^ (rr << 4) ^ (i << 5)); pr[i] = lds2f_o<i * 16>(sm + OFF_LNP + (t0 + rr) * 8); });
#pragma unroll
      for (int i = 0; i < 4; i++) v[i] = norm(v[i], pr[i]);
      if (t0 >= OHOLD) wait3(63);
#pragma unroll
      for (int i = 0; i < 4; i++) {
        const int tr = t0 + rr + 2 * i;
        if (tr != cand0 && tr != cand1) {
          if (OUTEF) asm volatile("st.global.L2::cache_hint.v4.u32 [%0], {%1,%2,%3,%4}, %5;" :: "l"(og + (tr + (tr & 64)) * 128), "r"(v[i].x), "r"(v[i].y), "r"(v[i].z), "r"(v[i].w), "l"(l2_stream()) : "memory");
          else og[(tr + (tr & 64)) * 128] = v[i];
        }
      }
    }
    if (wid == 11 && lane == 0) PTS(31);
  } else {
    asm volatile("setmaxnreg.inc.sync.aligned.u32 224;");
    const int t128 = tid & 127, warp = wid & 3, g = lane >> 2, t = lane & 3;
    const int mb3 = rb * 4 + wg * 2 + hf;
    float acc[64];
    uint4 abuf[4][4];
    uint32_t to;
    int tid2;
    {
      float acc0[96], acc1[96];
#pragma unroll
      for (int i = 0; i < 96; i++) { asm volatile("" : "=f"(acc0[i])); asm volatile("" : "=f"(acc1[i])); }
      const uint32_t xo0 = dlo(sb, 16) + hf * 512, xo1 = dlo(sb, 16) + (hf ^ 1) * 512;
      const uint32_t eb0 = (t128 << 24) + bars + B_EMPTY;
#pragma unroll 1
      for (int kb = 0; kb < 12; kb++) {
        const int s = kb & 3;
        mbar_wait(mb + B_FULL + 8 * s, (kb >> 2) & 1);
        if (LOCK) bar_sync(13, 256);
        if (kb == 0) TS(1);
        const uint32_t xs = xoff(s, wg) >> 4, ws = dlo(sb + woff(s), WSTR);
        pin(acc0); pin(acc1);
        wg_fence();
#pragma unroll
        for (int k = 0; k < 4; k++) {
          const uint64_t db = dsc<1024, 1>(ws + k * 128);
          const int sd = k == 0 ? kb : 1;
          wgmma_n192_ss<0, 1, 0>(acc0, dsc<1024, 1>(xs + xo0 + k * 2), db, sd);
          wgmma_n192_ss<0, 1, 0>(acc1, dsc<1024, 1>(xs + xo1 + k * 2), db, sd);
          if (k == RELK || k == 3) wg_commit();
          if (k == RELK) {
            wg_wait<1>();
            if (kb > 0 && t128 < 2) mbar_arrive_rem(eb0 + 8 * ((kb - 1) & 3));
          }
        }
        pin(acc0); pin(acc1);
      }
      float qa0[32], qa1[32], kv0[64], kv1[64];
#pragma unroll
      for (int i = 0; i < 96; i++) { if (i < 32) { qa0[i] = acc0[i]; qa1[i] = acc1[i]; } else { kv0[i - 32] = acc0[i]; kv1[i - 32] = acc1[i]; } }
      uint2 st[2][2];
      uint4 am;
      auto center = [&](float (&q)[32], float (&kv)[64], const uint2 (&v)[2]) {
        const uint32_t n0 = v[0].x & (t == 0 ? ~255u : 0u), n1 = v[1].x & (t == 0 ? ~255u : 0u);
        am = make_uint4(__byte_perm(n0, 0, 0x3232), __byte_perm(n1, 0, 0x3232),
                        __byte_perm(__float_as_uint(__uint_as_float(n0) - bf_hi(n0)), 0, 0x3232), __byte_perm(__float_as_uint(__uint_as_float(n1) - bf_hi(n1)), 0, 0x3232));
        wg_fence();
        wgmma_n64_rs<1, 0>(q, am.x, am.y, am.z, am.w, dsc<32, 0>(dlo(sb + OFF_COLSUM, 0)), 1);
        wgmma_n128_rs<1, 0>(kv, am.x, am.y, am.z, am.w, dsc<32, 0>(dlo(sb + OFF_COLSUM + 256, 0)), 1);
      };
      auto load_st = [&]() {
        mbar_wait(mb + B_AUX, 0);
#pragma unroll
        for (int i = 0; i < 4; i++) st[i >> 1][i & 1] = ld_rlx2((const uint2*)G.st1 + ((rb * 4 + wg * 2 + ((i >> 1) ^ hf)) * 2 + (warp >> 1)) * 96 + (warp & 1) * 16 + (i & 1) * 8 + g);
      };
      if (!wg) {
        wg_wait<0>();
        if (t128 < 2) mbar_arrive_rem(eb0 + 24);
        load_st();
#pragma unroll 1
        for (int s = 0; s < 4; s++) mbar_wait(mb + B_FULL + 8 * s, 1);
        bar_sync(6, 256);
      }
      static_for<0, 4>([&](auto sc) {
        constexpr int s = decltype(sc)::value;
        if (wg) mbar_wait(mb + B_FULL + 8 * s, 1);
        const uint32_t xs = (wg ? xoff(s, 1) : xoff(s, 0)) >> 4, ws = dlo(sb + woff(s) + WSTR, WSTR);
        pin(kv0); pin(kv1); pin(qa0); pin(qa1);
        wg_fence();
#pragma unroll
        for (int k = 0; k < 4; k++) {
          const uint64_t db = dsc<1024, 1>(ws + k * 128);
          wgmma_n128_ss<0, 1, 0>(kv0, dsc<1024, 1>(xs + xo0 + k * 2), db, 1);
          wgmma_n128_ss<0, 1, 0>(kv1, dsc<1024, 1>(xs + xo1 + k * 2), db, 1);
          if (k == 3 || (k == 2 && s == 0)) wg_commit();
          if (k == (s ? 3 : 2) && s < 3) {
            wg_wait<1>();
            if (s == 0) { if (wg && t128 < 2) mbar_arrive_rem(eb0 + 24); }
            else if (!wg) bar_arrive(8 + s, 256);
          }
        }
        if (s == STLD && wg) load_st();
      });
      center(qa0, kv0, st[0]);
      wg_commit();
      if (wg) bar_arrive(6, 256);
      float rl[2][2];
      uint32_t r2[2][2];
#pragma unroll
      for (int i = 0; i < 4; i++) { const float r = __uint_as_float(st[i >> 1][i & 1].y & ~255u); r2[i >> 1][i & 1] = pack2(r, r); rl[i >> 1][i & 1] = r * 1.4426950408889634f; }
      const uint32_t sad = sm + (wg ? 11 : 2) * SLOT_B + (warp * 16 + (lane & 15)) * 128 + (((lane >> 4) ^ (lane & 7)) << 4);
      wg_wait<0>();
      pin(kv0); pin(kv1); pin(qa0); pin(qa1); pin4(am);
      center(qa1, kv1, st[1]);
      wg_commit();
      if (wg) bar_arrive(11, 256);
      if (CUTS & 1) cut<2>(zero);
      TS(2);
      auto phi8 = [&](const float* a, int m) {
        return make_uint4(phi2(a[0], a[1], r2[m][0], rl[m][0]), phi2(a[2], a[3], r2[m][1], rl[m][1]), phi2(a[4], a[5], r2[m][0], rl[m][0]), phi2(a[6], a[7], r2[m][1], rl[m][1]));
      };
      auto stage = [&](float (&a)[64], auto mc) {
        constexpr int m = decltype(mc)::value;
        uint4 r[4];
#pragma unroll
        for (int j = 0; j < 4; j++) r[j] = phi8(a + j * 8, m);
        if (m == 0 || wg) bar_sync(wg ? 9 + m : 11, 256 + (r[SBAR].x & zero));
#pragma unroll
        for (int j = 0; j < 4; j++) {
          const int v = 32 + j * 8;
          stsm4_o<WSTR + m * 8192>(sad ^ (j << 5), hmul2(pack2(a[v], a[v + 1]), r2[m][0]), hmul2(pack2(a[v + 2], a[v + 3]), r2[m][1]),
                                                   hmul2(pack2(a[v + 4], a[v + 5]), r2[m][0]), hmul2(pack2(a[v + 6], a[v + 7]), r2[m][1]));
        }
#pragma unroll
        for (int j = 0; j < 4; j++) stsm4_o<m * 8192>(sad ^ (j << 5), r[j].x, r[j].y, r[j].z, r[j].w);
      };
      stage(kv0, std::integral_constant<int, 0>{});
      wg_wait<0>();
      pin(kv1); pin(qa1); pin4(am);
      stage(kv1, std::integral_constant<int, 1>{});
      fence_async_smem();
      TS(3);
      uint32_t xr[8][4];
      auto load_xr = [&]() {
        const uint32_t xa = sm + hf * 8192 + (warp * 16 + (lane & 15)) * 128 + (((lane >> 4) ^ (lane & 7)) << 4);
#pragma unroll
        for (int q = 0; q < 8; q++) ldsm4_o<0>((xa ^ ((q & 3) << 5)) + xoff(rank * 2 + (q >> 2), wg), xr[q][0], xr[q][1], xr[q][2], xr[q][3]);
      };
      if (!wg) { bar_arrive(4, 256); load_xr(); }
      else {
        float ka[36];
#pragma unroll
        for (int i = 0; i < 36; i++) ka[i] = 0.f;
        auto kv_mma = [&](auto ic) {
          constexpr int i = decltype(ic)::value;
          constexpr uint32_t o = sb + (i < 8 ? 11 : 2) * SLOT_B + (i & 7) * 2048;
          wgmma_n72_ss<1, 1, 0>(ka, dsc<1024, 1>(dlo(o, 8192)), dsc<1024, 1>(dlo(o + WSTR, sb + OFF_STATS - o - WSTR)), i);
        };
        mbar_wait(mb + B_LATE, 0);
        bar_sync(3, 128);
        wg_fence();
        static_for<0, 8>(kv_mma);
        wg_commit();
        uint4* dst = &G.kvp[cg * 2304 + rb * 32];
        if (CUTS & 4) cut<3>(zero);
        load_xr();
        bar_sync(4, 256);
        static_for<8, 16>(kv_mma);
        wg_commit();
        if (QHOLD == 1) bar_arrive(8, 256);
        wg_wait<0>();
        pin(ka);
        if (QHOLD == 2) bar_arrive(8, 256);
        TS(4);
        if (warp < 2) {
          st_rlx4(dst + warp * 512 + lane, make_uint4(pack2(ka[0], ka[1]), pack2(ka[4], ka[5]), pack2(ka[8], ka[9]), pack2(ka[12], ka[13])));
          st_rlx4(dst + warp * 512 + 256 + lane, make_uint4(pack2(ka[2], ka[3]), pack2(ka[6], ka[7]), pack2(ka[10], ka[11]), pack2(ka[14], ka[15])));
        } else {
          st_rlx4(dst + warp * 512 + lane, make_uint4(pack2(ka[16], ka[17]), pack2(ka[20], ka[21]), pack2(ka[24], ka[25]), pack2(ka[28], ka[29])));
          st_rlx4(dst + warp * 512 + 256 + lane, make_uint4(pack2(ka[18], ka[19]), pack2(ka[22], ka[23]), pack2(ka[26], ka[27]), pack2(ka[30], ka[31])));
        }
        st_rlx((uint32_t*)(dst + 2048) + t128, pack2(ka[32], ka[34]));
        if (QHOLD == 3) bar_arrive(8, 256);
        if (t128 == 0) mbar_arrive(sm + bar3(60));
      }
      TS(5);
      uint32_t pq[16];
      auto q_mma = [&](float (&q)[32], uint32_t xo, int next) {
#pragma unroll 1
        for (int s = 0; s < 4; s++) {
          const uint32_t xs = (xoff(s, wg) >> 4) + xo, ws = dlo(sb + woff(s), 8192);
          pin(q);
          wg_fence();
#pragma unroll
          for (int k = 0; k < 4; k++) wgmma_n64_ss<0, 1, 0>(q, dsc<1024, 1>(xs + k * 2), dsc<1024, 1>(ws + k * 128), 1);
          wg_commit();
        }
        if (next) bar_arrive(next, 256);
        wg_wait<0>();
        pin(q);
      };
      auto q_phi = [&](float (&q)[32], int m) {
#pragma unroll
        for (int j = 0; j < 4; j++) { const uint4 r = phi8(q + j * 8, m); pq[j * 4] = r.x; pq[j * 4 + 1] = r.y; pq[j * 4 + 2] = r.z; pq[j * 4 + 3] = r.w; }
      };
      auto o_of = [&](uint4 (&o)[4], uint4* first, bool pub) {
        float oa[2][20];
#pragma unroll
        for (int i = 0; i < 40; i++) oa[i / 20][i % 20] = 0.f;
        wg_fence();
#pragma unroll
        for (int ks = 0; ks < 4; ks++) {
          wgmma_n40_rs<1, 0>(oa[ks >> 1], pq[ks * 4], pq[ks * 4 + 1], pq[ks * 4 + 2], pq[ks * 4 + 3], dsc<1024, 1>(dlo(sb + OFF_KVB + ks * 2048, 8192)), ks & 1);
          if (ks & 1) wg_commit();
        }
#pragma unroll
        for (int h = 0; h < 2; h++) {
          if (h) wg_wait<0>(); else wg_wait<1>();
          pin(oa[h]);
          const float (&d)[20] = oa[h];
          const float i0 = rcp(d[16] + 1e-6f), i1 = rcp(d[18] + 1e-6f);
#pragma unroll
          for (int k2 = 0; k2 < 2; k2++) {
            o[h * 2 + k2] = make_uint4(pack2(d[k2 * 8] * i0, d[k2 * 8 + 1] * i0), pack2(d[k2 * 8 + 2] * i1, d[k2 * 8 + 3] * i1),
                                       pack2(d[k2 * 8 + 4] * i0, d[k2 * 8 + 5] * i0), pack2(d[k2 * 8 + 6] * i1, d[k2 * 8 + 7] * i1));
            if (pub && h * 2 + k2 < NPUB) st_rlx4(first + (h * 2 + k2) * 1024, o[h * 2 + k2]);
          }
        }
#pragma unroll
        for (int i = 0; i < 16; i++) asm volatile("" : "+r"(pq[i]) :: "memory");
      };
      bar_sync(wg ? 7 : 8, 256);
      q_mma(qa1, xo1, wg ? 8 : 7);
      q_phi(qa1, 1);
      tid2 = __shfl_sync(~0u, tid, lane);
      uint32_t done = 0;
#pragma unroll
      for (int j = 0; j < 8; j++) done |= pq[2 * j] | pq[2 * j + 1] | xr[j][3];
      bar_sync(wg ? 7 : 8, 256 + (done & zero));
      q_mma(qa0, xo0, wg ? 0 : 7);
      if (t128 == 0) mbar_arrive(mb + B_EMPTY + 8 * wg);
      TS(6);
      {
        uint4 a, v[8];
        uint32_t z[8], zs;
        const int blk = warp * 2 + wg;
        mbar_wait(mb + B_KVL, 0);
        static_for<0, 8>([&](auto ic) { constexpr int i = decltype(ic)::value; v[i] = lds4_o<sb + 11 * SLOT_B + i * 512>(own + (blk + (blk & 4)) * 4096 + lane * 16); });
#pragma unroll
        for (int i = 0; i < 8; i++) z[i] = lds1(sm + 2 * SLOT_B + i * 512 + t128 * 4);
#pragma unroll 1
        for (int it = 0;; it++) {
          zs = hadd2(hadd2(hadd2(z[0], z[1]), hadd2(z[2], z[3])), hadd2(hadd2(z[4], z[5]), hadd2(z[6], z[7])));
          a = hadd8(hadd8(hadd8(v[0], v[1]), hadd8(v[2], v[3])), hadd8(hadd8(v[4], v[5]), hadd8(v[6], v[7])));
          TSV(20, it + 1);
          if (!__any_sync(~0u, hnan(hadd2(hadd2(hadd2(a.x, a.y), hadd2(a.z, a.w)), zs)))) break;
          uint32_t mm = 0;
#pragma unroll
          for (int i = 0; i < 8; i++) mm = max4(max(mm, z[i]), v[i]);
          if (!__any_sync(~0u, mm == SENT)) break;
#pragma unroll
          for (int i = 0; i < 8; i++) { v[i] = ld_rlx4(&G.kvp[cg * 2304 + blk * 256 + i * 32 + lane]); z[i] = ld_rlx((const uint32_t*)&G.kvp[cg * 2304 + 2048 + i * 32] + t128); }
          SPINCHK(it, 4);
        }
        TS(23);
        const uint32_t kb0 = sm + OFF_KVB + blk * 1024 + (lane & 7) * 128;
        stsm4(kb0 + (((lane >> 3) ^ (lane & 7)) << 4), a.x, a.y, a.z, a.w);
        asm volatile("stmatrix.sync.aligned.m8n8.x1.shared.b16 [%0], {%1};" :: "r"(kb0 + ((4 ^ (lane & 7)) << 4)), "r"(zs >> (16 * wg)) : "memory");
        fence_async_smem();
        bar_sync(12, 256);
      }
      TS(7);
      if (t128 == 0) mbar_arrive_rem((wg << 24) + sb + bar3(48));
      to = clk();
      o_of(abuf[1], &G.obuf[((mb3 ^ 1) * 64 + hf * 32 + c3) * 128 + (tid2 & 127)], true);
      TS(29);
      cut<4>(zero);
      pin(qa0);
      q_phi(qa0, 0);
      o_of(abuf[0], nullptr, false);
#pragma unroll
      for (int q = 0; q < 32; q++) { asm volatile("" : "+r"(xr[q >> 2][q & 3])); acc[q * 2] = bf_lo(xr[q >> 2][q & 3]); acc[q * 2 + 1] = bf_hi(xr[q >> 2][q & 3]); }
      pin(acc);
    }
    {
    const int t128 = tid2 & 127, lane = tid2 & 31, g = lane >> 2, t = lane & 3;
    uint4* const od0 = &G.obuf[(mb3 * 64 + cg * 4) * 128 + t128];
    TS(8);
    {
      const uint32_t la = own + wg * 8192 + t128 * 16, fa = sm + wg * 256;
#pragma unroll
      for (int i = 8; i < 16; i++) abuf[i >> 2][i & 3] = make_uint4(0, 0, 0, 0);
#pragma unroll 1
      for (int pp = 0; pp < 16; pp += 4) {
        static_for<0, 4>([&](auto jc) {
          constexpr int j = decltype(jc)::value;
          constexpr uint32_t ro = sb + (10 + ((j + 1) & 3)) * SLOT_B;
          const int p = pp + j;
          const uint32_t o1 = ((p + 1) >> 3) * 128 + ((p + 1) & 7) * 8;
          uint4 (&a)[4] = abuf[j];
          uint4 (&n)[4] = abuf[(j + 1) & 3];
          auto fetch = [&]() {
            mbar_wait(fa + bar3(0) + o1, 0);
            n[0] = lds4_o<ro>(la); n[1] = lds4_o<ro + 2048>(la); n[2] = lds4_o<ro + 4096>(la); n[3] = lds4_o<ro + 6144>(la);
          };
          const bool early = j == 3 ? pp < 12 : (j > 1 || pp > 0);
          const uint32_t bs = dlo(sb, 8192) + ((WO_SLOTS >> (4 * p)) & 15) * (SLOT_B >> 4);
          mbar_wait(mb + B_FULL3 + 8 * p, 0);
          if (early) fetch();
          if (p == 1) TS(28);
          if (p == 2) TS(9);
          pin(acc);
          wg_fence();
#pragma unroll
          for (int k = 0; k < 4; k++) wgmma_n128_rs<1, 0>(acc, a[k].x, a[k].y, a[k].z, a[k].w, dsc<1024, 1>(bs + k * 128), 1);
          wg_commit();
          if (j < 2 && pp == 0) {
            if (j == 0 && NPUB < 4) {
              delay(to, BDELAY);
#pragma unroll
              for (int k = NPUB; k < 4; k++) st_rlx4(&G.obuf[((mb3 ^ 1) * 64 + hf * 32 + c3) * 128 + t128 + k * 1024], n[k]);
            }
            if (j == 0) TS(24);
            fetch();
            if (j == 0) TS(27);
          }
          if (__any_sync(~0u, max(max4(max4(0, n[0]), n[1]), max4(max4(0, n[2]), n[3])) == SENT)) {
            int pl = p + 1; asm volatile("" : "+r"(pl));
            const uint4* q = &G.obuf[(mb3 * 64 + chunk_of(pl) * 4) * 128 + t128];
#pragma unroll 1
            for (int it = 0;; it++) {
#pragma unroll
              for (int i = 0; i < 4; i++) n[i] = ld_rlx4(q + i * 128);
              TSV(21, _ts | 1 << pl);
              if (!__any_sync(~0u, max(max4(max4(0, n[0]), n[1]), max4(max4(0, n[2]), n[3])) == SENT)) break;
              SPINCHK(it, 5);
            }
          }
          if (lane == 0 && p < 11) mbar_arrive_rem((wg << 24) + sb + bar3(48) + o1);
          wg_wait<1>();
          pin(acc);
#pragma unroll
          for (int i = 0; i < 4; i++) pin4(abuf[(j + 3) & 3][i]);
          if (j < 3 && pp == 0) {
#pragma unroll
            for (int k = 0; k < 4; k++) if (((W0POS >> (4 * k)) & 15) == j) st_rlx4(od0 + k * 128, abuf[0][k]);
          }
          if (lane == 0) mbar_arrive(sm + bar3(32) + (p >> 3) * 128 + (p & 7) * 8);
        });
      }
    }
    uint4 wb[4];
#pragma unroll
    for (int i = 0; i < 4; i++) wb[i] = lds4(sm + OFF_LNP + ((g & 1) ? t * 64 : 256) + i * 16);
    const float2 ah = lds2f(sm + OFF_MSC + 8);
    wg_wait<0>();
    pin(acc);
#pragma unroll
    for (int i = 0; i < 4; i++) pin4(abuf[3][i]);
    TS(10);
    const uint32_t msc = sm + OFF_MSC;
    uint32_t hp[8][4];
    {
      float se[2][4], q[4] = {0.f, 0.f, 0.f, 0.f};
#pragma unroll
      for (int i = 0; i < 8; i++) se[i >> 2][i & 3] = 0.f;
#pragma unroll
      for (int j = 0; j < 8; j++) {
#pragma unroll
        for (int i = 0; i < 4; i++) { const float a = acc[j * 8 + i * 2], c = acc[j * 8 + i * 2 + 1]; hp[j][i] = pack2(a, c); q[i] = fmaf(a, a, fmaf(c, c, q[i])); }
        mma16816(se[j & 1], hp[j], (j & 1) ? wb[j >> 1].z : wb[j >> 1].x, (j & 1) ? wb[j >> 1].w : wb[j >> 1].y);
      }
      const bool od = t & 1;
      const float q0 = q[0] + q[2], q1 = q[1] + q[3];
      float qq = (od ? q1 : q0) + __shfl_xor_sync(~0u, od ? q0 : q1, 1);
      qq += __shfl_xor_sync(~0u, qq, 2);
      const float ss = od ? se[0][2] + se[1][2] : se[0][0] + se[1][0], ee = od ? se[0][3] + se[1][3] : se[0][1] + se[1][1];
#pragma unroll 1
      for (int c = 0; c < 2; c++) {
        const int tr = __float_as_int(c ? ah.y : ah.x), slot = (rb * 2 + hf) * 2 + c;
        if ((tr >> 4) == wid) {
          const int sl = (tr & 7) * 4 + ((tr >> 3) & 1);
          const float s1 = __shfl_sync(~0u, ss, sl), s2 = __shfl_sync(~0u, qq, sl), s3 = __shfl_sync(~0u, ee, sl);
          red4(lane < 8, &G.cst[lane * 32 + slot], s1, s2, s3, c3 ? 1.f : (float)((mb3 * 64 + (tr & 63)) * 16 + 1));
          if (g == (tr & 7)) {
#pragma unroll
            for (int i = 0; i < 4; i++)
              st_rlx4(&G.hsel[slot * 128 + c3 * 16 + i * 4 + t], (tr & 8) ? make_uint4(hp[2 * i][1], hp[2 * i][3], hp[2 * i + 1][1], hp[2 * i + 1][3])
                                                                          : make_uint4(hp[2 * i][0], hp[2 * i][2], hp[2 * i + 1][0], hp[2 * i + 1][2]));
          }
        }
      }
      red4(t < 2, &G.st2[mb3 * 64 + warp * 16 + (t & 1) * 8 + g], ss, qq, ee, 1.f);
      if (lane == 0) mbar_arrive(sm + bar3(61));
      TS(11);
    }
    uint32_t wa[32][4], wd[8][2][4];
    const uint32_t ga = own + ((lane >> 3) & 1) * 8192 + ((lane >> 4) * 8 + (lane & 7)) * 64 + ((warp ^ ((lane >> 1) & 3)) << 4);
    const uint32_t dw = sm + ((D_SLOTS >> (2 * (wid & 6))) & 15) * SLOT_B + (wid & 1) * 8192;
    const uint32_t da = dw + ((lane >> 4) * 8 + (lane & 7)) * 128 + ((((lane >> 3) & 1) ^ (lane & 7)) << 4);
    const uint32_t xl = own + ((lane & 16) ? 12 + wg : 4 - 3 * wg) * SLOT_B + (lane & 8) * 1024 + (lane & 7) * 16;
    float ya[8][4];
    int pass = 0;
    auto load_gu = [&](int f) {
      const uint32_t ad = ga + ((GU_SLOTS >> (16 * wg + 4 * f)) & 15) * SLOT_B;
      static_for<0, 8>([&](auto ic) { constexpr int i = decltype(ic)::value; ldsm4t_o<sb + i * 1024>(ad, wa[f * 8 + i]); });
    };
    if (fidx >= 0) mbar_wait(mb + B_FULL, 0);
    load_gu(0); load_gu(1);
    {
      bar_sync(1, 256);
      const uint32_t ha = sm + HST + wid * 4096 + (lane & 15) * 256 + (((lane >> 4) ^ (lane & 7)) << 4);
      static_for<0, 8>([&](auto jc) { constexpr int j = decltype(jc)::value; stsm4_o<(j >> 2) * 128>(ha ^ ((j & 3) << 5), hp[j][0], hp[j][1], hp[j][2], hp[j][3]); });
      asm volatile("fence.acq_rel.cta;" ::: "memory");
      __syncwarp();
      if (lane == 0) mbar_arrive(sm + bar3(62));
    }
    if (fidx >= 0) mbar_wait(mb + B_FFN, 1);
#pragma unroll 1
    for (;; pass++) {
      if (pass) { load_gu(0); load_gu(1); }
      load_gu(2);
      TS(15);
      mbar_wait(mb + B_SEL, 0);
      const uint4 sx = lds4(msc + 16 + pass * 32 + (lane & 16));
      TS(26);
      const uint4* xp = &G.hsel[sx.y * 128 + wid * 16 + (lane & 15)];
      uint4 xv = ld_rlx4(xp);
      load_gu(3);
      if (!pass) {
        if (fidx >= 0) mbar_wait(mb + B_FFN + 8, 0);
        static_for<0, 8>([&](auto ic) { constexpr int i = decltype(ic)::value; ldsm4t_o<(i & 1) * 2048>(da ^ ((i >> 1) << 5), wd[i >> 1][i & 1]); });
      }
#pragma unroll 1
      for (int it = 0; __any_sync(~0u, max4(0, xv) == SENT); it++) { xv = ld_rlx4(xp); SPINCHK(it, 7); }
      const float f = __uint_as_float(sx.z), n = __uint_as_float(sx.w);
      sts4(dw + ((lane & 12) * 2 + (lane >> 4) * 4 + t) * 16, pack2(fmaf(bf_lo(xv.x), f, n), fmaf(bf_hi(xv.x), f, n)), pack2(fmaf(bf_lo(xv.y), f, n), fmaf(bf_hi(xv.y), f, n)),
           pack2(fmaf(bf_lo(xv.z), f, n), fmaf(bf_hi(xv.z), f, n)), pack2(fmaf(bf_lo(xv.w), f, n), fmaf(bf_hi(xv.w), f, n)));
      if (wid == rb && (g & 3) == (cg >> 2)) sts4(msc + 96 + (lane >> 4) * 16 + t * 32, xv.x, xv.y, xv.z, xv.w);
      bar_sync(2 + wg, 128);
      TS(14);
      float gu[4][4];
#pragma unroll
      for (int i = 0; i < 16; i++) gu[i >> 2][i & 3] = 0.f;
      uint4 xb[4];
      static_for<0, 4>([&](auto ic) { constexpr int i = decltype(ic)::value; xb[i] = lds4_o<sb + i * 128>(xl); });
#pragma unroll
      for (int ks = 0; ks < 8; ks++) {
        if (ks == 6) {
#pragma unroll
          for (int j = 0; j < 8; j++) xb[3].x |= wd[4 + (j >> 1)][j & 1][3] & zero;
        }
#pragma unroll
        for (int j = 0; j < 4; j++) mma16816(gu[j], wa[j * 8 + ks], (ks & 1) ? xb[ks >> 1].z : xb[ks >> 1].x, (ks & 1) ? xb[ks >> 1].w : xb[ks >> 1].y);
        if (ks == 2) static_for<0, 8>([&](auto jc) { constexpr int j = decltype(jc)::value; ldsm4t_o<4096 + (j & 1) * 2048>(da ^ ((j >> 1) << 5), wd[4 + (j >> 1)][j & 1]); });
      }
      {
        float o[4];
#pragma unroll
        for (int j = 0; j < 4; j++) o[j] = t == 0 ? gu[0][j] : t == 1 ? gu[1][j] : t == 2 ? gu[2][j] : gu[3][j];
        const float e0 = ((t & 2) ? o[2] : o[0]) + __shfl_xor_sync(~0u, (t & 2) ? o[0] : o[2], 2), e1 = ((t & 2) ? o[3] : o[1]) + __shfl_xor_sync(~0u, (t & 2) ? o[1] : o[3], 2);
        sts1(sm + (4 - 3 * wg) * SLOT_B + 1024 + t128 * 4, __float_as_uint(((t & 1) ? e1 : e0) + __shfl_xor_sync(~0u, (t & 1) ? e0 : e1, 1)));
      }
      TS(25);
      bar_sync(1, 256);
      const uint4 p0 = lds4_o<sb + 4 * SLOT_B + 1024>(own + lane * 16), p1 = lds4_o<sb + SLOT_B + 1024>(own + lane * 16);
      const float g0 = __uint_as_float(p0.x) + __uint_as_float(p1.x), g1 = __uint_as_float(p0.y) + __uint_as_float(p1.y);
      const float u0 = __uint_as_float(p0.z) + __uint_as_float(p1.z), u1 = __uint_as_float(p0.w) + __uint_as_float(p1.w);
      const uint32_t act = pack2(g0 * rcp(1.f + ex2(-1.4426950408889634f * g0)) * u0, g1 * rcp(1.f + ex2(-1.4426950408889634f * g1)) * u1);
      uint32_t bq[4];
#pragma unroll
      for (int i = 0; i < 4; i++) {
        const uint32_t lo = __shfl_sync(~0u, act, i * 8 + 2 * t), hi = __shfl_sync(~0u, act, i * 8 + 2 * t + 1);
        bq[i] = __byte_perm(lo, hi, (g & 1) ? 0x7632 : 0x5410);
      }
      TS(16);
#pragma unroll
      for (int i = 0; i < 8; i++) { ya[i][0] = 0.f; ya[i][1] = 0.f; ya[i][2] = 0.f; ya[i][3] = 0.f; }
#pragma unroll
      for (int ks = 0; ks < 2; ks++)
#pragma unroll
        for (int i = 0; i < 8; i++) mma16816(ya[i], wd[i][ks], bq[ks * 2], bq[ks * 2 + 1]);
      mbar_wait(mb + B_SEL2, 0);
      if (pass || !lds1(msc + 80)) break;
      bar_sync(1, 256);
    }
    if (fidx >= 0) {
      uint2* const yp = (uint2*)&G.ybuf[((wid * 16 + t * 2) * NFFN + fidx) * 4] + g;
#pragma unroll
      for (int h = 0; h < 2; h++) {
        float o[4];
#pragma unroll
        for (int j = 0; j < 4; j++) o[j] = t == 0 ? ya[h * 4][j] : t == 1 ? ya[h * 4 + 1][j] : t == 2 ? ya[h * 4 + 2][j] : ya[h * 4 + 3][j];
        st_rlx2(yp + h * (8 * NFFN * 8), __float_as_uint(o[0]), __float_as_uint(o[1]));
        st_rlx2(yp + h * (8 * NFFN * 8) + NFFN * 8, __float_as_uint(o[2]), __float_as_uint(o[3]));
      }
    }
    TS(17);
    const uint32_t ty = clk();
    if (wid < 7) {
      const uint4* const yq = &G.ybuf[b * NFFN * 4 + wid * 64 + lane];
      const uint4 sel = lds4(msc + 16 + pass * 32 + (lane & 1) * 16);
      const uint32_t fh = lds1(msc + 96 + (lane & 1) * 16 + (g & 3) * 32 + (cg & 3) * 4);
      const float r = __uint_as_float(sel.x ^ (~(uint32_t)((int)sel.x >> 31) | 0x80000000u));
      float sg = rcp(1.f + ex2(-1.4426950408889634f * r)), base = fmaf((lane & 2) ? bf_hi(fh) : bf_lo(fh), 1.f + __uint_as_float(sel.z), __uint_as_float(sel.w));
      __nv_bfloat16* op = P.out + (size_t)(2047 - (sel.x & 2047)) * D_ + b * 8 + ((lane >> 1) & 7);
      asm volatile("" : "+f"(sg), "+f"(base), "+l"(op) :: "memory");
      delay(ty, YDELAY);
      uint4 v0, v1;
#pragma unroll 1
      for (int it = 0;; it++) {
        v0 = ld_rlx4(yq); v1 = ld_rlx4(yq + 32);
        TSV(22, it + 1);
        if (!__any_sync(~0u, max(max4(0, v0), max4(0, v1)) == SENT)) break;
        SPINCHK(it, 8);
      }
      if (lane == 0) mbar_arrive(sm + bar3(63));
      TS(18);
      float y0 = __uint_as_float(v0.x) + __uint_as_float(v1.x), y1 = __uint_as_float(v0.y) + __uint_as_float(v1.y);
      float y2 = __uint_as_float(v0.z) + __uint_as_float(v1.z), y3 = __uint_as_float(v0.w) + __uint_as_float(v1.w);
      float z0 = ((lane & 16) ? y2 : y0) + __shfl_xor_sync(~0u, (lane & 16) ? y0 : y2, 16), z1 = ((lane & 16) ? y3 : y1) + __shfl_xor_sync(~0u, (lane & 16) ? y1 : y3, 16);
      z0 = ((lane & 8) ? z1 : z0) + __shfl_xor_sync(~0u, (lane & 8) ? z0 : z1, 8);
      z0 += __shfl_xor_sync(~0u, z0, 4);
      const uint32_t yx = sm + OFF_COLSUM;
      if (!(lane & 4)) sts1(yx + (t * 4 + (lane >> 3)) * 32 + wid * 4, __float_as_uint(z0));
      if (wid) bar_arrive(1, 224);
      else {
        bar_sync(1, 224);
        const uint4 a = lds4(yx + (lane & 15) * 32), c = lds4(yx + (lane & 15) * 32 + 16);
        const float y = ((__uint_as_float(a.x) + __uint_as_float(a.y)) + (__uint_as_float(a.z) + __uint_as_float(a.w))) + ((__uint_as_float(c.x) + __uint_as_float(c.y)) + __uint_as_float(c.z));
        if (lane < 16) *op = __float2bfloat16(fmaf(y, sg, base));
        if (b == 0 && lane == 16) G.epoch = lds1(mb + B_SW + 4);
      }
    }
    }
    TS(19); TSG(31);
    if (warp == 0) TS_DUMP(wg);
  }
}

typedef CUresult (*EncodeFn)(CUtensorMap*, CUtensorMapDataType, cuuint32_t, void*, const cuuint64_t*, const cuuint64_t*, const cuuint32_t*,
                             const cuuint32_t*, CUtensorMapInterleave, CUtensorMapSwizzle, CUtensorMapL2promotion, CUtensorMapFloatOOBfill);
void make_map(EncodeFn enc, CUtensorMap* m, const void* p, uint64_t cols, uint64_t rows, uint64_t d0, uint32_t b0, uint32_t b1, uint32_t b2, CUtensorMapSwizzle sw,
              CUtensorMapL2promotion promo = CU_TENSOR_MAP_L2_PROMOTION_L2_128B) {
  cuuint64_t dims[3] = {d0, rows, cols / d0}, str[2] = {cols * 2, d0 * 2};
  cuuint32_t box[3] = {b0, b1, b2}, es[3] = {1, 1, 1};
  enc(m, CU_TENSOR_MAP_DATA_TYPE_BFLOAT16, b2 ? 3 : 2, const_cast<void*>(p), dims, str, box, es, CU_TENSOR_MAP_INTERLEAVE_NONE, sw,
      promo, CU_TENSOR_MAP_FLOAT_OOB_FILL_NONE);
}

}

extern "C" void kernel_launch(void* const* d_in, const int* in_sizes, int n_in, void* d_out, int out_size) {
  (void)in_sizes; (void)n_in; (void)out_size;
  Ptrs P;
  P.x = (const __nv_bfloat16*)d_in[0]; P.wqkv = (const __nv_bfloat16*)d_in[1]; P.wo = (const __nv_bfloat16*)d_in[2];
  P.wr = (const __nv_bfloat16*)d_in[4]; P.wg = (const __nv_bfloat16*)d_in[5]; P.wu = (const __nv_bfloat16*)d_in[6];
  P.wd = (const __nv_bfloat16*)d_in[7]; P.out = (__nv_bfloat16*)d_out;
  void* fn = nullptr;
  cudaDriverEntryPointQueryResult q;
  cudaGetDriverEntryPoint("cuTensorMapEncodeTiled", &fn, cudaEnableDefault, &q);
  EncodeFn enc = (EncodeFn)fn;
  CUtensorMap tmX, tmW, tmO, tmG, tmU, tmD, tmM, tmPG, tmPU, tmPD;
  make_map(enc, &tmX, P.x, D_, S_, D_, 64, 128, 0, CU_TENSOR_MAP_SWIZZLE_128B);
  make_map(enc, &tmW, P.wqkv, 3 * D_, D_, 3 * D_, 64, 64, 0, CU_TENSOR_MAP_SWIZZLE_128B);
  make_map(enc, &tmG, P.wg, F_, D_, F_, 32, 128, 0, CU_TENSOR_MAP_SWIZZLE_64B);
  make_map(enc, &tmU, P.wu, F_, D_, F_, 32, 128, 0, CU_TENSOR_MAP_SWIZZLE_64B);
  make_map(enc, &tmD, P.wd, D_, F_, 64, 64, 32, 4, CU_TENSOR_MAP_SWIZZLE_128B);
  make_map(enc, &tmPG, P.wg, F_, D_, F_, 8, 32, 0, CU_TENSOR_MAP_SWIZZLE_NONE);
  make_map(enc, &tmPU, P.wu, F_, D_, F_, 8, 32, 0, CU_TENSOR_MAP_SWIZZLE_NONE);
  make_map(enc, &tmPD, P.wd, 128, F_ * 8, 128, 8, 32, 0, CU_TENSOR_MAP_SWIZZLE_NONE, CU_TENSOR_MAP_L2_PROMOTION_L2_256B);
  for (int m = 0; m < 2; m++) {
    cuuint64_t dims[4] = {64, m ? 64u : 16u, m ? 16u : 64u, 16}, str[3] = {2 * D_, (m ? 128u : 32u) * D_, 128};
    cuuint32_t box[4] = {64, 16, 4, 2}, es[4] = {1, 1, 1, 1};
    enc(m ? &tmM : &tmO, CU_TENSOR_MAP_DATA_TYPE_BFLOAT16, 4, const_cast<__nv_bfloat16*>(P.wo), dims, str, box, es, CU_TENSOR_MAP_INTERLEAVE_NONE,
        CU_TENSOR_MAP_SWIZZLE_128B, CU_TENSOR_MAP_L2_PROMOTION_L2_128B, CU_TENSOR_MAP_FLOAT_OOB_FILL_NONE);
  }
  cudaFuncSetAttribute(fused_kernel, cudaFuncAttributeMaxDynamicSharedMemorySize, SMEM_BYTES);
  fused_kernel<<<NCTA, 384, SMEM_BYTES>>>(tmX, tmW, tmO, tmG, tmU, tmD, tmM, tmPG, tmPU, tmPD, P);
}
```

```cpp
#include <cuda_runtime.h>
#include <cuda.h>
#include <cuda_bf16.h>
#include <stdint.h>
#include <type_traits>

namespace {

constexpr int S_ = 2048, D_ = 1024, F_ = 3584;
constexpr int NCTA = 128, NFFN = 112;
constexpr uint32_t SENT = 0xFFFFFFFFu;
constexpr int SPIN_LIMIT = 1 << 20;

#define ADELAY 900
#define NPK 0x233333333333ull
#define KDELAY 800
#define SBAR 2
#define NOOUT 0
#define OHOLD 72
#define OUTEF 0
#define CUTS 0
#define EFO 0
#define EFWO 0
#define TMPF 1
#define INIF 0
#define FEV (RW == 6 ? 0xDCCB0FFFu : 0xDCC0FFFFu)
#define NPUB 2
#define ASTEP 300
#define BDELAY 1500
#define LATEP 0x20
#define RW 6
#define PD0 2
#define NPD 8
#define PDT 100
#define KORD 0xBA9F87E6D54C3210ull
#define SDELAY 450
#define LDELAY 500
#define NOSPEC 0
#define LOCK 1
#define STLD 2
#define RELK 1
#define PERT 5
#define QHOLD 3
#define CDELAY 0
#define YDELAY 500
#define EFX 0
#define EFW 1
#define EFF 1
#define GDELAY 800
#define PFST 1
#define W0POS 0x2211
constexpr uint32_t STAGE_B = 57344;
__host__ __device__ constexpr uint32_t xoff(int s, int w) { return ((0x87CA3651u >> (4 * (s + 4 * w))) & 15) * 16384; }
__host__ __device__ constexpr uint32_t woff(int s) { return (s < 2 ? 9 * 16384 : 0) + (s & 1) * 8192; }
constexpr uint32_t WSTR = 32768;
constexpr uint32_t OFF_BARS = 229376;
constexpr uint32_t OFF_COLSUM = 229632;
constexpr uint32_t OFF_STATS = 230400;
constexpr uint32_t SMEM_BYTES = 232448;
constexpr uint32_t B_FULL = 0, B_EMPTY = 32, B_AUX = 64, B_SEL2 = 72, B_KVL = 80, B_FULL3 = 88, B_SW = 216, B_OUT = 224, B_LATE = 232, B_SEL = B_FULL + 8, B_FFN = 240;
__host__ __device__ constexpr uint32_t o3(int p) { return p * 8 + (p & 8) * 8; }
__host__ __device__ constexpr uint32_t bar3(int i) { return OFF_STATS + 1024 + (i >> 3) * 128 + ((i & 32) ? 0 : 64) + (i & 7) * 8; }
constexpr uint32_t SLOT_B = 16384;
constexpr uint32_t sb = 1024;
constexpr uint32_t bars = sb + OFF_BARS;
constexpr uint64_t WO_SLOTS = RW == 6 ? 0x6514736514736514ull : 0x4536145361453614ull;
constexpr uint32_t GU_SLOTS = RW == 6 ? 0xBA297308u : 0xBA081297u, D_SLOTS = RW == 6 ? 0xD1C4 : 0xD3C6, DS0 = D_SLOTS & 15, DS1 = (D_SLOTS >> 8) & 15;
constexpr uint32_t HST = (RW - 1) * SLOT_B;
constexpr uint32_t OFF_LNP = OFF_STATS;
constexpr uint32_t OFF_MSC = OFF_COLSUM + 512;
constexpr uint32_t OFF_KVB = 2 * SLOT_B + 8192;

struct Scratch {
  uint4 st1[64 * 48];
  uint4 csp[16 * 8 * 48];
  uint4 kvp[16 * 2304];
  uint4 obuf[32 * 64 * 128];
  uint4 st2[S_];
  uint32_t pred[S_];
  uint4 cst[8 * 32];
  uint4 hsel[64 * 128];
  uint32_t cand[8 * 32];
  uint4 ybuf[NCTA * NFFN * 4];
  unsigned epoch;
};
__device__ __align__(1024) Scratch G;
#define TS_DECL
#define TS(i)
#define TSG(i)
#define TSV(i, v)
#define TS_DUMP(slot)
#define PTS(i)

__device__ __forceinline__ uint32_t smem_u32(const void* p) { return (uint32_t)__cvta_generic_to_shared(p); }
__device__ __forceinline__ void mbar_init(uint32_t bar, uint32_t cnt) { asm volatile("mbarrier.init.shared::cta.b64 [%0], %1;" :: "r"(bar), "r"(cnt) : "memory"); }
__device__ __forceinline__ void mbar_expect_tx(uint32_t bar, uint32_t bytes) { asm volatile("mbarrier.arrive.expect_tx.shared::cta.b64 _, [%0], %1;" :: "r"(bar), "r"(bytes) : "memory"); }
__device__ __forceinline__ void mbar_arrive(uint32_t bar) { asm volatile("mbarrier.arrive.shared::cta.b64 _, [%0];" :: "r"(bar) : "memory"); }
#define SPINCHK(it, code) if ((it) > SPIN_LIMIT) break
__device__ __forceinline__ void mbar_wait(uint32_t bar, uint32_t parity) {
  asm volatile("{\n.reg .pred p;\n.reg .u32 c;\nmov.u32 c, 0;\n"
               "WL:\nmbarrier.try_wait.parity.shared::cta.b64 p, [%0], %1;\n@p bra WD;\n"
               "add.u32 c, c, 1;\nsetp.lt.u32 p, c, 1048576;\n@p bra WL;\nWD:\n}" :: "r"(bar), "r"(parity) : "memory");
}
__device__ __forceinline__ uint64_t l2_stream() { uint64_t p; asm("createpolicy.fractional.L2::evict_first.b64 %0, 1.0;" : "=l"(p)); return p; }
__device__ __forceinline__ void tma_2d(uint32_t dst, const CUtensorMap* tm, int c0, int c1, uint32_t bar, bool stream) {
  if (stream) asm volatile("cp.async.bulk.tensor.2d.shared::cluster.global.mbarrier::complete_tx::bytes.L2::cache_hint [%0], [%1, {%3, %4}], [%2], %5;"
                           :: "r"(dst), "l"(tm), "r"(bar), "r"(c0), "r"(c1), "l"(l2_stream()) : "memory");
  else asm volatile("cp.async.bulk.tensor.2d.shared::cluster.global.mbarrier::complete_tx::bytes [%0], [%1, {%3, %4}], [%2];"
                    :: "r"(dst), "l"(tm), "r"(bar), "r"(c0), "r"(c1) : "memory");
}
__device__ __forceinline__ void tma_3d(uint32_t dst, const CUtensorMap* tm, int c0, int c1, int c2, uint32_t bar, bool stream) {
  if (stream) asm volatile("cp.async.bulk.tensor.3d.shared::cluster.global.mbarrier::complete_tx::bytes.L2::cache_hint [%0], [%1, {%3, %4, %5}], [%2], %6;"
                           :: "r"(dst), "l"(tm), "r"(bar), "r"(c0), "r"(c1), "r"(c2), "l"(l2_stream()) : "memory");
  else asm volatile("cp.async.bulk.tensor.3d.shared::cluster.global.mbarrier::complete_tx::bytes [%0], [%1, {%3, %4, %5}], [%2];"
                    :: "r"(dst), "l"(tm), "r"(bar), "r"(c0), "r"(c1), "r"(c2) : "memory");
}
__device__ __forceinline__ void tma_2d_mc(uint32_t dst, const CUtensorMap* tm, int c0, int c1, uint32_t bar, bool stream) {
  if (stream) asm volatile("cp.async.bulk.tensor.2d.shared::cluster.global.mbarrier::complete_tx::bytes.multicast::cluster.L2::cache_hint [%0], [%1, {%3, %4}], [%2], %5, %6;"
                           :: "r"(dst), "l"(tm), "r"(bar), "r"(c0), "r"(c1), "h"((uint16_t)3), "l"(l2_stream()) : "memory");
  else asm volatile("cp.async.bulk.tensor.2d.shared::cluster.global.mbarrier::complete_tx::bytes.multicast::cluster [%0], [%1, {%3, %4}], [%2], %5;"
                    :: "r"(dst), "l"(tm), "r"(bar), "r"(c0), "r"(c1), "h"((uint16_t)3) : "memory");
}
__device__ __forceinline__ bool elect_one() {
  uint32_t p;
  asm volatile("{\n.reg .pred q;\nelect.sync _|q, 0xFFFFFFFF;\nselp.u32 %0, 1, 0, q;\n}" : "=r"(p));
  return p;
}
__device__ __forceinline__ void bulk_load_mc(uint32_t dst, const void* src, uint32_t bar, uint16_t mask) {
  if (EFO) asm volatile("cp.async.bulk.shared::cluster.global.mbarrier::complete_tx::bytes.multicast::cluster.L2::cache_hint [%0], [%1], 8192, [%2], %3, %4;"
               :: "r"(dst), "l"(src), "r"(bar), "h"(mask), "l"(l2_stream()) : "memory");
  else asm volatile("cp.async.bulk.shared::cluster.global.mbarrier::complete_tx::bytes.multicast::cluster [%0], [%1], 8192, [%2], %3;"
               :: "r"(dst), "l"(src), "r"(bar), "h"(mask) : "memory");
}
__device__ __forceinline__ void bulk_load(uint32_t dst, const void* src, uint32_t bytes, uint32_t bar) {
  asm volatile("cp.async.bulk.shared::cluster.global.mbarrier::complete_tx::bytes [%0], [%1], %2, [%3];" :: "r"(dst), "l"(src), "r"(bytes), "r"(bar) : "memory");
}
__device__ __forceinline__ void mbar_arrive_rem(uint32_t bar) { asm volatile("mbarrier.arrive.shared::cluster.b64 _, [%0];" :: "r"(bar) : "memory"); }
template <uint32_t O> __device__ __forceinline__ void ldsm4_o(uint32_t addr, uint32_t& a, uint32_t& b, uint32_t& c, uint32_t& d) {
  asm volatile("ldmatrix.sync.aligned.m8n8.x4.shared.b16 {%0,%1,%2,%3}, [%4+%5];" : "=r"(a), "=r"(b), "=r"(c), "=r"(d) : "r"(addr), "n"(O) : "memory");
}
template <uint32_t O> __device__ __forceinline__ void ldsm4t_o(uint32_t addr, uint32_t (&r)[4]) {
  asm volatile("ldmatrix.sync.aligned.m8n8.x4.trans.shared.b16 {%0,%1,%2,%3}, [%4+%5];" : "=r"(r[0]), "=r"(r[1]), "=r"(r[2]), "=r"(r[3]) : "r"(addr), "n"(O) : "memory");
}
__device__ __forceinline__ void mma16816(float (&c)[4], const uint32_t (&a)[4], uint32_t b0, uint32_t b1) {
  asm("mma.sync.aligned.m16n8k16.row.col.f32.bf16.bf16.f32 {%0,%1,%2,%3}, {%4,%5,%6,%7}, {%8,%9}, {%0,%1,%2,%3};"
      : "+f"(c[0]), "+f"(c[1]), "+f"(c[2]), "+f"(c[3]) : "r"(a[0]), "r"(a[1]), "r"(a[2]), "r"(a[3]), "r"(b0), "r"(b1));
}
__device__ __forceinline__ void l2_prefetch(const void* p) { asm volatile("prefetch.global.L2 [%0];" :: "l"(p) : "memory"); }
__device__ __forceinline__ uint32_t clk() { uint32_t t; asm volatile("mov.u32 %0, %%clock;" : "=r"(t) :: "memory"); return t; }
__device__ __forceinline__ void delay(uint32_t t0, uint32_t n) { while (clk() - t0 < n) {} }
template <int ID> __device__ __forceinline__ void cut(uint32_t zero) { asm volatile("{\n.reg .pred p;\nsetp.eq.u32 p, %0, %1;\nCUT:\n@p nanosleep.u32 1;\n@p bra.uni CUT;\n}" :: "r"(zero), "n"(ID) : "memory"); }
__device__ __forceinline__ void tmap_prefetch(const CUtensorMap* tm) { asm volatile("prefetch.tensormap [%0];" :: "l"(tm) : "memory"); }
__device__ __forceinline__ void wg_fence() { asm volatile("wgmma.fence.sync.aligned;" ::: "memory"); }
__device__ __forceinline__ void wg_commit() { asm volatile("wgmma.commit_group.sync.aligned;" ::: "memory"); }
template <int N> __device__ __forceinline__ void wg_wait() { asm volatile("wgmma.wait_group.sync.aligned %0;" :: "n"(N) : "memory"); }
template <int N> __device__ __forceinline__ void pin(float (&d)[N]) {
#pragma unroll
  for (int i = 0; i < N; i++) asm volatile("" : "+f"(d[i]) :: "memory");
}
__device__ __forceinline__ void pin4(uint4& v) { asm volatile("" : "+r"(v.x), "+r"(v.y), "+r"(v.z), "+r"(v.w) :: "memory"); }
template <uint32_t SBO, uint32_t SWZ> __device__ __forceinline__ uint64_t dsc(uint32_t lo) { return ((uint64_t)((SBO >> 4) | (SWZ << 30)) << 32) | lo; }
__host__ __device__ constexpr uint32_t dlo(uint32_t addr, uint32_t lbo) { return (addr >> 4) | ((lbo >> 4) << 16); }
__device__ __forceinline__ void bar_sync(int id, int n) { asm volatile("bar.sync %0, %1;" :: "r"(id), "r"(n) : "memory"); }
__device__ __forceinline__ void bar_arrive(int id, int n) { asm volatile("bar.arrive %0, %1;" :: "r"(id), "r"(n) : "memory"); }
__device__ __forceinline__ void fence_async_smem() { asm volatile("fence.proxy.async.shared::cta;" ::: "memory"); }
__device__ __forceinline__ void fence_gpu() { asm volatile("fence.acq_rel.gpu;" ::: "memory"); }
__device__ __forceinline__ uint4 ld_cg4(const void* p) { uint4 v; asm volatile("ld.global.cg.v4.u32 {%0,%1,%2,%3}, [%4];" : "=r"(v.x), "=r"(v.y), "=r"(v.z), "=r"(v.w) : "l"(p) : "memory"); return v; }
__device__ __forceinline__ uint4 ld_rlx4(const void* p) { uint4 v; asm volatile("ld.relaxed.gpu.global.v4.u32 {%0,%1,%2,%3}, [%4];" : "=r"(v.x), "=r"(v.y), "=r"(v.z), "=r"(v.w) : "l"(p) : "memory"); return v; }
__device__ __forceinline__ uint32_t ld_rlx(const void* p) { uint32_t v; asm volatile("ld.relaxed.gpu.global.u32 %0, [%1];" : "=r"(v) : "l"(p) : "memory"); return v; }
__device__ __forceinline__ void st_rlx4(void* p, uint4 v) { asm volatile("st.relaxed.gpu.global.v4.u32 [%0], {%1,%2,%3,%4};" :: "l"(p), "r"(v.x), "r"(v.y), "r"(v.z), "r"(v.w) : "memory"); }
__device__ __forceinline__ void st_rlx2(void* p, uint32_t a, uint32_t b) { asm volatile("st.relaxed.gpu.global.v2.u32 [%0], {%1,%2};" :: "l"(p), "r"(a), "r"(b) : "memory"); }
__device__ __forceinline__ void st_rlx(void* p, uint32_t a) { asm volatile("st.relaxed.gpu.global.u32 [%0], %1;" :: "l"(p), "r"(a) : "memory"); }
__device__ __forceinline__ void red4(bool on, void* p, float a, float b, float c, float d) {
  asm volatile("{\n.reg .pred q;\nsetp.ne.b32 q, %5, 0;\n@q red.relaxed.gpu.global.add.v4.f32 [%0], {%1,%2,%3,%4};\n}" :: "l"(p), "f"(a), "f"(b), "f"(c), "f"(d), "r"((int)on) : "memory");
}
__device__ __forceinline__ uint32_t pack2(float lo, float hi) { uint32_t r; asm("cvt.rn.bf16x2.f32 %0, %1, %2;" : "=r"(r) : "f"(hi), "f"(lo)); return r; }
__device__ __forceinline__ float bf_lo(uint32_t v) { return __uint_as_float(v << 16); }
__device__ __forceinline__ float bf_hi(uint32_t v) { return __uint_as_float(v & 0xFFFF0000u); }
__device__ __forceinline__ void stsm4(uint32_t addr, uint32_t a, uint32_t b, uint32_t c, uint32_t d) {
  asm volatile("stmatrix.sync.aligned.m8n8.x4.shared.b16 [%0], {%1,%2,%3,%4};" :: "r"(addr), "r"(a), "r"(b), "r"(c), "r"(d) : "memory");
}
template <uint32_t O> __device__ __forceinline__ void stsm4_o(uint32_t addr, uint32_t a, uint32_t b, uint32_t c, uint32_t d) {
  asm volatile("stmatrix.sync.aligned.m8n8.x4.shared.b16 [%0+%5], {%1,%2,%3,%4};" :: "r"(addr), "r"(a), "r"(b), "r"(c), "r"(d), "n"(O) : "memory");
}
__device__ __forceinline__ void sts4(uint32_t addr, uint32_t a, uint32_t b, uint32_t c, uint32_t d) { asm volatile("st.shared.v4.u32 [%0], {%1,%2,%3,%4};" :: "r"(addr), "r"(a), "r"(b), "r"(c), "r"(d) : "memory"); }
__device__ __forceinline__ void sts2f(uint32_t addr, float a, float b) { asm volatile("st.shared.v2.f32 [%0], {%1,%2};" :: "r"(addr), "f"(a), "f"(b) : "memory"); }
__device__ __forceinline__ void sts1(uint32_t addr, uint32_t a) { asm volatile("st.shared.u32 [%0], %1;" :: "r"(addr), "r"(a) : "memory"); }
__device__ __forceinline__ float2 lds2f(uint32_t addr) { float2 v; asm volatile("ld.shared.v2.f32 {%0,%1}, [%2];" : "=f"(v.x), "=f"(v.y) : "r"(addr) : "memory"); return v; }
template <uint32_t O> __device__ __forceinline__ float2 lds2f_o(uint32_t addr) { float2 v; asm volatile("ld.shared.v2.f32 {%0,%1}, [%2+%3];" : "=f"(v.x), "=f"(v.y) : "r"(addr), "n"(O) : "memory"); return v; }
template <int I, int N, class F> __device__ __forceinline__ void static_for(F&& f) { if constexpr (I < N) { f(std::integral_constant<int, I>{}); static_for<I + 1, N>(f); } }
__device__ __forceinline__ uint4 lds4(uint32_t addr) { uint4 v; asm volatile("ld.shared.v4.u32 {%0,%1,%2,%3}, [%4];" : "=r"(v.x), "=r"(v.y), "=r"(v.z), "=r"(v.w) : "r"(addr) : "memory"); return v; }
__device__ __forceinline__ uint32_t lds1(uint32_t addr) { uint32_t v; asm volatile("ld.shared.u32 %0, [%1];" : "=r"(v) : "r"(addr) : "memory"); return v; }
__device__ __forceinline__ float ex2(float x) { float y; asm("ex2.approx.ftz.f32 %0, %1;" : "=f"(y) : "f"(x)); return y; }
__device__ __forceinline__ uint32_t max4(uint32_t m, const uint4& v) { return __vimax3_u32(__vimax3_u32(m, v.x, v.y), v.z, v.w); }
__device__ __forceinline__ float rsq(float x) { float y; asm("rsqrt.approx.ftz.f32 %0, %1;" : "=f"(y) : "f"(x)); return y; }
__device__ __forceinline__ float rcp(float x) { float y; asm("rcp.approx.ftz.f32 %0, %1;" : "=f"(y) : "f"(x)); return y; }
__device__ __forceinline__ uint2 ld_rlx2(const void* p) { uint2 v; asm volatile("ld.relaxed.gpu.global.v2.u32 {%0,%1}, [%2];" : "=r"(v.x), "=r"(v.y) : "l"(p) : "memory"); return v; }
template <uint32_t O> __device__ __forceinline__ uint4 lds4_o(uint32_t addr) { uint4 v; asm volatile("ld.shared.v4.u32 {%0,%1,%2,%3}, [%4+%5];" : "=r"(v.x), "=r"(v.y), "=r"(v.z), "=r"(v.w) : "r"(addr), "n"(O) : "memory"); return v; }
__device__ __forceinline__ uint32_t hadd2(uint32_t a, uint32_t b) { uint32_t r; asm("add.rn.bf16x2 %0, %1, %2;" : "=r"(r) : "r"(a), "r"(b)); return r; }
__device__ __forceinline__ uint4 hadd8(const uint4& a, const uint4& b) { return make_uint4(hadd2(a.x, b.x), hadd2(a.y, b.y), hadd2(a.z, b.z), hadd2(a.w, b.w)); }
__device__ __forceinline__ bool hnan(uint32_t a) { return (a & 0x7FFF0000u) > 0x7F800000u; }
__device__ __forceinline__ uint32_t hfma2(uint32_t a, uint32_t b, uint32_t c) { uint32_t r; asm("fma.rn.bf16x2 %0, %1, %2, %3;" : "=r"(r) : "r"(a), "r"(b), "r"(c)); return r; }
__device__ __forceinline__ uint32_t ordered(float v) { const uint32_t u = __float_as_uint(v); return u ^ ((uint32_t)((int)u >> 31) | 0x80000000u); }
__device__ __forceinline__ uint32_t route(const uint4& v, float sw, int row, float2& pr) {
  const float mean = __uint_as_float(v.x) * (1.f / D_);
  pr.x = rsq(fmaxf(fmaf(-mean, mean, __uint_as_float(v.y) * (1.f / D_)), 0.f) + 1e-5f);
  pr.y = -mean * pr.x;
  return min(ordered(pr.x * fmaf(-mean, sw, __uint_as_float(v.z))) & ~2047u, 0xFFFFF000u) | (2047 - row);
}
__device__ __forceinline__ uint2 top2(uint32_t a, uint32_t b, uint32_t c, uint32_t d) {
  const uint32_t h0 = max(a, b), h1 = max(c, d), h = max(h0, h1), l = __vimax3_u32(min(h0, h1), min(a, b), min(c, d));
  const uint32_t m1 = __reduce_max_sync(~0u, h);
  return make_uint2(m1, __reduce_max_sync(~0u, h == m1 ? l : h));
}
__device__ __forceinline__ uint32_t hmul2(uint32_t a, uint32_t b) { uint32_t r; asm("mul.rn.bf16x2 %0, %1, %2;" : "=r"(r) : "r"(a), "r"(b)); return r; }
__device__ __forceinline__ uint32_t phi2(float u0, float u1, uint32_t r2, float rl) {
  uint32_t p, r;
  asm("cvt.rn.relu.bf16x2.f32 %0, %1, %2;" : "=r"(p) : "f"(u1), "f"(u0));
  asm("fma.rn.bf16x2 %0, %1, %2, %3;" : "=r"(r) : "r"(p), "r"(r2), "r"(pack2(__saturatef(ex2(u0 * rl) + 1e-6f), __saturatef(ex2(u1 * rl) + 1e-6f))));
  return r;
}

template<int TA, int TB, int OFF, int SZ> __device__ __forceinline__ void wgmma_n192_ss(float (&d)[SZ], uint64_t da, uint64_t db, int scale_d) {
  asm volatile("{\n.reg .pred p;\nsetp.ne.b32 p, %98, 0;\n"
    "wgmma.mma_async.sync.aligned.m64n192k16.f32.bf16.bf16 {%0,%1,%2,%3,%4,%5,%6,%7,%8,%9,%10,%11,%12,%13,%14,%15,%16,%17,%18,%19,%20,%21,%22,%23,%24,%25,%26,%27,%28,%29,%30,%31,%32,%33,%34,%35,%36,%37,%38,%39,%40,%41,%42,%43,%44,%45,%46,%47,%48,%49,%50,%51,%52,%53,%54,%55,%56,%57,%58,%59,%60,%61,%62,%63,%64,%65,%66,%67,%68,%69,%70,%71,%72,%73,%74,%75,%76,%77,%78,%79,%80,%81,%82,%83,%84,%85,%86,%87,%88,%89,%90,%91,%92,%93,%94,%95}, %96, %97, p, 1, 1, %99, %100;\n}\n"
    : "+f"(d[OFF+0]), "+f"(d[OFF+1]), "+f"(d[OFF+2]), "+f"(d[OFF+3]), "+f"(d[OFF+4]), "+f"(d[OFF+5]), "+f"(d[OFF+6]), "+f"(d[OFF+7]),
      "+f"(d[OFF+8]), "+f"(d[OFF+9]), "+f"(d[OFF+10]), "+f"(d[OFF+11]), "+f"(d[OFF+12]), "+f"(d[OFF+13]), "+f"(d[OFF+14]), "+f"(d[OFF+15]),
      "+f"(d[OFF+16]), "+f"(d[OFF+17]), "+f"(d[OFF+18]), "+f"(d[OFF+19]), "+f"(d[OFF+20]), "+f"(d[OFF+21]), "+f"(d[OFF+22]), "+f"(d[OFF+23]),
      "+f"(d[OFF+24]), "+f"(d[OFF+25]), "+f"(d[OFF+26]), "+f"(d[OFF+27]), "+f"(d[OFF+28]), "+f"(d[OFF+29]), "+f"(d[OFF+30]), "+f"(d[OFF+31]),
      "+f"(d[OFF+32]), "+f"(d[OFF+33]), "+f"(d[OFF+34]), "+f"(d[OFF+35]), "+f"(d[OFF+36]), "+f"(d[OFF+37]), "+f"(d[OFF+38]), "+f"(d[OFF+39]),
      "+f"(d[OFF+40]), "+f"(d[OFF+41]), "+f"(d[OFF+42]), "+f"(d[OFF+43]), "+f"(d[OFF+44]), "+f"(d[OFF+45]), "+f"(d[OFF+46]), "+f"(d[OFF+47]),
      "+f"(d[OFF+48]), "+f"(d[OFF+49]), "+f"(d[OFF+50]), "+f"(d[OFF+51]), "+f"(d[OFF+52]), "+f"(d[OFF+53]), "+f"(d[OFF+54]), "+f"(d[OFF+55]),
      "+f"(d[OFF+56]), "+f"(d[OFF+57]), "+f"(d[OFF+58]), "+f"(d[OFF+59]), "+f"(d[OFF+60]), "+f"(d[OFF+61]), "+f"(d[OFF+62]), "+f"(d[OFF+63]),
      "+f"(d[OFF+64]), "+f"(d[OFF+65]), "+f"(d[OFF+66]), "+f"(d[OFF+67]), "+f"(d[OFF+68]), "+f"(d[OFF+69]), "+f"(d[OFF+70]), "+f"(d[OFF+71]),
      "+f"(d[OFF+72]), "+f"(d[OFF+73]), "+f"(d[OFF+74]), "+f"(d[OFF+75]), "+f"(d[OFF+76]), "+f"(d[OFF+77]), "+f"(d[OFF+78]), "+f"(d[OFF+79]),
      "+f"(d[OFF+80]), "+f"(d[OFF+81]), "+f"(d[OFF+82]), "+f"(d[OFF+83]), "+f"(d[OFF+84]), "+f"(d[OFF+85]), "+f"(d[OFF+86]), "+f"(d[OFF+87]),
      "+f"(d[OFF+88]), "+f"(d[OFF+89]), "+f"(d[OFF+90]), "+f"(d[OFF+91]), "+f"(d[OFF+92]), "+f"(d[OFF+93]), "+f"(d[OFF+94]), "+f"(d[OFF+95])
    : "l"(da), "l"(db), "r"(scale_d), "n"(TA), "n"(TB));
}
template<int TA, int TB, int OFF, int SZ> __device__ __forceinline__ void wgmma_n128_ss(float (&d)[SZ], uint64_t da, uint64_t db, int scale_d) {
  asm volatile("{\n.reg .pred p;\nsetp.ne.b32 p, %66, 0;\n"
    "wgmma.mma_async.sync.aligned.m64n128k16.f32.bf16.bf16 {%0,%1,%2,%3,%4,%5,%6,%7,%8,%9,%10,%11,%12,%13,%14,%15,%16,%17,%18,%19,%20,%21,%22,%23,%24,%25,%26,%27,%28,%29,%30,%31,%32,%33,%34,%35,%36,%37,%38,%39,%40,%41,%42,%43,%44,%45,%46,%47,%48,%49,%50,%51,%52,%53,%54,%55,%56,%57,%58,%59,%60,%61,%62,%63}, %64, %65, p, 1, 1, %67, %68;\n}\n"
    : "+f"(d[OFF+0]), "+f"(d[OFF+1]), "+f"(d[OFF+2]), "+f"(d[OFF+3]), "+f"(d[OFF+4]), "+f"(d[OFF+5]), "+f"(d[OFF+6]), "+f"(d[OFF+7]),
      "+f"(d[OFF+8]), "+f"(d[OFF+9]), "+f"(d[OFF+10]), "+f"(d[OFF+11]), "+f"(d[OFF+12]), "+f"(d[OFF+13]), "+f"(d[OFF+14]), "+f"(d[OFF+15]),
      "+f"(d[OFF+16]), "+f"(d[OFF+17]), "+f"(d[OFF+18]), "+f"(d[OFF+19]), "+f"(d[OFF+20]), "+f"(d[OFF+21]), "+f"(d[OFF+22]), "+f"(d[OFF+23]),
      "+f"(d[OFF+24]), "+f"(d[OFF+25]), "+f"(d[OFF+26]), "+f"(d[OFF+27]), "+f"(d[OFF+28]), "+f"(d[OFF+29]), "+f"(d[OFF+30]), "+f"(d[OFF+31]),
      "+f"(d[OFF+32]), "+f"(d[OFF+33]), "+f"(d[OFF+34]), "+f"(d[OFF+35]), "+f"(d[OFF+36]), "+f"(d[OFF+37]), "+f"(d[OFF+38]), "+f"(d[OFF+39]),
      "+f"(d[OFF+40]), "+f"(d[OFF+41]), "+f"(d[OFF+42]), "+f"(d[OFF+43]), "+f"(d[OFF+44]), "+f"(d[OFF+45]), "+f"(d[OFF+46]), "+f"(d[OFF+47]),
      "+f"(d[OFF+48]), "+f"(d[OFF+49]), "+f"(d[OFF+50]), "+f"(d[OFF+51]), "+f"(d[OFF+52]), "+f"(d[OFF+53]), "+f"(d[OFF+54]), "+f"(d[OFF+55]),
      "+f"(d[OFF+56]), "+f"(d[OFF+57]), "+f"(d[OFF+58]), "+f"(d[OFF+59]), "+f"(d[OFF+60]), "+f"(d[OFF+61]), "+f"(d[OFF+62]), "+f"(d[OFF+63])
    : "l"(da), "l"(db), "r"(scale_d), "n"(TA), "n"(TB));
}
template<int TA, int TB, int OFF, int SZ> __device__ __forceinline__ void wgmma_n64_ss(float (&d)[SZ], uint64_t da, uint64_t db, int scale_d) {
  asm volatile("{\n.reg .pred p;\nsetp.ne.b32 p, %34, 0;\n"
    "wgmma.mma_async.sync.aligned.m64n64k16.f32.bf16.bf16 {%0,%1,%2,%3,%4,%5,%6,%7,%8,%9,%10,%11,%12,%13,%14,%15,%16,%17,%18,%19,%20,%21,%22,%23,%24,%25,%26,%27,%28,%29,%30,%31}, %32, %33, p, 1, 1, %35, %36;\n}\n"
    : "+f"(d[OFF+0]), "+f"(d[OFF+1]), "+f"(d[OFF+2]), "+f"(d[OFF+3]), "+f"(d[OFF+4]), "+f"(d[OFF+5]), "+f"(d[OFF+6]), "+f"(d[OFF+7]),
      "+f"(d[OFF+8]), "+f"(d[OFF+9]), "+f"(d[OFF+10]), "+f"(d[OFF+11]), "+f"(d[OFF+12]), "+f"(d[OFF+13]), "+f"(d[OFF+14]), "+f"(d[OFF+15]),
      "+f"(d[OFF+16]), "+f"(d[OFF+17]), "+f"(d[OFF+18]), "+f"(d[OFF+19]), "+f"(d[OFF+20]), "+f"(d[OFF+21]), "+f"(d[OFF+22]), "+f"(d[OFF+23]),
      "+f"(d[OFF+24]), "+f"(d[OFF+25]), "+f"(d[OFF+26]), "+f"(d[OFF+27]), "+f"(d[OFF+28]), "+f"(d[OFF+29]), "+f"(d[OFF+30]), "+f"(d[OFF+31])
    : "l"(da), "l"(db), "r"(scale_d), "n"(TA), "n"(TB));
}
template<int TB, int OFF, int SZ> __device__ __forceinline__ void wgmma_n64_rs(float (&d)[SZ], uint32_t a0, uint32_t a1, uint32_t a2, uint32_t a3, uint64_t db, int scale_d) {
  asm volatile("{\n.reg .pred p;\nsetp.ne.b32 p, %37, 0;\n"
    "wgmma.mma_async.sync.aligned.m64n64k16.f32.bf16.bf16 {%0,%1,%2,%3,%4,%5,%6,%7,%8,%9,%10,%11,%12,%13,%14,%15,%16,%17,%18,%19,%20,%21,%22,%23,%24,%25,%26,%27,%28,%29,%30,%31}, {%32,%33,%34,%35}, %36, p, 1, 1, %38;\n}\n"
    : "+f"(d[OFF+0]), "+f"(d[OFF+1]), "+f"(d[OFF+2]), "+f"(d[OFF+3]), "+f"(d[OFF+4]), "+f"(d[OFF+5]), "+f"(d[OFF+6]), "+f"(d[OFF+7]),
      "+f"(d[OFF+8]), "+f"(d[OFF+9]), "+f"(d[OFF+10]), "+f"(d[OFF+11]), "+f"(d[OFF+12]), "+f"(d[OFF+13]), "+f"(d[OFF+14]), "+f"(d[OFF+15]),
      "+f"(d[OFF+16]), "+f"(d[OFF+17]), "+f"(d[OFF+18]), "+f"(d[OFF+19]), "+f"(d[OFF+20]), "+f"(d[OFF+21]), "+f"(d[OFF+22]), "+f"(d[OFF+23]),
      "+f"(d[OFF+24]), "+f"(d[OFF+25]), "+f"(d[OFF+26]), "+f"(d[OFF+27]), "+f"(d[OFF+28]), "+f"(d[OFF+29]), "+f"(d[OFF+30]), "+f"(d[OFF+31])
    : "r"(a0), "r"(a1), "r"(a2), "r"(a3), "l"(db), "r"(scale_d), "n"(TB));
}
template<int TA, int TB, int OFF, int SZ> __device__ __forceinline__ void wgmma_n72_ss(float (&d)[SZ], uint64_t da, uint64_t db, int scale_d) {
  asm volatile("{\n.reg .pred p;\nsetp.ne.b32 p, %38, 0;\n"
    "wgmma.mma_async.sync.aligned.m64n72k16.f32.bf16.bf16 {%0,%1,%2,%3,%4,%5,%6,%7,%8,%9,%10,%11,%12,%13,%14,%15,%16,%17,%18,%19,%20,%21,%22,%23,%24,%25,%26,%27,%28,%29,%30,%31,%32,%33,%34,%35}, %36, %37, p, 1, 1, %39, %40;\n}\n"
    : "+f"(d[OFF+0]), "+f"(d[OFF+1]), "+f"(d[OFF+2]), "+f"(d[OFF+3]), "+f"(d[OFF+4]), "+f"(d[OFF+5]), "+f"(d[OFF+6]), "+f"(d[OFF+7]),
      "+f"(d[OFF+8]), "+f"(d[OFF+9]), "+f"(d[OFF+10]), "+f"(d[OFF+11]), "+f"(d[OFF+12]), "+f"(d[OFF+13]), "+f"(d[OFF+14]), "+f"(d[OFF+15]),
      "+f"(d[OFF+16]), "+f"(d[OFF+17]), "+f"(d[OFF+18]), "+f"(d[OFF+19]), "+f"(d[OFF+20]), "+f"(d[OFF+21]), "+f"(d[OFF+22]), "+f"(d[OFF+23]),
      "+f"(d[OFF+24]), "+f"(d[OFF+25]), "+f"(d[OFF+26]), "+f"(d[OFF+27]), "+f"(d[OFF+28]), "+f"(d[OFF+29]), "+f"(d[OFF+30]), "+f"(d[OFF+31]),
      "+f"(d[OFF+32]), "+f"(d[OFF+33]), "+f"(d[OFF+34]), "+f"(d[OFF+35])
    : "l"(da), "l"(db), "r"(scale_d), "n"(TA), "n"(TB));
}
template<int TB, int OFF, int SZ> __device__ __forceinline__ void wgmma_n40_rs(float (&d)[SZ], uint32_t a0, uint32_t a1, uint32_t a2, uint32_t a3, uint64_t db, int scale_d) {
  asm volatile("{\n.reg .pred p;\nsetp.ne.b32 p, %25, 0;\n"
    "wgmma.mma_async.sync.aligned.m64n40k16.f32.bf16.bf16 {%0,%1,%2,%3,%4,%5,%6,%7,%8,%9,%10,%11,%12,%13,%14,%15,%16,%17,%18,%19}, {%20,%21,%22,%23}, %24, p, 1, 1, %26;\n}\n"
    : "+f"(d[OFF+0]), "+f"(d[OFF+1]), "+f"(d[OFF+2]), "+f"(d[OFF+3]), "+f"(d[OFF+4]), "+f"(d[OFF+5]), "+f"(d[OFF+6]), "+f"(d[OFF+7]),
      "+f"(d[OFF+8]), "+f"(d[OFF+9]), "+f"(d[OFF+10]), "+f"(d[OFF+11]), "+f"(d[OFF+12]), "+f"(d[OFF+13]), "+f"(d[OFF+14]), "+f"(d[OFF+15]),
      "+f"(d[OFF+16]), "+f"(d[OFF+17]), "+f"(d[OFF+18]), "+f"(d[OFF+19])
    : "r"(a0), "r"(a1), "r"(a2), "r"(a3), "l"(db), "r"(scale_d), "n"(TB));
}
template<int TB, int OFF, int SZ> __device__ __forceinline__ void wgmma_n128_rs(float (&d)[SZ], uint32_t a0, uint32_t a1, uint32_t a2, uint32_t a3, uint64_t db, int scale_d) {
  asm volatile("{\n.reg .pred p;\nsetp.ne.b32 p, %69, 0;\n"
    "wgmma.mma_async.sync.aligned.m64n128k16.f32.bf16.bf16 {%0,%1,%2,%3,%4,%5,%6,%7,%8,%9,%10,%11,%12,%13,%14,%15,%16,%17,%18,%19,%20,%21,%22,%23,%24,%25,%26,%27,%28,%29,%30,%31,%32,%33,%34,%35,%36,%37,%38,%39,%40,%41,%42,%43,%44,%45,%46,%47,%48,%49,%50,%51,%52,%53,%54,%55,%56,%57,%58,%59,%60,%61,%62,%63}, {%64,%65,%66,%67}, %68, p, 1, 1, %70;\n}\n"
    : "+f"(d[OFF+0]), "+f"(d[OFF+1]), "+f"(d[OFF+2]), "+f"(d[OFF+3]), "+f"(d[OFF+4]), "+f"(d[OFF+5]), "+f"(d[OFF+6]), "+f"(d[OFF+7]),
      "+f"(d[OFF+8]), "+f"(d[OFF+9]), "+f"(d[OFF+10]), "+f"(d[OFF+11]), "+f"(d[OFF+12]), "+f"(d[OFF+13]), "+f"(d[OFF+14]), "+f"(d[OFF+15]),
      "+f"(d[OFF+16]), "+f"(d[OFF+17]), "+f"(d[OFF+18]), "+f"(d[OFF+19]), "+f"(d[OFF+20]), "+f"(d[OFF+21]), "+f"(d[OFF+22]), "+f"(d[OFF+23]),
      "+f"(d[OFF+24]), "+f"(d[OFF+25]), "+f"(d[OFF+26]), "+f"(d[OFF+27]), "+f"(d[OFF+28]), "+f"(d[OFF+29]), "+f"(d[OFF+30]), "+f"(d[OFF+31]),
      "+f"(d[OFF+32]), "+f"(d[OFF+33]), "+f"(d[OFF+34]), "+f"(d[OFF+35]), "+f"(d[OFF+36]), "+f"(d[OFF+37]), "+f"(d[OFF+38]), "+f"(d[OFF+39]),
      "+f"(d[OFF+40]), "+f"(d[OFF+41]), "+f"(d[OFF+42]), "+f"(d[OFF+43]), "+f"(d[OFF+44]), "+f"(d[OFF+45]), "+f"(d[OFF+46]), "+f"(d[OFF+47]),
      "+f"(d[OFF+48]), "+f"(d[OFF+49]), "+f"(d[OFF+50]), "+f"(d[OFF+51]), "+f"(d[OFF+52]), "+f"(d[OFF+53]), "+f"(d[OFF+54]), "+f"(d[OFF+55]),
      "+f"(d[OFF+56]), "+f"(d[OFF+57]), "+f"(d[OFF+58]), "+f"(d[OFF+59]), "+f"(d[OFF+60]), "+f"(d[OFF+61]), "+f"(d[OFF+62]), "+f"(d[OFF+63])
    : "r"(a0), "r"(a1), "r"(a2), "r"(a3), "l"(db), "r"(scale_d), "n"(TB));
}

struct Ptrs { const __nv_bfloat16 *x, *wqkv, *wo, *wr, *wg, *wu, *wd; __nv_bfloat16* out; };

__global__ void __cluster_dims__(2, 1, 1) __launch_bounds__(384, 1) fused_kernel(const __grid_constant__ CUtensorMap tmX, const __grid_constant__ CUtensorMap tmW,
                                                       const __grid_constant__ CUtensorMap tmO, const __grid_constant__ CUtensorMap tmG,
                                                       const __grid_constant__ CUtensorMap tmU, const __grid_constant__ CUtensorMap tmD,
                                                       const __grid_constant__ CUtensorMap tmM, const __grid_constant__ CUtensorMap tmPG,
                                                       const __grid_constant__ CUtensorMap tmPU, const __grid_constant__ CUtensorMap tmPD,
                                                       const Ptrs P) {
  extern __shared__ __align__(1024) uint8_t smem_raw[];
  if (TMPF && threadIdx.x == 0) { tmap_prefetch(&tmX); tmap_prefetch(&tmW); }
  const int tid = threadIdx.x, wid = __shfl_sync(~0u, tid >> 5, 0), wg = __shfl_sync(~0u, tid >> 7, 0), lane = tid & 31;
  const int pj = blockIdx.x >> 1, pi = pj - 36;
  const int b = (pj < 4 ? 32 + pj * 8 : pj < 36 ? pj - 4 : 33 + pi + ((pi * 37) >> 8)) * 2 + (blockIdx.x & 1);
  const int rb = b >> 4, cg = b & 15, hf = cg >> 3, c3 = cg & 7;
  const int jp = cg >> 1;
  const int fidx = jp == rb ? -1 : b - 2 * rb - (jp > rb ? 2 : 0);
  const uint32_t rank = b & 1, own = rank << 24;
  const uint32_t zero = gridDim.y - 1;
  const uint32_t sm = own + sb, mb = own + bars;
  auto chunk_of = [&](int p) { return (int)((0x1765432FEDCBA980ull >> (4 * p)) & 15) ^ (p == 0 || p == 15 ? cg : p < 9 ? cg & 8 : cg & 14); };
  const int kl = (jp & 3) * 256;
  auto k_of = [&](int kb) { return kb >= 12 ? kl + (kb - 12) * 64 : kb * 64 < kl ? kb * 64 : kb * 64 + 256; };
  auto load_w = [&](int kb) {
#pragma unroll
    for (int i = 0; i < 3; i++) tma_2d(sm + woff(kb & 3) + i * WSTR, &tmW, i * D_ + cg * 64, k_of(kb), mb + B_FULL + 8 * (kb & 3), EFW);
  };
  TS_DECL; TS(0); TSG(30);
  if (wid == 8) {
    if (elect_one()) {
      if (smem_u32(smem_raw) != sm) {
#pragma unroll
        for (int i = 0; i < PERT; i++) sts1(mb, lds1(mb));
        asm volatile("trap;");
      }
#pragma unroll
      for (int s = 0; s < 4; s++) mbar_init(mb + B_FULL + 8 * s, 1);
      asm volatile("fence.mbarrier_init.release.cluster;" ::: "memory");
      if (INIF) fence_async_smem();
    }
  } else if (wid == 9) {
    if (elect_one()) {
#pragma unroll
      for (int i = 4; i < 32; i++)
        if (i != 27) mbar_init(mb + 8 * i, i < 8 ? 8 : i == 8 ? 64 : i == 26 ? 2 : i == 29 ? 4 : 1);
      asm volatile("fence.mbarrier_init.release.cluster;" ::: "memory");
      if (INIF) fence_async_smem();
    }
  }
  __syncwarp();
  asm volatile("barrier.cluster.arrive.relaxed.aligned;" ::: "memory");
  if (wid == 8) {
    if (elect_one()) {
      mbar_expect_tx(mb + B_FULL, STAGE_B);
      tma_2d(sm + xoff(0, 0), &tmX, k_of(0), rb * 256, mb + B_FULL, EFX);
      tma_2d(sm + xoff(0, 1), &tmX, k_of(0), rb * 256 + 128, mb + B_FULL, EFX);
      load_w(0);
    }
    __syncwarp();
  }
  asm volatile("barrier.cluster.wait.aligned;" ::: "memory");

  if (wg == 2) {
    asm volatile("setmaxnreg.dec.sync.aligned.u32 56;");
    auto wait3 = [&](int i) { mbar_wait(sm + bar3(i), 0); };
    if (wid == 8) {
      if (elect_one()) {
        int np = fidx >= 0 ? 0 : 32;
        if (fidx >= 0) mbar_expect_tx(mb + B_FFN, 32 * 512);
#pragma unroll 1
        for (int kb = 1; kb < 16; kb++) {
          const uint32_t fb = mb + B_FULL + 8 * (kb & 3);
          mbar_wait(fb + B_EMPTY, ((kb >> 2) & 1) ^ 1);
          mbar_expect_tx(fb, STAGE_B);
          tma_2d_mc(sm + xoff(kb & 3, rank), &tmX, k_of(kb), rb * 256 + rank * 128, fb, EFX);
          load_w(kb);
          if (kb >= 12) asm volatile("mbarrier.arrive.shared::cta.b64 _, [%0], 7;" :: "r"(fb + B_EMPTY) : "memory");
#pragma unroll 1
          for (int n = ((NPK << 16) >> (4 * kb)) & 15; n > 0 && np < 32; n--, np++)
            tma_2d(sm + OFF_STATS + 512, (np & 1) ? &tmPU : &tmPG, (fidx >> 1) * 64, (np >> 1) * 64 + rank * 32, mb + B_FFN, false);
        }
        if (fidx >= 0) { mbar_wait(mb + B_FFN, 0); mbar_expect_tx(mb + B_FFN, 65536 + NPD * 512); mbar_expect_tx(mb + B_FFN + 8, 65536); }
#pragma unroll
        for (int p = 4; p < 8; p++) sts4(sm + OFF_STATS + p * 144, 0x3F803F80u, 0x3F803F80u, 0x3F803F80u, 0x3F803F80u);
        fence_async_smem();
        mbar_arrive(mb + B_LATE);
        PTS(2);
        mbar_expect_tx(mb + B_KVL, 36864);
        mbar_wait(mb + B_LATE, 0);
        wait3(60);
        delay(clk(), KDELAY);
        bulk_load(sm + 11 * SLOT_B, &G.kvp[cg * 2304], SLOT_B, mb + B_KVL);
        bulk_load(sm + 13 * SLOT_B, &G.kvp[cg * 2304 + 1024], SLOT_B, mb + B_KVL);
        bulk_load(sm + 2 * SLOT_B, &G.kvp[cg * 2304 + 2048], 4096, mb + B_KVL);
        PTS(3);
        const uint4* src = &G.obuf[(rb * 4 + rank * 2 + hf) * 64 * 128];
        wait3(48);
        const uint32_t t1 = clk();
#pragma unroll
        for (int p = 1; p < 5; p++) {
          delay(t1, ADELAY + (p - 1) * ASTEP);
          bulk_load_mc(sm + (10 + (p & 3)) * SLOT_B + rank * 8192, src + ((hf ^ 1) * 8 + p - 1) * 512, sm + bar3(p) + rank * 256, 3);
        }
        PTS(7);
#pragma unroll 1
        for (int i = 5; i < 17; i++) {
          const int p = min(i, 15);
          const uint32_t d = sm + (10 + (p & 3)) * SLOT_B + rank * 8192, fb = sm + bar3(0) + o3(p) + rank * 256;
          const uint4* q = src + chunk_of(i & 15) * 512;
          mbar_wait(sm + bar3(48) + o3(p - 4 + ((LATEP >> p) & 1)), 0);
          bulk_load_mc(d, q, fb, i < 15 ? 3 : 1 << ((i ^ rank ^ 1) & 1));
        }
        PTS(15);
      }
    } else {
      const int r4 = lane >> 3, c8 = lane & 7;
      const uint32_t eb = (lane << 24) + bars + B_EMPTY;
      auto tagged = [](float v, uint32_t tag) { return ((__float_as_uint(v) + 128) & ~255u) | tag; };
      auto gather = [&](uint32_t tag) {
        const int q = (wid - 9) * 24 + lane;
        const uint4* cp = lane < 24 ? &G.csp[cg * 8 * 48 + q] : &G.st1[rb * 8 * 48 + (wid - 9) * 8 + lane - 24];
        uint4 v[8];
        delay(clk(), GDELAY);
#pragma unroll 1
        for (int it = 0;; it++) {
#pragma unroll
          for (int i = 0; i < 8; i++) v[i] = ld_rlx4(cp + i * 48);
          uint32_t x = 0;
#pragma unroll
          for (int i = 0; i < 8; i++) { v[i].x ^= tag; v[i].y ^= tag; v[i].z ^= tag; v[i].w ^= tag; x |= v[i].x | v[i].y | v[i].z | v[i].w; }
          if (!__any_sync(~0u, (x & 255) != 0)) break;
          SPINCHK(it, 3);
        }
        float c[4] = {0.f, 0.f, 0.f, 0.f};
#pragma unroll
        for (int i = 0; i < 8; i++) { c[0] += __uint_as_float(v[i].x); c[1] += __uint_as_float(v[i].y); c[2] += __uint_as_float(v[i].z); c[3] += __uint_as_float(v[i].w); }
        const uint32_t h0 = pack2(c[0], c[1]), h1 = pack2(c[2], c[3]), ca = sm + OFF_COLSUM + (q >> 1) * 32 + (q & 1) * 8;
        if (lane < 24) {
          sts2f(ca, __uint_as_float(h0), __uint_as_float(h1));
          sts2f(ca + 16, __uint_as_float(pack2(c[0] - bf_lo(h0), c[1] - bf_hi(h0))), __uint_as_float(pack2(c[2] - bf_lo(h1), c[3] - bf_hi(h1))));
        }
        fence_async_smem();
        mbar_arrive(mb + B_AUX);
      };
      const int r2 = lane >> 4, c16 = lane & 15;
      float a[12];
#pragma unroll
      for (int i = 0; i < 12; i++) a[i] = 0.f;
      auto kb_of = [](int it) { return (int)(KORD >> (4 * it)) & 15; };
      if (wid == 9) {
        const uint32_t a0 = sm + rb * 1024 + r2 * 128 + (((c16 >> 1) ^ r2) << 4) + (c16 & 1) * 8;
        const uint2* gw = (const uint2*)(P.wqkv + (kl + rb * 8 + r2) * 3072 + cg * 64) + c16;
#pragma unroll 1
        for (int it = 0; it < 16; it++) {
          uint2 w[12];
          const int kb = kb_of(it);
          if (kb >= 12) {
#pragma unroll
            for (int j = 0; j < 12; j++) w[j] = ld_rlx2(gw + (j >> 2) * 256 + (j & 3) * 1536);
            gw += 64 * 768;
          } else {
            const uint32_t so = a0 + woff(kb & 3);
            mbar_wait(mb + B_FULL + 8 * (kb & 3), (kb >> 2) & 1);
            static_for<0, 12>([&](auto ic) { constexpr int i = decltype(ic)::value;
              const float2 v = lds2f_o<(i >> 2) * WSTR + (i & 3) * 256>(so ^ ((i & 3) << 5)); w[i] = make_uint2(__float_as_uint(v.x), __float_as_uint(v.y)); });
            uint32_t done = 0;
#pragma unroll
            for (int i = 0; i < 12; i++) done |= w[i].y;
            if (lane < 2) mbar_arrive_rem(eb + 8 * (kb & 3) + (done & zero));
          }
#pragma unroll
          for (int i = 0; i < 12; i++) { float* q = a + (i >> 2) * 4; q[0] += bf_lo(w[i].x); q[1] += bf_hi(w[i].x); q[2] += bf_lo(w[i].y); q[3] += bf_hi(w[i].y); }
        }
        if (lane == 0) PTS(8);
        float c[6];
#pragma unroll
        for (int i = 0; i < 6; i++) {
          const int o = (i >> 1) * 4 + (i & 1);
          c[i] = (r2 ? a[o + 2] : a[o]) + __shfl_xor_sync(~0u, r2 ? a[o] : a[o + 2], 16);
        }
        bar_sync(5, 96);
        if (lane == 0) PTS(5);
        const uint32_t tag = lds1(mb + B_SW + 4) & 255;
#pragma unroll
        for (int sg = 0; sg < 3; sg++) st_rlx2((uint2*)&G.csp[(cg * 8 + rb) * 48] + sg * 32 + c16 * 2 + r2, tagged(c[sg * 2], tag), tagged(c[sg * 2 + 1], tag));
      } else {
       if (wid == 10) {
        if (lane < 24 && (lane & 28) != 4) sts4(sm + OFF_STATS + (lane < 16 ? lane * 128 + c8 * 16 : c8 * 16), 0x3F803F80u, 0x3F803F80u, 0x3F803F80u, 0x3F803F80u);
       } else {
        mbar_wait(mb + B_FULL + 8 * PFST, 0);
        const uint32_t ep = ld_rlx(&G.epoch);
        uint4 v[4];
#pragma unroll
        for (int i = 0; i < 4; i++) v[i] = ld_cg4((const uint4*)P.wr + lane + i * 32);
        if (elect_one()) { tmap_prefetch(&tmO); tmap_prefetch(&tmG); tmap_prefetch(&tmU); tmap_prefetch(&tmD); tmap_prefetch(&tmPD); tmap_prefetch(&tmM); }
        __syncwarp();
        const uint4 sv = make_uint4(SENT, SENT, SENT, SENT);
#pragma unroll 1
        for (int i = 0; i < 9; i++) {
          uint4* q = i < 8 ? &G.obuf[((rb * 4 + (i >> 1)) * 64 + cg * 4) * 128 + (i & 1) * 256 + lane] : &G.kvp[cg * 2304 + rb * 288 + lane];
#pragma unroll
          for (int j = 0; j < 8; j++) q[j * 32] = sv;
          if (i == 8) q[256] = sv;
          else if (lane < ((i & 1) ? 24 : 16)) l2_prefetch((i & 1) ? P.wqkv + (kl + (i >> 1) * 64 + rb * 8 + c8) * 3072 + r4 * 1024 + cg * 64 : P.x + (b * 16 + lane) * D_ + kl + i * 32);
        }
        float s = 0.f;
#pragma unroll 1
        for (int i = 0; i < 4; i++) {
          s += (bf_lo(v[0].x) + bf_hi(v[0].x)) + (bf_lo(v[0].y) + bf_hi(v[0].y)) + (bf_lo(v[0].z) + bf_hi(v[0].z)) + (bf_lo(v[0].w) + bf_hi(v[0].w));
          v[0] = v[1]; v[1] = v[2]; v[2] = v[3];
        }
#pragma unroll
        for (int o = 16; o; o >>= 1) s += __shfl_xor_sync(~0u, s, o);
        if (lane == 0) sts2f(mb + B_SW, s, __uint_as_float(ep + 1));
       }
        const uint32_t xa = sm + (c3 * 16 + r4) * 128 + ((c8 ^ r4) << 4);
        const uint4* gx = (const uint4*)(P.x + (b * 16 + r4) * D_ + kl) + c8;
        uint32_t e[4] = {0, 0, 0, 0};
        uint4 wq;
#pragma unroll 1
        for (int kb = wid == 10 ? 0 : 12; kb < (wid == 10 ? 12 : 16); kb++) {
          uint4 v[4];
          if (!(kb & 3)) wq = ld_cg4((const uint4*)(P.wr + k_of(kb + r4)) + c8);
          if (kb >= 12) {
#pragma unroll
            for (int j = 0; j < 4; j++) v[j] = ld_cg4(gx + j * 512);
            gx += 8;
          } else {
            const uint32_t so = xa + xoff(kb & 3, hf);
            mbar_wait(mb + B_FULL + 8 * (kb & 3), (kb >> 2) & 1);
            v[0] = lds4_o<0>(so); v[1] = lds4_o<512>(so ^ 64); v[2] = lds4_o<1024>(so); v[3] = lds4_o<1536>(so ^ 64);
            if (lane < 2) mbar_arrive_rem(eb + 8 * (kb & 3) + ((v[0].x | v[1].x | v[2].x | v[3].x) & zero));
          }
#pragma unroll
          for (int j = 0; j < 16; j++) {
            const uint32_t u = (j & 3) == 0 ? v[j >> 2].x : (j & 3) == 1 ? v[j >> 2].y : (j & 3) == 2 ? v[j >> 2].z : v[j >> 2].w;
            const float d0 = bf_lo(u), d1 = bf_hi(u);
            a[j >> 2] += d0 + d1; a[4 + (j >> 2)] = fmaf(d0, d0, fmaf(d1, d1, a[4 + (j >> 2)]));
          }
          cut<1>(zero);
          const int sl = (kb & 3) * 8 + c8;
          const uint4 wn = make_uint4(__shfl_sync(~0u, wq.x, sl), __shfl_sync(~0u, wq.y, sl), __shfl_sync(~0u, wq.z, sl), __shfl_sync(~0u, wq.w, sl));
#pragma unroll
          for (int j = 0; j < 4; j++) e[j] = hfma2(v[j].x, wn.x, hfma2(v[j].y, wn.y, hfma2(v[j].z, wn.z, hfma2(v[j].w, wn.w, e[j]))));
        }
        float mean, pd;
#pragma unroll 1
        for (int h = 0; h < 2; h++) {
          float u[4], v[2];
#pragma unroll
          for (int i = 0; i < 4; i++) u[i] = ((lane & 4) ? a[4 + i] : a[i]) + __shfl_xor_sync(~0u, (lane & 4) ? a[i] : a[4 + i], 4);
#pragma unroll
          for (int i = 0; i < 2; i++) v[i] = ((lane & 2) ? u[2 + i] : u[i]) + __shfl_xor_sync(~0u, (lane & 2) ? u[i] : u[2 + i], 2);
          mean = pd;
          pd = ((lane & 1) ? v[1] : v[0]) + __shfl_xor_sync(~0u, (lane & 1) ? v[0] : v[1], 1);
#pragma unroll
          for (int j = 0; j < 4; j++) { a[j] = bf_lo(e[j]); a[4 + j] = bf_hi(e[j]); }
        }
        if (wid == 11) {
          sts2f(sm + OFF_COLSUM + 512 + lane * 8, mean, pd);
          fence_gpu();
          bar_arrive(5, 96); PTS(0);
          if (elect_one()) {
#pragma unroll 1
            for (int p = 0; p < 16; p++) {
              const uint32_t ad = sm + bar3(0) + o3(p);
              mbar_init(ad, 1); mbar_init(ad + 256, 1); mbar_init(ad + 448, 8); mbar_init(ad + 704, p == 0 ? 2 : p == 12 ? 1 : p == 15 ? 7 : 8);
              mbar_expect_tx(ad, 8192); mbar_expect_tx(ad + 256, 8192); mbar_expect_tx(mb + B_FULL3 + 8 * p, SLOT_B);
            }
            asm volatile("fence.mbarrier_init.release.cluster;" ::: "memory");
            fence_async_smem();
            mbar_arrive_rem(bars + B_LATE); mbar_arrive_rem((1u << 24) + bars + B_LATE);
          }
          __syncwarp();
        } else {
          if (lane == 0) PTS(1);
          bar_sync(5, 96);
          const float2 u = lds2f(sm + OFF_COLSUM + 512 + lane * 8), sw = lds2f(mb + B_SW);
          mean = (mean + u.x) * (1.f / D_);
          pd += u.y;
          pd += __shfl_xor_sync(~0u, pd, 4);
          const float var = fmaxf(fmaf(-mean, mean, __shfl_xor_sync(~0u, mean, 4)), 0.f);
          const uint32_t tag = __float_as_uint(sw.y) & 255;
          if (c8 < 4) {
            st_rlx2((uint2*)G.st1 + (b >> 1) * 96 + rank * 16 + r4 + 4 * c8, tagged(-mean, tag), tagged(rsq(var + 1e-5f), tag));
            st_rlx(&G.pred[b * 16 + r4 + 4 * c8], (ordered(fmaf(-mean, sw.x, pd)) & ~255u) | tag);
          }
        }
      }
      if (wid < 11) gather(lds1(mb + B_SW + 4) & 255);
      if (wid == 9) {
        if (lane == 0) PTS(6);
        {
          const uint4 sv = make_uint4(SENT, SENT, SENT, SENT);
          uint4* y = &G.ybuf[b * NFFN * 4 + lane];
#pragma unroll
          for (int i = 0; i < 14; i++) y[i * 32] = sv;
          if (lane < 16) G.st2[b * 16 + lane] = make_uint4(0, 0, 0, 0);
          G.hsel[b * 64 + lane] = sv; G.hsel[b * 64 + 32 + lane] = sv;
          if (b < 8) { G.cand[b * 32 + lane] = SENT; G.cst[b * 32 + lane] = make_uint4(0, 0, 0, 0); }
          fence_gpu();
          __syncwarp();
          if (lane == 0) mbar_arrive(mb + B_LATE);
        }
      } else if (wid == 10) {
        {
          mbar_wait(mb + B_FULL + 24, 1);
#pragma unroll 1
          for (int r = -4; r < (fidx >= 0 ? 16 : 0); r++) {
            l2_prefetch((r < 0 ? (const char*)P.wo + (b + 1) * 16384 : (const char*)P.wd + fidx * 65536) + r * 4096 + lane * 128);
            delay(clk(), PDT);
          }
          PTS(4);
        }
      }
      mbar_wait(mb + B_LATE, 0);
      if (wid == 9) {
        if (elect_one()) {
          wait3(60);
#pragma unroll 1
          for (int p = 0; p < 16; p++) {
            const bool mix = (unsigned)(p - 1) < 8;
            const int c1 = mix ? ((p - 1) >> 1) * 16 : 0, c2 = mix ? (hf ^ 1) * 8 + ((p - 1) & 1) * 4 : chunk_of(p) * 4;
            const uint32_t d = sm + (uint32_t)((WO_SLOTS >> (4 * p)) & 15) * SLOT_B;
            if ((0xFFE2 >> p) & 1) mbar_wait(p < RW ? mb + B_EMPTY + 8 * (p >> 2) : sm + bar3(32) + o3(p - RW + 1), p < RW);
            if (EFWO) asm volatile("cp.async.bulk.tensor.4d.shared::cluster.global.mbarrier::complete_tx::bytes.L2::cache_hint [%0], [%1, {0, %3, %4, %5}], [%2], %6;"
                         :: "r"(d), "l"(mix ? &tmM : &tmO), "r"(mb + B_FULL3 + 8 * p), "r"(c1), "r"(c2), "r"(c3 * 2), "l"(l2_stream()) : "memory");
            else asm volatile("cp.async.bulk.tensor.4d.shared::cluster.global.mbarrier::complete_tx::bytes [%0], [%1, {0, %3, %4, %5}], [%2];"
                         :: "r"(d), "l"(mix ? &tmM : &tmO), "r"(mb + B_FULL3 + 8 * p), "r"(c1), "r"(c2), "r"(c3 * 2) : "memory");
            if (p >= 10) PTS(7 + p);
          }
        }
      } else if (wid == 11) {
        const uint2 w = ld_rlx2((const uint2*)(P.wr + c3 * 128) + lane);
        wait3(36);
        sts1(sm + OFF_LNP + (lane & 1) * 128 + (lane >> 1) * 4, w.x); sts1(sm + OFF_LNP + (lane & 1) * 128 + 64 + (lane >> 1) * 4, w.y);
        if (lane < 16) sts1(sm + OFF_LNP + 256 + lane * 4, 0x3F803F80u);
        const uint32_t tag = lds1(mb + B_SW + 4) & 255;
        uint4 k;
        for (int it = 0;; it++) {
          k = ld_rlx4((const uint4*)&G.pred[rb * 256 + hf * 64 + r2 * 128] + c16);
          k.x ^= tag; k.y ^= tag; k.z ^= tag; k.w ^= tag;
          if (!__any_sync(~0u, (k.x | k.y | k.z | k.w) & 255)) break;
          SPINCHK(it, 13);
        }
        const uint2 ahead = top2(k.x | (lane * 4), k.y | (lane * 4 + 1), k.z | (lane * 4 + 2), k.w | (lane * 4 + 3));
        if (lane == 0) sts2f(sm + OFF_MSC + 8, __uint_as_float((ahead.x & 127) ^ NOSPEC), __uint_as_float((ahead.y & 127) ^ NOSPEC));
        __syncwarp();
        if (lane == 0) mbar_arrive(mb + B_FULL3 + 8 * 15);
      } else if (fidx >= 0 && elect_one()) {
        wait3(60);
        mbar_expect_tx(mb + B_FULL, 65536);
#pragma unroll 1
        for (int i = 0; i < 8; i++) {
          if (i == 10 - RW) {
#pragma unroll 1
            for (int j = 0; j < NPD; j++) { mbar_wait(sm + bar3(32) + o3(PD0 + j), 0); tma_2d(sm + OFF_COLSUM, &tmPD, 0, fidx * 256 + j * 32, mb + B_FFN, false); }
          }
          const int f = (0x76325140 >> (4 * i)) & 15, ev = (FEV >> (4 * i)) & 15;
          const uint32_t d = sm + ((GU_SLOTS >> (4 * f)) & 15) * SLOT_B, fb = mb + (i < 4 ? B_FULL : B_FFN);
          mbar_wait(ev == 15 ? mb + B_EMPTY + 8 : sm + bar3(32) + o3(ev), ev == 15);
          tma_2d(d, &tmG, fidx * 32, f * 128, fb, EFF);
          tma_2d(d + 8192, &tmU, fidx * 32, f * 128, fb, EFF);
          PTS(23 + i);
        }
#pragma unroll 1
        for (int i = 0; i < 4; i++) {
          mbar_wait(sm + bar3(32) + o3(13 + ((i + 1) >> 1)), 0);
          tma_3d(sm + ((D_SLOTS >> (4 * i)) & 15) * SLOT_B, &tmD, 0, fidx * 32, i * 4, mb + B_FFN + 8, EFF);
        }
      }
    }
    __syncwarp();
    const float sw = __uint_as_float(lds1(mb + B_SW));
    const int rr = lane >> 4, row00 = rb * 256 + hf * 64;
    uint2 pick;
    if (wid == 8) {
      wait3(61);
      delay(clk(), SDELAY);
      uint4 v;
      int id;
      for (int it = 0;; it++) {
        v = ld_rlx4(&G.cst[jp * 32 + lane]);
        id = __float2int_rn(__uint_as_float(v.w));
        if (!__any_sync(~0u, (id & 15) != 8)) break;
        SPINCHK(it, 14);
      }
      float2 pr;
      const uint32_t k = route(v, sw, id >> 4, pr);
      pick.x = __reduce_max_sync(~0u, k); pick.y = __reduce_max_sync(~0u, k == pick.x ? 0 : k);
      if (k == pick.x || k == pick.y) sts4(sm + OFF_MSC + 16 + (k == pick.y) * 16, k, lane, __float_as_uint(pr.x), __float_as_uint(pr.y));
      __syncwarp();
      if (lane == 0) { mbar_arrive(mb + B_SEL); PTS(16); }
    } else if (wid == 9) {
      wait3(61);
      delay(clk(), LDELAY);
      uint4 v[4];
      for (int it = 0;; it++) {
#pragma unroll
        for (int i = 0; i < 4; i++) v[i] = ld_rlx4(&G.st2[row00 + (i >> 1) * 128 + (i & 1) * 32 + lane]);
        if (!__any_sync(~0u, (v[0].w & v[1].w & v[2].w & v[3].w) != 0x41000000u)) break;
        SPINCHK(it, 6);
      }
      uint32_t k[4];
#pragma unroll
      for (int i = 0; i < 4; i++) {
        float2 pr;
        k[i] = route(v[i], sw, row00 + (i >> 1) * 128 + (i & 1) * 32 + lane, pr);
        const float nm = __uint_as_float(v[i].x) * (-1.f / D_);
        sts2f(sm + OFF_LNP + (i * 32 + lane) * 8, __uint_as_float(pack2(pr.x, pr.x)), __uint_as_float(pack2(nm, nm)));
      }
      const uint2 m = top2(k[0], k[1], k[2], k[3]);
      if (lane == 0) { st_rlx2(&G.cand[c3 * 32 + (rb * 2 + hf) * 2], m.x, m.y); sts2f(sm + OFF_MSC + 0, __uint_as_float(m.x), __uint_as_float(m.y)); }
      wait3(62);
      __syncwarp();
      if (lane == 0) { mbar_arrive(mb + B_OUT); PTS(12); }
      const int ca = 2047 - (((lane & 4) ? m.y : m.x) & 2047), ta = ((ca >> 1) & 64) + (ca & 63);
      uint32_t h0, h1, h2, h3;
      ldsm4_o<0>(sm + HST + ta * 256 + ((((lane & 3) * 4 + (lane >> 3)) ^ (ta & 7)) << 4), h0, h1, h2, h3);
      st_rlx4(&G.hsel[(32 + (rb * 2 + hf) * 2 + rr) * 128 + c3 * 16 + (lane & 15)], make_uint4(h0, h1, h2, h3));
    }
    mbar_wait(mb + B_OUT, 0);
    const float2 cf = lds2f(sm + OFF_MSC + 0);
    const int ca0 = ~__float_as_int(cf.x), ca1 = ~__float_as_int(cf.y), cand0 = ((ca0 >> 1) & 64) + (ca0 & 63), cand1 = ((ca1 >> 1) & 64) + (ca1 & 63);
    auto norm = [](const uint4& v, const float2& pr) {
      const uint32_t r = __float_as_uint(pr.x), m = __float_as_uint(pr.y);
      return make_uint4(hfma2(hadd2(v.x, m), r, v.x), hfma2(hadd2(v.y, m), r, v.y), hfma2(hadd2(v.z, m), r, v.z), hfma2(hadd2(v.w, m), r, v.w));
    };
    uint4* const og = (uint4*)(P.out + row00 * D_ + c3 * 128) + (lane & 15);
    if (wid == 8) {
      delay(clk(), CDELAY);
      uint32_t k;
      for (int it = 0;; it++) { k = ld_rlx(&G.cand[c3 * 32 + lane]); if (!__any_sync(~0u, k == SENT)) break; SPINCHK(it, 12); }
      const uint32_t m1 = __reduce_max_sync(~0u, k), m2 = __reduce_max_sync(~0u, k == m1 ? 0 : k);
      const uint32_t miss = ((m1 ^ pick.x) | (m2 ^ pick.y)) & 2047;
      if (miss && (k == m1 || k == m2)) {
        float2 pr;
        route(ld_rlx4(&G.st2[2047 - (k & 2047)]), sw, 0, pr);
        sts4(sm + OFF_MSC + 48 + (k == m2) * 16, k, 32 + lane, __float_as_uint(pr.x), __float_as_uint(pr.y));
      }
      if (lane == 0) sts1(sm + OFF_MSC + 80, miss);
      __syncwarp();
      if (lane == 0) { mbar_arrive(mb + B_SEL2); PTS(13); }
      const uint32_t kc = __float_as_uint(rr ? cf.y : cf.x);
      const int c = rr ? cand1 : cand0;
      if (kc != m1 && kc != m2) og[(c + (c & 64)) * 128] = norm(lds4(sm + HST + c * 256 + (((lane & 15) ^ (c & 7)) << 4)), lds2f(sm + OFF_LNP + c * 8));
    }
#pragma unroll 1
    for (int t0 = wid == 8 ? 120 : (11 - wid) * 8; t0 < (wid == 8 ? 128 : 120) * !NOOUT; t0 += 24) {
      uint4 v[4];
      float2 pr[4];
      const uint32_t ad = sm + HST + t0 * 256 + lane * 16;
      static_for<0, 4>([&](auto ic) { constexpr int i = decltype(ic)::value; v[i] = lds4_o<i * 512>(ad ^ (rr << 4) ^ (i << 5)); pr[i] = lds2f_o<i * 16>(sm + OFF_LNP + (t0 + rr) * 8); });
#pragma unroll
      for (int i = 0; i < 4; i++) v[i] = norm(v[i], pr[i]);
      if (t0 >= OHOLD) wait3(63);
#pragma unroll
      for (int i = 0; i < 4; i++) {
        const int tr = t0 + rr + 2 * i;
        if (tr != cand0 && tr != cand1) {
          if (OUTEF) asm volatile("st.global.L2::cache_hint.v4.u32 [%0], {%1,%2,%3,%4}, %5;" :: "l"(og + (tr + (tr & 64)) * 128), "r"(v[i].x), "r"(v[i].y), "r"(v[i].z), "r"(v[i].w), "l"(l2_stream()) : "memory");
          else og[(tr + (tr & 64)) * 128] = v[i];
        }
      }
    }
    if (wid == 11 && lane == 0) PTS(31);
  } else {
    asm volatile("setmaxnreg.inc.sync.aligned.u32 224;");
    const int t128 = tid & 127, warp = wid & 3, g = lane >> 2, t = lane & 3;
    const int mb3 = rb * 4 + wg * 2 + hf;
    float acc[64];
    uint4 abuf[4][4];
    uint32_t to;
    int tid2;
    {
      float acc0[96], acc1[96];
#pragma unroll
      for (int i = 0; i < 96; i++) { asm volatile("" : "=f"(acc0[i])); asm volatile("" : "=f"(acc1[i])); }
      const uint32_t xo0 = dlo(sb, 16) + hf * 512, xo1 = dlo(sb, 16) + (hf ^ 1) * 512;
      const uint32_t eb0 = (t128 << 24) + bars + B_EMPTY;
#pragma unroll 1
      for (int kb = 0; kb < 12; kb++) {
        const int s = kb & 3;
        mbar_wait(mb + B_FULL + 8 * s, (kb >> 2) & 1);
        if (LOCK) bar_sync(13, 256);
        if (kb == 0) TS(1);
        const uint32_t xs = xoff(s, wg) >> 4, ws = dlo(sb + woff(s), WSTR);
        pin(acc0); pin(acc1);
        wg_fence();
#pragma unroll
        for (int k = 0; k < 4; k++) {
          const uint64_t db = dsc<1024, 1>(ws + k * 128);
          const int sd = k == 0 ? kb : 1;
          wgmma_n192_ss<0, 1, 0>(acc0, dsc<1024, 1>(xs + xo0 + k * 2), db, sd);
          wgmma_n192_ss<0, 1, 0>(acc1, dsc<1024, 1>(xs + xo1 + k * 2), db, sd);
          if (k == RELK || k == 3) wg_commit();
          if (k == RELK) {
            wg_wait<1>();
            if (kb > 0 && t128 < 2) mbar_arrive_rem(eb0 + 8 * ((kb - 1) & 3));
          }
        }
        pin(acc0); pin(acc1);
      }
      float qa0[32], qa1[32], kv0[64], kv1[64];
#pragma unroll
      for (int i = 0; i < 96; i++) { if (i < 32) { qa0[i] = acc0[i]; qa1[i] = acc1[i]; } else { kv0[i - 32] = acc0[i]; kv1[i - 32] = acc1[i]; } }
      uint2 st[2][2];
      uint4 am;
      auto center = [&](float (&q)[32], float (&kv)[64], const uint2 (&v)[2]) {
        const uint32_t n0 = v[0].x & (t == 0 ? ~255u : 0u), n1 = v[1].x & (t == 0 ? ~255u : 0u);
        am = make_uint4(__byte_perm(n0, 0, 0x3232), __byte_perm(n1, 0, 0x3232),
                        __byte_perm(__float_as_uint(__uint_as_float(n0) - bf_hi(n0)), 0, 0x3232), __byte_perm(__float_as_uint(__uint_as_float(n1) - bf_hi(n1)), 0, 0x3232));
        wg_fence();
        wgmma_n64_rs<1, 0>(q, am.x, am.y, am.z, am.w, dsc<32, 0>(dlo(sb + OFF_COLSUM, 0)), 1);
        wgmma_n128_rs<1, 0>(kv, am.x, am.y, am.z, am.w, dsc<32, 0>(dlo(sb + OFF_COLSUM + 256, 0)), 1);
      };
      auto load_st = [&]() {
        mbar_wait(mb + B_AUX, 0);
#pragma unroll
        for (int i = 0; i < 4; i++) st[i >> 1][i & 1] = ld_rlx2((const uint2*)G.st1 + ((rb * 4 + wg * 2 + ((i >> 1) ^ hf)) * 2 + (warp >> 1)) * 96 + (warp & 1) * 16 + (i & 1) * 8 + g);
      };
      if (!wg) {
        wg_wait<0>();
        if (t128 < 2) mbar_arrive_rem(eb0 + 24);
        load_st();
#pragma unroll 1
        for (int s = 0; s < 4; s++) mbar_wait(mb + B_FULL + 8 * s, 1);
        bar_sync(6, 256);
      }
      static_for<0, 4>([&](auto sc) {
        constexpr int s = decltype(sc)::value;
        if (wg) mbar_wait(mb + B_FULL + 8 * s, 1);
        const uint32_t xs = (wg ? xoff(s, 1) : xoff(s, 0)) >> 4, ws = dlo(sb + woff(s) + WSTR, WSTR);
        pin(kv0); pin(kv1); pin(qa0); pin(qa1);
        wg_fence();
#pragma unroll
        for (int k = 0; k < 4; k++) {
          const uint64_t db = dsc<1024, 1>(ws + k * 128);
          wgmma_n128_ss<0, 1, 0>(kv0, dsc<1024, 1>(xs + xo0 + k * 2), db, 1);
          wgmma_n128_ss<0, 1, 0>(kv1, dsc<1024, 1>(xs + xo1 + k * 2), db, 1);
          if (k == 3 || (k == 2 && s == 0)) wg_commit();
          if (k == (s ? 3 : 2) && s < 3) {
            wg_wait<1>();
            if (s == 0) { if (wg && t128 < 2) mbar_arrive_rem(eb0 + 24); }
            else if (!wg) bar_arrive(8 + s, 256);
          }
        }
        if (s == STLD && wg) load_st();
      });
      center(qa0, kv0, st[0]);
      wg_commit();
      if (wg) bar_arrive(6, 256);
      float rl[2][2];
      uint32_t r2[2][2];
#pragma unroll
      for (int i = 0; i < 4; i++) { const float r = __uint_as_float(st[i >> 1][i & 1].y & ~255u); r2[i >> 1][i & 1] = pack2(r, r); rl[i >> 1][i & 1] = r * 1.4426950408889634f; }
      const uint32_t sad = sm + (wg ? 11 : 2) * SLOT_B + (warp * 16 + (lane & 15)) * 128 + (((lane >> 4) ^ (lane & 7)) << 4);
      wg_wait<0>();
      pin(kv0); pin(kv1); pin(qa0); pin(qa1); pin4(am);
      center(qa1, kv1, st[1]);
      wg_commit();
      if (wg) bar_arrive(11, 256);
      if (CUTS & 1) cut<2>(zero);
      TS(2);
      auto phi8 = [&](const float* a, int m) {
        return make_uint4(phi2(a[0], a[1], r2[m][0], rl[m][0]), phi2(a[2], a[3], r2[m][1], rl[m][1]), phi2(a[4], a[5], r2[m][0], rl[m][0]), phi2(a[6], a[7], r2[m][1], rl[m][1]));
      };
      auto stage = [&](float (&a)[64], auto mc) {
        constexpr int m = decltype(mc)::value;
        uint4 r[4];
#pragma unroll
        for (int j = 0; j < 4; j++) r[j] = phi8(a + j * 8, m);
        if (m == 0 || wg) bar_sync(wg ? 9 + m : 11, 256 + (r[SBAR].x & zero));
#pragma unroll
        for (int j = 0; j < 4; j++) {
          const int v = 32 + j * 8;
          stsm4_o<WSTR + m * 8192>(sad ^ (j << 5), hmul2(pack2(a[v], a[v + 1]), r2[m][0]), hmul2(pack2(a[v + 2], a[v + 3]), r2[m][1]),
                                                   hmul2(pack2(a[v + 4], a[v + 5]), r2[m][0]), hmul2(pack2(a[v + 6], a[v + 7]), r2[m][1]));
        }
#pragma unroll
        for (int j = 0; j < 4; j++) stsm4_o<m * 8192>(sad ^ (j << 5), r[j].x, r[j].y, r[j].z, r[j].w);
      };
      stage(kv0, std::integral_constant<int, 0>{});
      wg_wait<0>();
      pin(kv1); pin(qa1); pin4(am);
      stage(kv1, std::integral_constant<int, 1>{});
      fence_async_smem();
      TS(3);
      uint32_t xr[8][4];
      auto load_xr = [&]() {
        const uint32_t xa = sm + hf * 8192 + (warp * 16 + (lane & 15)) * 128 + (((lane >> 4) ^ (lane & 7)) << 4);
#pragma unroll
        for (int q = 0; q < 8; q++) ldsm4_o<0>((xa ^ ((q & 3) << 5)) + xoff(rank * 2 + (q >> 2), wg), xr[q][0], xr[q][1], xr[q][2], xr[q][3]);
      };
      if (!wg) { bar_arrive(4, 256); load_xr(); }
      else {
        float ka[36];
#pragma unroll
        for (int i = 0; i < 36; i++) ka[i] = 0.f;
        auto kv_mma = [&](auto ic) {
          constexpr int i = decltype(ic)::value;
          constexpr uint32_t o = sb + (i < 8 ? 11 : 2) * SLOT_B + (i & 7) * 2048;
          wgmma_n72_ss<1, 1, 0>(ka, dsc<1024, 1>(dlo(o, 8192)), dsc<1024, 1>(dlo(o + WSTR, sb + OFF_STATS - o - WSTR)), i);
        };
        mbar_wait(mb + B_LATE, 0);
        bar_sync(3, 128);
        wg_fence();
        static_for<0, 8>(kv_mma);
        wg_commit();
        uint4* dst = &G.kvp[cg * 2304 + rb * 32];
        if (CUTS & 4) cut<3>(zero);
        load_xr();
        bar_sync(4, 256);
        static_for<8, 16>(kv_mma);
        wg_commit();
        if (QHOLD == 1) bar_arrive(8, 256);
        wg_wait<0>();
        pin(ka);
        if (QHOLD == 2) bar_arrive(8, 256);
        TS(4);
        if (warp < 2) {
          st_rlx4(dst + warp * 512 + lane, make_uint4(pack2(ka[0], ka[1]), pack2(ka[4], ka[5]), pack2(ka[8], ka[9]), pack2(ka[12], ka[13])));
          st_rlx4(dst + warp * 512 + 256 + lane, make_uint4(pack2(ka[2], ka[3]), pack2(ka[6], ka[7]), pack2(ka[10], ka[11]), pack2(ka[14], ka[15])));
        } else {
          st_rlx4(dst + warp * 512 + lane, make_uint4(pack2(ka[16], ka[17]), pack2(ka[20], ka[21]), pack2(ka[24], ka[25]), pack2(ka[28], ka[29])));
          st_rlx4(dst + warp * 512 + 256 + lane, make_uint4(pack2(ka[18], ka[19]), pack2(ka[22], ka[23]), pack2(ka[26], ka[27]), pack2(ka[30], ka[31])));
        }
        st_rlx((uint32_t*)(dst + 2048) + t128, pack2(ka[32], ka[34]));
        if (QHOLD == 3) bar_arrive(8, 256);
        if (t128 == 0) mbar_arrive(sm + bar3(60));
      }
      TS(5);
      uint32_t pq[16];
      auto q_mma = [&](float (&q)[32], uint32_t xo, int next) {
#pragma unroll 1
        for (int s = 0; s < 4; s++) {
          const uint32_t xs = (xoff(s, wg) >> 4) + xo, ws = dlo(sb + woff(s), 8192);
          pin(q);
          wg_fence();
#pragma unroll
          for (int k = 0; k < 4; k++) wgmma_n64_ss<0, 1, 0>(q, dsc<1024, 1>(xs + k * 2), dsc<1024, 1>(ws + k * 128), 1);
          wg_commit();
        }
        if (next) bar_arrive(next, 256);
        wg_wait<0>();
        pin(q);
      };
      auto q_phi = [&](float (&q)[32], int m) {
#pragma unroll
        for (int j = 0; j < 4; j++) { const uint4 r = phi8(q + j * 8, m); pq[j * 4] = r.x; pq[j * 4 + 1] = r.y; pq[j * 4 + 2] = r.z; pq[j * 4 + 3] = r.w; }
      };
      auto o_of = [&](uint4 (&o)[4], uint4* first, bool pub) {
        float oa[2][20];
#pragma unroll
        for (int i = 0; i < 40; i++) oa[i / 20][i % 20] = 0.f;
        wg_fence();
#pragma unroll
        for (int ks = 0; ks < 4; ks++) {
          wgmma_n40_rs<1, 0>(oa[ks >> 1], pq[ks * 4], pq[ks * 4 + 1], pq[ks * 4 + 2], pq[ks * 4 + 3], dsc<1024, 1>(dlo(sb + OFF_KVB + ks * 2048, 8192)), ks & 1);
          if (ks & 1) wg_commit();
        }
#pragma unroll
        for (int h = 0; h < 2; h++) {
          if (h) wg_wait<0>(); else wg_wait<1>();
          pin(oa[h]);
          const float (&d)[20] = oa[h];
          const float i0 = rcp(d[16] + 1e-6f), i1 = rcp(d[18] + 1e-6f);
#pragma unroll
          for (int k2 = 0; k2 < 2; k2++) {
            o[h * 2 + k2] = make_uint4(pack2(d[k2 * 8] * i0, d[k2 * 8 + 1] * i0), pack2(d[k2 * 8 + 2] * i1, d[k2 * 8 + 3] * i1),
                                       pack2(d[k2 * 8 + 4] * i0, d[k2 * 8 + 5] * i0), pack2(d[k2 * 8 + 6] * i1, d[k2 * 8 + 7] * i1));
            if (pub && h * 2 + k2 < NPUB) st_rlx4(first + (h * 2 + k2) * 1024, o[h * 2 + k2]);
          }
        }
#pragma unroll
        for (int i = 0; i < 16; i++) asm volatile("" : "+r"(pq[i]) :: "memory");
      };
      bar_sync(wg ? 7 : 8, 256);
      q_mma(qa1, xo1, wg ? 8 : 7);
      q_phi(qa1, 1);
      tid2 = __shfl_sync(~0u, tid, lane);
      uint32_t done = 0;
#pragma unroll
      for (int j = 0; j < 8; j++) done |= pq[2 * j] | pq[2 * j + 1] | xr[j][3];
      bar_sync(wg ? 7 : 8, 256 + (done & zero));
      q_mma(qa0, xo0, wg ? 0 : 7);
      if (t128 == 0) mbar_arrive(mb + B_EMPTY + 8 * wg);
      TS(6);
      {
        uint4 a, v[8];
        uint32_t z[8], zs;
        const int blk = warp * 2 + wg;
        mbar_wait(mb + B_KVL, 0);
        static_for<0, 8>([&](auto ic) { constexpr int i = decltype(ic)::value; v[i] = lds4_o<sb + 11 * SLOT_B + i * 512>(own + (blk + (blk & 4)) * 4096 + lane * 16); });
#pragma unroll
        for (int i = 0; i < 8; i++) z[i] = lds1(sm + 2 * SLOT_B + i * 512 + t128 * 4);
#pragma unroll 1
        for (int it = 0;; it++) {
          zs = hadd2(hadd2(hadd2(z[0], z[1]), hadd2(z[2], z[3])), hadd2(hadd2(z[4], z[5]), hadd2(z[6], z[7])));
          a = hadd8(hadd8(hadd8(v[0], v[1]), hadd8(v[2], v[3])), hadd8(hadd8(v[4], v[5]), hadd8(v[6], v[7])));
          TSV(20, it + 1);
          if (!__any_sync(~0u, hnan(hadd2(hadd2(hadd2(a.x, a.y), hadd2(a.z, a.w)), zs)))) break;
          uint32_t mm = 0;
#pragma unroll
          for (int i = 0; i < 8; i++) mm = max4(max(mm, z[i]), v[i]);
          if (!__any_sync(~0u, mm == SENT)) break;
#pragma unroll
          for (int i = 0; i < 8; i++) { v[i] = ld_rlx4(&G.kvp[cg * 2304 + blk * 256 + i * 32 + lane]); z[i] = ld_rlx((const uint32_t*)&G.kvp[cg * 2304 + 2048 + i * 32] + t128); }
          SPINCHK(it, 4);
        }
        TS(23);
        const uint32_t kb0 = sm + OFF_KVB + blk * 1024 + (lane & 7) * 128;
        stsm4(kb0 + (((lane >> 3) ^ (lane & 7)) << 4), a.x, a.y, a.z, a.w);
        asm volatile("stmatrix.sync.aligned.m8n8.x1.shared.b16 [%0], {%1};" :: "r"(kb0 + ((4 ^ (lane & 7)) << 4)), "r"(zs >> (16 * wg)) : "memory");
        fence_async_smem();
        bar_sync(12, 256);
      }
      TS(7);
      if (t128 == 0) mbar_arrive_rem((wg << 24) + sb + bar3(48));
      to = clk();
      o_of(abuf[1], &G.obuf[((mb3 ^ 1) * 64 + hf * 32 + c3) * 128 + (tid2 & 127)], true);
      TS(29);
      cut<4>(zero);
      pin(qa0);
      q_phi(qa0, 0);
      o_of(abuf[0], nullptr, false);
#pragma unroll
      for (int q = 0; q < 32; q++) { asm volatile("" : "+r"(xr[q >> 2][q & 3])); acc[q * 2] = bf_lo(xr[q >> 2][q & 3]); acc[q * 2 + 1] = bf_hi(xr[q >> 2][q & 3]); }
      pin(acc);
    }
    {
    const int t128 = tid2 & 127, lane = tid2 & 31, g = lane >> 2, t = lane & 3;
    uint4* const od0 = &G.obuf[(mb3 * 64 + cg * 4) * 128 + t128];
    TS(8);
    {
      const uint32_t la = own + wg * 8192 + t128 * 16, fa = sm + wg * 256;
#pragma unroll
      for (int i = 8; i < 16; i++) abuf[i >> 2][i & 3] = make_uint4(0, 0, 0, 0);
#pragma unroll 1
      for (int pp = 0; pp < 16; pp += 4) {
        static_for<0, 4>([&](auto jc) {
          constexpr int j = decltype(jc)::value;
          constexpr uint32_t ro = sb + (10 + ((j + 1) & 3)) * SLOT_B;
          const int p = pp + j;
          const uint32_t o1 = ((p + 1) >> 3) * 128 + ((p + 1) & 7) * 8;
          uint4 (&a)[4] = abuf[j];
          uint4 (&n)[4] = abuf[(j + 1) & 3];
          auto fetch = [&]() {
            mbar_wait(fa + bar3(0) + o1, 0);
            n[0] = lds4_o<ro>(la); n[1] = lds4_o<ro + 2048>(la); n[2] = lds4_o<ro + 4096>(la); n[3] = lds4_o<ro + 6144>(la);
          };
          const bool early = j == 3 ? pp < 12 : (j > 1 || pp > 0);
          const uint32_t bs = dlo(sb, 8192) + ((WO_SLOTS >> (4 * p)) & 15) * (SLOT_B >> 4);
          mbar_wait(mb + B_FULL3 + 8 * p, 0);
          if (early) fetch();
          if (p == 1) TS(28);
          if (p == 2) TS(9);
          pin(acc);
          wg_fence();
#pragma unroll
          for (int k = 0; k < 4; k++) wgmma_n128_rs<1, 0>(acc, a[k].x, a[k].y, a[k].z, a[k].w, dsc<1024, 1>(bs + k * 128), 1);
          wg_commit();
          if (j < 2 && pp == 0) {
            if (j == 0 && NPUB < 4) {
              delay(to, BDELAY);
#pragma unroll
              for (int k = NPUB; k < 4; k++) st_rlx4(&G.obuf[((mb3 ^ 1) * 64 + hf * 32 + c3) * 128 + t128 + k * 1024], n[k]);
            }
            if (j == 0) TS(24);
            fetch();
            if (j == 0) TS(27);
          }
          if (__any_sync(~0u, max(max4(max4(0, n[0]), n[1]), max4(max4(0, n[2]), n[3])) == SENT)) {
            int pl = p + 1; asm volatile("" : "+r"(pl));
            const uint4* q = &G.obuf[(mb3 * 64 + chunk_of(pl) * 4) * 128 + t128];
#pragma unroll 1
            for (int it = 0;; it++) {
#pragma unroll
              for (int i = 0; i < 4; i++) n[i] = ld_rlx4(q + i * 128);
              TSV(21, _ts | 1 << pl);
              if (!__any_sync(~0u, max(max4(max4(0, n[0]), n[1]), max4(max4(0, n[2]), n[3])) == SENT)) break;
              SPINCHK(it, 5);
            }
          }
          if (lane == 0 && p < 11) mbar_arrive_rem((wg << 24) + sb + bar3(48) + o1);
          wg_wait<1>();
          pin(acc);
#pragma unroll
          for (int i = 0; i < 4; i++) pin4(abuf[(j + 3) & 3][i]);
          if (j < 3 && pp == 0) {
#pragma unroll
            for (int k = 0; k < 4; k++) if (((W0POS >> (4 * k)) & 15) == j) st_rlx4(od0 + k * 128, abuf[0][k]);
          }
          if (lane == 0) mbar_arrive(sm + bar3(32) + (p >> 3) * 128 + (p & 7) * 8);
        });
      }
    }
    uint4 wb[4];
#pragma unroll
    for (int i = 0; i < 4; i++) wb[i] = lds4(sm + OFF_LNP + ((g & 1) ? t * 64 : 256) + i * 16);
    const float2 ah = lds2f(sm + OFF_MSC + 8);
    wg_wait<0>();
    pin(acc);
#pragma unroll
    for (int i = 0; i < 4; i++) pin4(abuf[3][i]);
    TS(10);
    const uint32_t msc = sm + OFF_MSC;
    uint32_t hp[8][4];
    {
      float se[2][4], q[4] = {0.f, 0.f, 0.f, 0.f};
#pragma unroll
      for (int i = 0; i < 8; i++) se[i >> 2][i & 3] = 0.f;
#pragma unroll
      for (int j = 0; j < 8; j++) {
#pragma unroll
        for (int i = 0; i < 4; i++) { const float a = acc[j * 8 + i * 2], c = acc[j * 8 + i * 2 + 1]; hp[j][i] = pack2(a, c); q[i] = fmaf(a, a, fmaf(c, c, q[i])); }
        mma16816(se[j & 1], hp[j], (j & 1) ? wb[j >> 1].z : wb[j >> 1].x, (j & 1) ? wb[j >> 1].w : wb[j >> 1].y);
      }
      const bool od = t & 1;
      const float q0 = q[0] + q[2], q1 = q[1] + q[3];
      float qq = (od ? q1 : q0) + __shfl_xor_sync(~0u, od ? q0 : q1, 1);
      qq += __shfl_xor_sync(~0u, qq, 2);
      const float ss = od ? se[0][2] + se[1][2] : se[0][0] + se[1][0], ee = od ? se[0][3] + se[1][3] : se[0][1] + se[1][1];
#pragma unroll 1
      for (int c = 0; c < 2; c++) {
        const int tr = __float_as_int(c ? ah.y : ah.x), slot = (rb * 2 + hf) * 2 + c;
        if ((tr >> 4) == wid) {
          const int sl = (tr & 7) * 4 + ((tr >> 3) & 1);
          const float s1 = __shfl_sync(~0u, ss, sl), s2 = __shfl_sync(~0u, qq, sl), s3 = __shfl_sync(~0u, ee, sl);
          red4(lane < 8, &G.cst[lane * 32 + slot], s1, s2, s3, c3 ? 1.f : (float)((mb3 * 64 + (tr & 63)) * 16 + 1));
          if (g == (tr & 7)) {
#pragma unroll
            for (int i = 0; i < 4; i++)
              st_rlx4(&G.hsel[slot * 128 + c3 * 16 + i * 4 + t], (tr & 8) ? make_uint4(hp[2 * i][1], hp[2 * i][3], hp[2 * i + 1][1], hp[2 * i + 1][3])
                                                                          : make_uint4(hp[2 * i][0], hp[2 * i][2], hp[2 * i + 1][0], hp[2 * i + 1][2]));
          }
        }
      }
      red4(t < 2, &G.st2[mb3 * 64 + warp * 16 + (t & 1) * 8 + g], ss, qq, ee, 1.f);
      if (lane == 0) mbar_arrive(sm + bar3(61));
      TS(11);
    }
    uint32_t wa[32][4], wd[8][2][4];
    const uint32_t ga = own + ((lane >> 3) & 1) * 8192 + ((lane >> 4) * 8 + (lane & 7)) * 64 + ((warp ^ ((lane >> 1) & 3)) << 4);
    const uint32_t dw = sm + ((D_SLOTS >> (2 * (wid & 6))) & 15) * SLOT_B + (wid & 1) * 8192;
    const uint32_t da = dw + ((lane >> 4) * 8 + (lane & 7)) * 128 + ((((lane >> 3) & 1) ^ (lane & 7)) << 4);
    const uint32_t xl = own + ((lane & 16) ? 12 + wg : wg ? DS1 : DS0) * SLOT_B + (lane & 8) * 1024 + (lane & 7) * 16;
    float ya[8][4];
    int pass = 0;
    auto load_gu = [&](int f) {
      const uint32_t ad = ga + ((GU_SLOTS >> (16 * wg + 4 * f)) & 15) * SLOT_B;
      static_for<0, 8>([&](auto ic) { constexpr int i = decltype(ic)::value; ldsm4t_o<sb + i * 1024>(ad, wa[f * 8 + i]); });
    };
    if (fidx >= 0) mbar_wait(mb + B_FULL, 0);
    load_gu(0); load_gu(1);
    {
      bar_sync(1, 256);
      const uint32_t ha = sm + HST + wid * 4096 + (lane & 15) * 256 + (((lane >> 4) ^ (lane & 7)) << 4);
      static_for<0, 8>([&](auto jc) { constexpr int j = decltype(jc)::value; stsm4_o<(j >> 2) * 128>(ha ^ ((j & 3) << 5), hp[j][0], hp[j][1], hp[j][2], hp[j][3]); });
      asm volatile("fence.acq_rel.cta;" ::: "memory");
      __syncwarp();
      if (lane == 0) mbar_arrive(sm + bar3(62));
    }
    if (fidx >= 0) mbar_wait(mb + B_FFN, 1);
#pragma unroll 1
    for (;; pass++) {
      if (pass) { load_gu(0); load_gu(1); }
      load_gu(2);
      TS(15);
      mbar_wait(mb + B_SEL, 0);
      const uint4 sx = lds4(msc + 16 + pass * 32 + (lane & 16));
      TS(26);
      const uint4* xp = &G.hsel[sx.y * 128 + wid * 16 + (lane & 15)];
      uint4 xv = ld_rlx4(xp);
      load_gu(3);
      if (!pass) {
        if (fidx >= 0) mbar_wait(mb + B_FFN + 8, 0);
        static_for<0, 8>([&](auto ic) { constexpr int i = decltype(ic)::value; ldsm4t_o<(i & 1) * 2048>(da ^ ((i >> 1) << 5), wd[i >> 1][i & 1]); });
      }
#pragma unroll 1
      for (int it = 0; __any_sync(~0u, max4(0, xv) == SENT); it++) { xv = ld_rlx4(xp); SPINCHK(it, 7); }
      const float f = __uint_as_float(sx.z), n = __uint_as_float(sx.w);
      sts4(dw + ((lane & 12) * 2 + (lane >> 4) * 4 + t) * 16, pack2(fmaf(bf_lo(xv.x), f, n), fmaf(bf_hi(xv.x), f, n)), pack2(fmaf(bf_lo(xv.y), f, n), fmaf(bf_hi(xv.y), f, n)),
           pack2(fmaf(bf_lo(xv.z), f, n), fmaf(bf_hi(xv.z), f, n)), pack2(fmaf(bf_lo(xv.w), f, n), fmaf(bf_hi(xv.w), f, n)));
      if (wid == rb && (g & 3) == (cg >> 2)) sts4(msc + 96 + (lane >> 4) * 16 + t * 32, xv.x, xv.y, xv.z, xv.w);
      bar_sync(2 + wg, 128);
      TS(14);
      float gu[4][4];
#pragma unroll
      for (int i = 0; i < 16; i++) gu[i >> 2][i & 3] = 0.f;
      uint4 xb[4];
      static_for<0, 4>([&](auto ic) { constexpr int i = decltype(ic)::value; xb[i] = lds4_o<sb + i * 128>(xl); });
#pragma unroll
      for (int ks = 0; ks < 8; ks++) {
        if (ks == 6) {
#pragma unroll
          for (int j = 0; j < 8; j++) xb[3].x |= wd[4 + (j >> 1)][j & 1][3] & zero;
        }
#pragma unroll
        for (int j = 0; j < 4; j++) mma16816(gu[j], wa[j * 8 + ks], (ks & 1) ? xb[ks >> 1].z : xb[ks >> 1].x, (ks & 1) ? xb[ks >> 1].w : xb[ks >> 1].y);
        if (ks == 2) static_for<0, 8>([&](auto jc) { constexpr int j = decltype(jc)::value; ldsm4t_o<4096 + (j & 1) * 2048>(da ^ ((j >> 1) << 5), wd[4 + (j >> 1)][j & 1]); });
      }
      {
        float o[4];
#pragma unroll
        for (int j = 0; j < 4; j++) o[j] = t == 0 ? gu[0][j] : t == 1 ? gu[1][j] : t == 2 ? gu[2][j] : gu[3][j];
        const float e0 = ((t & 2) ? o[2] : o[0]) + __shfl_xor_sync(~0u, (t & 2) ? o[0] : o[2], 2), e1 = ((t & 2) ? o[3] : o[1]) + __shfl_xor_sync(~0u, (t & 2) ? o[1] : o[3], 2);
        sts1(sm + (wg ? DS1 : DS0) * SLOT_B + 1024 + t128 * 4, __float_as_uint(((t & 1) ? e1 : e0) + __shfl_xor_sync(~0u, (t & 1) ? e0 : e1, 1)));
      }
      TS(25);
      bar_sync(1, 256);
      const uint4 p0 = lds4_o<sb + DS0 * SLOT_B + 1024>(own + lane * 16), p1 = lds4_o<sb + DS1 * SLOT_B + 1024>(own + lane * 16);
      const float g0 = __uint_as_float(p0.x) + __uint_as_float(p1.x), g1 = __uint_as_float(p0.y) + __uint_as_float(p1.y);
      const float u0 = __uint_as_float(p0.z) + __uint_as_float(p1.z), u1 = __uint_as_float(p0.w) + __uint_as_float(p1.w);
      const uint32_t act = pack2(g0 * rcp(1.f + ex2(-1.4426950408889634f * g0)) * u0, g1 * rcp(1.f + ex2(-1.4426950408889634f * g1)) * u1);
      uint32_t bq[4];
#pragma unroll
      for (int i = 0; i < 4; i++) {
        const uint32_t lo = __shfl_sync(~0u, act, i * 8 + 2 * t), hi = __shfl_sync(~0u, act, i * 8 + 2 * t + 1);
        bq[i] = __byte_perm(lo, hi, (g & 1) ? 0x7632 : 0x5410);
      }
      TS(16);
#pragma unroll
      for (int i = 0; i < 8; i++) { ya[i][0] = 0.f; ya[i][1] = 0.f; ya[i][2] = 0.f; ya[i][3] = 0.f; }
#pragma unroll
      for (int ks = 0; ks < 2; ks++)
#pragma unroll
        for (int i = 0; i < 8; i++) mma16816(ya[i], wd[i][ks], bq[ks * 2], bq[ks * 2 + 1]);
      mbar_wait(mb + B_SEL2, 0);
      if (pass || !lds1(msc + 80)) break;
      bar_sync(1, 256);
    }
    if (fidx >= 0) {
      uint2* const yp = (uint2*)&G.ybuf[((wid * 16 + t * 2) * NFFN + fidx) * 4] + g;
#pragma unroll
      for (int h = 0; h < 2; h++) {
        float o[4];
#pragma unroll
        for (int j = 0; j < 4; j++) o[j] = t == 0 ? ya[h * 4][j] : t == 1 ? ya[h * 4 + 1][j] : t == 2 ? ya[h * 4 + 2][j] : ya[h * 4 + 3][j];
        st_rlx2(yp + h * (8 * NFFN * 8), __float_as_uint(o[0]), __float_as_uint(o[1]));
        st_rlx2(yp + h * (8 * NFFN * 8) + NFFN * 8, __float_as_uint(o[2]), __float_as_uint(o[3]));
      }
    }
    TS(17);
    const uint32_t ty = clk();
    if (wid < 7) {
      const uint4* const yq = &G.ybuf[b * NFFN * 4 + wid * 64 + lane];
      const uint4 sel = lds4(msc + 16 + pass * 32 + (lane & 1) * 16);
      const uint32_t fh = lds1(msc + 96 + (lane & 1) * 16 + (g & 3) * 32 + (cg & 3) * 4);
      const float r = __uint_as_float(sel.x ^ (~(uint32_t)((int)sel.x >> 31) | 0x80000000u));
      float sg = rcp(1.f + ex2(-1.4426950408889634f * r)), base = fmaf((lane & 2) ? bf_hi(fh) : bf_lo(fh), 1.f + __uint_as_float(sel.z), __uint_as_float(sel.w));
      __nv_bfloat16* op = P.out + (size_t)(2047 - (sel.x & 2047)) * D_ + b * 8 + ((lane >> 1) & 7);
      asm volatile("" : "+f"(sg), "+f"(base), "+l"(op) :: "memory");
      delay(ty, YDELAY);
      uint4 v0, v1;
#pragma unroll 1
      for (int it = 0;; it++) {
        v0 = ld_rlx4(yq); v1 = ld_rlx4(yq + 32);
        TSV(22, it + 1);
        if (!__any_sync(~0u, max(max4(0, v0), max4(0, v1)) == SENT)) break;
        SPINCHK(it, 8);
      }
      if (lane == 0) mbar_arrive(sm + bar3(63));
      TS(18);
      float y0 = __uint_as_float(v0.x) + __uint_as_float(v1.x), y1 = __uint_as_float(v0.y) + __uint_as_float(v1.y);
      float y2 = __uint_as_float(v0.z) + __uint_as_float(v1.z), y3 = __uint_as_float(v0.w) + __uint_as_float(v1.w);
      float z0 = ((lane & 16) ? y2 : y0) + __shfl_xor_sync(~0u, (lane & 16) ? y0 : y2, 16), z1 = ((lane & 16) ? y3 : y1) + __shfl_xor_sync(~0u, (lane & 16) ? y1 : y3, 16);
      z0 = ((lane & 8) ? z1 : z0) + __shfl_xor_sync(~0u, (lane & 8) ? z0 : z1, 8);
      z0 += __shfl_xor_sync(~0u, z0, 4);
      const uint32_t yx = sm + OFF_COLSUM;
      if (!(lane & 4)) sts1(yx + (t * 4 + (lane >> 3)) * 32 + wid * 4, __float_as_uint(z0));
      if (wid) bar_arrive(1, 224);
      else {
        bar_sync(1, 224);
        const uint4 a = lds4(yx + (lane & 15) * 32), c = lds4(yx + (lane & 15) * 32 + 16);
        const float y = ((__uint_as_float(a.x) + __uint_as_float(a.y)) + (__uint_as_float(a.z) + __uint_as_float(a.w))) + ((__uint_as_float(c.x) + __uint_as_float(c.y)) + __uint_as_float(c.z));
        if (lane < 16) *op = __float2bfloat16(fmaf(y, sg, base));
        if (b == 0 && lane == 16) G.epoch = lds1(mb + B_SW + 4);
      }
    }
    }
    TS(19); TSG(31);
    if (warp == 0) TS_DUMP(wg);
  }
}

typedef CUresult (*EncodeFn)(CUtensorMap*, CUtensorMapDataType, cuuint32_t, void*, const cuuint64_t*, const cuuint64_t*, const cuuint32_t*,
                             const cuuint32_t*, CUtensorMapInterleave, CUtensorMapSwizzle, CUtensorMapL2promotion, CUtensorMapFloatOOBfill);
void make_map(EncodeFn enc, CUtensorMap* m, const void* p, uint64_t cols, uint64_t rows, uint64_t d0, uint32_t b0, uint32_t b1, uint32_t b2, CUtensorMapSwizzle sw,
              CUtensorMapL2promotion promo = CU_TENSOR_MAP_L2_PROMOTION_L2_128B) {
  cuuint64_t dims[3] = {d0, rows, cols / d0}, str[2] = {cols * 2, d0 * 2};
  cuuint32_t box[3] = {b0, b1, b2}, es[3] = {1, 1, 1};
  enc(m, CU_TENSOR_MAP_DATA_TYPE_BFLOAT16, b2 ? 3 : 2, const_cast<void*>(p), dims, str, box, es, CU_TENSOR_MAP_INTERLEAVE_NONE, sw,
      promo, CU_TENSOR_MAP_FLOAT_OOB_FILL_NONE);
}

}

extern "C" void kernel_launch(void* const* d_in, const int* in_sizes, int n_in, void* d_out, int out_size) {
  (void)in_sizes; (void)n_in; (void)out_size;
  Ptrs P;
  P.x = (const __nv_bfloat16*)d_in[0]; P.wqkv = (const __nv_bfloat16*)d_in[1]; P.wo = (const __nv_bfloat16*)d_in[2];
  P.wr = (const __nv_bfloat16*)d_in[4]; P.wg = (const __nv_bfloat16*)d_in[5]; P.wu = (const __nv_bfloat16*)d_in[6];
  P.wd = (const __nv_bfloat16*)d_in[7]; P.out = (__nv_bfloat16*)d_out;
  void* fn = nullptr;
  cudaDriverEntryPointQueryResult q;
  cudaGetDriverEntryPoint("cuTensorMapEncodeTiled", &fn, cudaEnableDefault, &q);
  EncodeFn enc = (EncodeFn)fn;
  CUtensorMap tmX, tmW, tmO, tmG, tmU, tmD, tmM, tmPG, tmPU, tmPD;
  make_map(enc, &tmX, P.x, D_, S_, D_, 64, 128, 0, CU_TENSOR_MAP_SWIZZLE_128B);
  make_map(enc, &tmW, P.wqkv, 3 * D_, D_, 3 * D_, 64, 64, 0, CU_TENSOR_MAP_SWIZZLE_128B);
  make_map(enc, &tmG, P.wg, F_, D_, F_, 32, 128, 0, CU_TENSOR_MAP_SWIZZLE_64B);
  make_map(enc, &tmU, P.wu, F_, D_, F_, 32, 128, 0, CU_TENSOR_MAP_SWIZZLE_64B);
  make_map(enc, &tmD, P.wd, D_, F_, 64, 64, 32, 4, CU_TENSOR_MAP_SWIZZLE_128B);
  make_map(enc, &tmPG, P.wg, F_, D_, F_, 8, 32, 0, CU_TENSOR_MAP_SWIZZLE_NONE);
  make_map(enc, &tmPU, P.wu, F_, D_, F_, 8, 32, 0, CU_TENSOR_MAP_SWIZZLE_NONE);
  make_map(enc, &tmPD, P.wd, 128, F_ * 8, 128, 8, 32, 0, CU_TENSOR_MAP_SWIZZLE_NONE, CU_TENSOR_MAP_L2_PROMOTION_L2_256B);
  for (int m = 0; m < 2; m++) {
    cuuint64_t dims[4] = {64, m ? 64u : 16u, m ? 16u : 64u, 16}, str[3] = {2 * D_, (m ? 128u : 32u) * D_, 128};
    cuuint32_t box[4] = {64, 16, 4, 2}, es[4] = {1, 1, 1, 1};
    enc(m ? &tmM : &tmO, CU_TENSOR_MAP_DATA_TYPE_BFLOAT16, 4, const_cast<__nv_bfloat16*>(P.wo), dims, str, box, es, CU_TENSOR_MAP_INTERLEAVE_NONE,
        CU_TENSOR_MAP_SWIZZLE_128B, CU_TENSOR_MAP_L2_PROMOTION_L2_128B, CU_TENSOR_MAP_FLOAT_OOB_FILL_NONE);
  }
  cudaFuncSetAttribute(fused_kernel, cudaFuncAttributeMaxDynamicSharedMemorySize, SMEM_BYTES);
  fused_kernel<<<NCTA, 384, SMEM_BYTES>>>(tmX, tmW, tmO, tmG, tmU, tmD, tmM, tmPG, tmPU, tmPD, P);
}
```

```cpp
#include <cuda_runtime.h>
#include <cuda.h>
#include <cuda_bf16.h>
#include <stdint.h>
#include <type_traits>

namespace {

constexpr int S_ = 2048, D_ = 1024, F_ = 3584;
constexpr int NCTA = 128, NFFN = 112;
constexpr uint32_t SENT = 0xFFFFFFFFu;
constexpr int SPIN_LIMIT = 1 << 20;

#define ADELAY 900
#define NPK 0x233333333333ull
#define KDELAY 800
#define SBAR 2
#define NOOUT 0
#define OHOLD 72
#define OUTEF 0
#define CUTS 0
#define EFO 0
#define EFWO 0
#define TMPF 1
#define INIF 0
#define DEV 0xFFEE
#define FDT 100
#define ASTEP 300
#define BDELAY 1500
#define LATEP 0x20
#define GEV 0xDCCB
#define PDS 2
#define D1POS 1
#define GUPOS 1
#define PD0 2
#define PDT 60
#define KORD 0xBA9F87E6D54C3210ull
#define SDELAY 450
#define LDELAY 500
#define NOSPEC 0
#define LOCK 1
#define STLD 2
#define RELK 1
#define PERT 5
#define QHOLD 3
#define CDELAY 0
#define YDELAY 500
#define EFX 0
#define EFW 1
#define EFF 1
#define GDELAY 800
#define PFST 1
#define W0N 2
constexpr uint32_t STAGE_B = 57344;
__host__ __device__ constexpr uint32_t xoff(int s, int w) { return ((0x87CA3651u >> (4 * (s + 4 * w))) & 15) * 16384; }
__host__ __device__ constexpr uint32_t woff(int s) { return (s < 2 ? 9 * 16384 : 0) + (s & 1) * 8192; }
constexpr uint32_t WSTR = 32768;
constexpr uint32_t OFF_BARS = 229376;
constexpr uint32_t OFF_COLSUM = 229632;
constexpr uint32_t OFF_STATS = 230400;
constexpr uint32_t SMEM_BYTES = 232448;
constexpr uint32_t B_FULL = 0, B_EMPTY = 32, B_AUX = 64, B_SEL2 = 72, B_KVL = 80, B_FULL3 = 88, B_SW = 216, B_OUT = 224, B_LATE = 232, B_SEL = B_FULL + 8, B_FFN = 240;
__host__ __device__ constexpr uint32_t o3(int p) { return p * 8 + (p & 8) * 8; }
__host__ __device__ constexpr uint32_t bar3(int i) { return OFF_STATS + 1024 + (i >> 3) * 128 + ((i & 32) ? 0 : 64) + (i & 7) * 8; }
constexpr uint32_t SLOT_B = 16384;
constexpr uint32_t sb = 1024;
constexpr uint32_t bars = sb + OFF_BARS;
constexpr uint64_t WO_SLOTS = 0x8794208794208794ull;
constexpr uint32_t GU_SLOTS = 0x35356161u, D_SLOTS = 0x9420, DS0 = D_SLOTS & 15, DS1 = (D_SLOTS >> 8) & 15;
constexpr uint32_t HST = 7 * SLOT_B;
constexpr uint32_t OFF_LNP = OFF_STATS;
constexpr uint32_t OFF_MSC = OFF_COLSUM + 512;
constexpr uint32_t OFF_KVB = 2 * SLOT_B + 8192;

struct Scratch {
  uint4 st1[64 * 48];
  uint4 csp[16 * 8 * 48];
  uint4 kvp[16 * 2304];
  uint4 obuf[32 * 64 * 128];
  uint4 st2[S_];
  uint32_t pred[S_];
  uint4 cst[8 * 32];
  uint4 hsel[64 * 128];
  uint32_t cand[8 * 32];
  uint4 ybuf[NCTA * NFFN * 4];
  unsigned epoch;
};
__device__ __align__(1024) Scratch G;
#define TS_DECL
#define TS(i)
#define TSG(i)
#define TSV(i, v)
#define TS_DUMP(slot)
#define PTS(i)

__device__ __forceinline__ uint32_t smem_u32(const void* p) { return (uint32_t)__cvta_generic_to_shared(p); }
__device__ __forceinline__ void mbar_init(uint32_t bar, uint32_t cnt) { asm volatile("mbarrier.init.shared::cta.b64 [%0], %1;" :: "r"(bar), "r"(cnt) : "memory"); }
__device__ __forceinline__ void mbar_expect_tx(uint32_t bar, uint32_t bytes) { asm volatile("mbarrier.arrive.expect_tx.shared::cta.b64 _, [%0], %1;" :: "r"(bar), "r"(bytes) : "memory"); }
__device__ __forceinline__ void mbar_arrive(uint32_t bar) { asm volatile("mbarrier.arrive.shared::cta.b64 _, [%0];" :: "r"(bar) : "memory"); }
#define SPINCHK(it, code) if ((it) > SPIN_LIMIT) break
__device__ __forceinline__ void mbar_wait(uint32_t bar, uint32_t parity) {
  asm volatile("{\n.reg .pred p;\n.reg .u32 c;\nmov.u32 c, 0;\n"
               "WL:\nmbarrier.try_wait.parity.shared::cta.b64 p, [%0], %1;\n@p bra WD;\n"
               "add.u32 c, c, 1;\nsetp.lt.u32 p, c, 1048576;\n@p bra WL;\nWD:\n}" :: "r"(bar), "r"(parity) : "memory");
}
__device__ __forceinline__ uint64_t l2_stream() { uint64_t p; asm("createpolicy.fractional.L2::evict_first.b64 %0, 1.0;" : "=l"(p)); return p; }
__device__ __forceinline__ void tma_2d(uint32_t dst, const CUtensorMap* tm, int c0, int c1, uint32_t bar, bool stream) {
  if (stream) asm volatile("cp.async.bulk.tensor.2d.shared::cluster.global.mbarrier::complete_tx::bytes.L2::cache_hint [%0], [%1, {%3, %4}], [%2], %5;"
                           :: "r"(dst), "l"(tm), "r"(bar), "r"(c0), "r"(c1), "l"(l2_stream()) : "memory");
  else asm volatile("cp.async.bulk.tensor.2d.shared::cluster.global.mbarrier::complete_tx::bytes [%0], [%1, {%3, %4}], [%2];"
                    :: "r"(dst), "l"(tm), "r"(bar), "r"(c0), "r"(c1) : "memory");
}
__device__ __forceinline__ void tma_3d(uint32_t dst, const CUtensorMap* tm, int c0, int c1, int c2, uint32_t bar, bool stream) {
  if (stream) asm volatile("cp.async.bulk.tensor.3d.shared::cluster.global.mbarrier::complete_tx::bytes.L2::cache_hint [%0], [%1, {%3, %4, %5}], [%2], %6;"
                           :: "r"(dst), "l"(tm), "r"(bar), "r"(c0), "r"(c1), "r"(c2), "l"(l2_stream()) : "memory");
  else asm volatile("cp.async.bulk.tensor.3d.shared::cluster.global.mbarrier::complete_tx::bytes [%0], [%1, {%3, %4, %5}], [%2];"
                    :: "r"(dst), "l"(tm), "r"(bar), "r"(c0), "r"(c1), "r"(c2) : "memory");
}
__device__ __forceinline__ void tma_2d_mc(uint32_t dst, const CUtensorMap* tm, int c0, int c1, uint32_t bar, bool stream) {
  if (stream) asm volatile("cp.async.bulk.tensor.2d.shared::cluster.global.mbarrier::complete_tx::bytes.multicast::cluster.L2::cache_hint [%0], [%1, {%3, %4}], [%2], %5, %6;"
                           :: "r"(dst), "l"(tm), "r"(bar), "r"(c0), "r"(c1), "h"((uint16_t)3), "l"(l2_stream()) : "memory");
  else asm volatile("cp.async.bulk.tensor.2d.shared::cluster.global.mbarrier::complete_tx::bytes.multicast::cluster [%0], [%1, {%3, %4}], [%2], %5;"
                    :: "r"(dst), "l"(tm), "r"(bar), "r"(c0), "r"(c1), "h"((uint16_t)3) : "memory");
}
__device__ __forceinline__ bool elect_one() {
  uint32_t p;
  asm volatile("{\n.reg .pred q;\nelect.sync _|q, 0xFFFFFFFF;\nselp.u32 %0, 1, 0, q;\n}" : "=r"(p));
  return p;
}
__device__ __forceinline__ void bulk_load_mc(uint32_t dst, const void* src, uint32_t bar, uint16_t mask) {
  if (EFO) asm volatile("cp.async.bulk.shared::cluster.global.mbarrier::complete_tx::bytes.multicast::cluster.L2::cache_hint [%0], [%1], 8192, [%2], %3, %4;"
               :: "r"(dst), "l"(src), "r"(bar), "h"(mask), "l"(l2_stream()) : "memory");
  else asm volatile("cp.async.bulk.shared::cluster.global.mbarrier::complete_tx::bytes.multicast::cluster [%0], [%1], 8192, [%2], %3;"
               :: "r"(dst), "l"(src), "r"(bar), "h"(mask) : "memory");
}
__device__ __forceinline__ void bulk_load(uint32_t dst, const void* src, uint32_t bytes, uint32_t bar) {
  asm volatile("cp.async.bulk.shared::cluster.global.mbarrier::complete_tx::bytes [%0], [%1], %2, [%3];" :: "r"(dst), "l"(src), "r"(bytes), "r"(bar) : "memory");
}
__device__ __forceinline__ void mbar_arrive_rem(uint32_t bar) { asm volatile("mbarrier.arrive.shared::cluster.b64 _, [%0];" :: "r"(bar) : "memory"); }
template <uint32_t O> __device__ __forceinline__ void ldsm4_o(uint32_t addr, uint32_t& a, uint32_t& b, uint32_t& c, uint32_t& d) {
  asm volatile("ldmatrix.sync.aligned.m8n8.x4.shared.b16 {%0,%1,%2,%3}, [%4+%5];" : "=r"(a), "=r"(b), "=r"(c), "=r"(d) : "r"(addr), "n"(O) : "memory");
}
template <uint32_t O> __device__ __forceinline__ void ldsm4t_o(uint32_t addr, uint32_t (&r)[4]) {
  asm volatile("ldmatrix.sync.aligned.m8n8.x4.trans.shared.b16 {%0,%1,%2,%3}, [%4+%5];" : "=r"(r[0]), "=r"(r[1]), "=r"(r[2]), "=r"(r[3]) : "r"(addr), "n"(O) : "memory");
}
__device__ __forceinline__ void mma16816(float (&c)[4], const uint32_t (&a)[4], uint32_t b0, uint32_t b1) {
  asm("mma.sync.aligned.m16n8k16.row.col.f32.bf16.bf16.f32 {%0,%1,%2,%3}, {%4,%5,%6,%7}, {%8,%9}, {%0,%1,%2,%3};"
      : "+f"(c[0]), "+f"(c[1]), "+f"(c[2]), "+f"(c[3]) : "r"(a[0]), "r"(a[1]), "r"(a[2]), "r"(a[3]), "r"(b0), "r"(b1));
}
__device__ __forceinline__ void l2_prefetch(const void* p) { asm volatile("prefetch.global.L2 [%0];" :: "l"(p) : "memory"); }
__device__ __forceinline__ uint32_t clk() { uint32_t t; asm volatile("mov.u32 %0, %%clock;" : "=r"(t) :: "memory"); return t; }
__device__ __forceinline__ void delay(uint32_t t0, uint32_t n) { while (clk() - t0 < n) {} }
template <int ID> __device__ __forceinline__ void cut(uint32_t zero) { asm volatile("{\n.reg .pred p;\nsetp.eq.u32 p, %0, %1;\nCUT:\n@p nanosleep.u32 1;\n@p bra.uni CUT;\n}" :: "r"(zero), "n"(ID) : "memory"); }
__device__ __forceinline__ void tmap_prefetch(const CUtensorMap* tm) { asm volatile("prefetch.tensormap [%0];" :: "l"(tm) : "memory"); }
__device__ __forceinline__ void wg_fence() { asm volatile("wgmma.fence.sync.aligned;" ::: "memory"); }
__device__ __forceinline__ void wg_commit() { asm volatile("wgmma.commit_group.sync.aligned;" ::: "memory"); }
template <int N> __device__ __forceinline__ void wg_wait() { asm volatile("wgmma.wait_group.sync.aligned %0;" :: "n"(N) : "memory"); }
template <int N> __device__ __forceinline__ void pin(float (&d)[N]) {
#pragma unroll
  for (int i = 0; i < N; i++) asm volatile("" : "+f"(d[i]) :: "memory");
}
__device__ __forceinline__ void pin4(uint4& v) { asm volatile("" : "+r"(v.x), "+r"(v.y), "+r"(v.z), "+r"(v.w) :: "memory"); }
template <uint32_t SBO, uint32_t SWZ> __device__ __forceinline__ uint64_t dsc(uint32_t lo) { return ((uint64_t)((SBO >> 4) | (SWZ << 30)) << 32) | lo; }
__host__ __device__ constexpr uint32_t dlo(uint32_t addr, uint32_t lbo) { return (addr >> 4) | ((lbo >> 4) << 16); }
__device__ __forceinline__ void bar_sync(int id, int n) { asm volatile("bar.sync %0, %1;" :: "r"(id), "r"(n) : "memory"); }
__device__ __forceinline__ void bar_arrive(int id, int n) { asm volatile("bar.arrive %0, %1;" :: "r"(id), "r"(n) : "memory"); }
__device__ __forceinline__ void fence_async_smem() { asm volatile("fence.proxy.async.shared::cta;" ::: "memory"); }
__device__ __forceinline__ void fence_gpu() { asm volatile("fence.acq_rel.gpu;" ::: "memory"); }
__device__ __forceinline__ uint4 ld_cg4(const void* p) { uint4 v; asm volatile("ld.global.cg.v4.u32 {%0,%1,%2,%3}, [%4];" : "=r"(v.x), "=r"(v.y), "=r"(v.z), "=r"(v.w) : "l"(p) : "memory"); return v; }
__device__ __forceinline__ uint4 ld_rlx4(const void* p) { uint4 v; asm volatile("ld.relaxed.gpu.global.v4.u32 {%0,%1,%2,%3}, [%4];" : "=r"(v.x), "=r"(v.y), "=r"(v.z), "=r"(v.w) : "l"(p) : "memory"); return v; }
__device__ __forceinline__ uint32_t ld_rlx(const void* p) { uint32_t v; asm volatile("ld.relaxed.gpu.global.u32 %0, [%1];" : "=r"(v) : "l"(p) : "memory"); return v; }
__device__ __forceinline__ void st_rlx4(void* p, uint4 v) { asm volatile("st.relaxed.gpu.global.v4.u32 [%0], {%1,%2,%3,%4};" :: "l"(p), "r"(v.x), "r"(v.y), "r"(v.z), "r"(v.w) : "memory"); }
__device__ __forceinline__ void st_rlx2(void* p, uint32_t a, uint32_t b) { asm volatile("st.relaxed.gpu.global.v2.u32 [%0], {%1,%2};" :: "l"(p), "r"(a), "r"(b) : "memory"); }
__device__ __forceinline__ void st_rlx(void* p, uint32_t a) { asm volatile("st.relaxed.gpu.global.u32 [%0], %1;" :: "l"(p), "r"(a) : "memory"); }
__device__ __forceinline__ void red4(bool on, void* p, float a, float b, float c, float d) {
  asm volatile("{\n.reg .pred q;\nsetp.ne.b32 q, %5, 0;\n@q red.relaxed.gpu.global.add.v4.f32 [%0], {%1,%2,%3,%4};\n}" :: "l"(p), "f"(a), "f"(b), "f"(c), "f"(d), "r"((int)on) : "memory");
}
__device__ __forceinline__ uint32_t pack2(float lo, float hi) { uint32_t r; asm("cvt.rn.bf16x2.f32 %0, %1, %2;" : "=r"(r) : "f"(hi), "f"(lo)); return r; }
__device__ __forceinline__ float bf_lo(uint32_t v) { return __uint_as_float(v << 16); }
__device__ __forceinline__ float bf_hi(uint32_t v) { return __uint_as_float(v & 0xFFFF0000u); }
__device__ __forceinline__ void stsm4(uint32_t addr, uint32_t a, uint32_t b, uint32_t c, uint32_t d) {
  asm volatile("stmatrix.sync.aligned.m8n8.x4.shared.b16 [%0], {%1,%2,%3,%4};" :: "r"(addr), "r"(a), "r"(b), "r"(c), "r"(d) : "memory");
}
template <uint32_t O> __device__ __forceinline__ void stsm4_o(uint32_t addr, uint32_t a, uint32_t b, uint32_t c, uint32_t d) {
  asm volatile("stmatrix.sync.aligned.m8n8.x4.shared.b16 [%0+%5], {%1,%2,%3,%4};" :: "r"(addr), "r"(a), "r"(b), "r"(c), "r"(d), "n"(O) : "memory");
}
__device__ __forceinline__ void sts4(uint32_t addr, uint32_t a, uint32_t b, uint32_t c, uint32_t d) { asm volatile("st.shared.v4.u32 [%0], {%1,%2,%3,%4};" :: "r"(addr), "r"(a), "r"(b), "r"(c), "r"(d) : "memory"); }
__device__ __forceinline__ void sts2f(uint32_t addr, float a, float b) { asm volatile("st.shared.v2.f32 [%0], {%1,%2};" :: "r"(addr), "f"(a), "f"(b) : "memory"); }
__device__ __forceinline__ void sts1(uint32_t addr, uint32_t a) { asm volatile("st.shared.u32 [%0], %1;" :: "r"(addr), "r"(a) : "memory"); }
__device__ __forceinline__ float2 lds2f(uint32_t addr) { float2 v; asm volatile("ld.shared.v2.f32 {%0,%1}, [%2];" : "=f"(v.x), "=f"(v.y) : "r"(addr) : "memory"); return v; }
template <uint32_t O> __device__ __forceinline__ float2 lds2f_o(uint32_t addr) { float2 v; asm volatile("ld.shared.v2.f32 {%0,%1}, [%2+%3];" : "=f"(v.x), "=f"(v.y) : "r"(addr), "n"(O) : "memory"); return v; }
template <int I, int N, class F> __device__ __forceinline__ void static_for(F&& f) { if constexpr (I < N) { f(std::integral_constant<int, I>{}); static_for<I + 1, N>(f); } }
__device__ __forceinline__ uint4 lds4(uint32_t addr) { uint4 v; asm volatile("ld.shared.v4.u32 {%0,%1,%2,%3}, [%4];" : "=r"(v.x), "=r"(v.y), "=r"(v.z), "=r"(v.w) : "r"(addr) : "memory"); return v; }
__device__ __forceinline__ uint32_t lds1(uint32_t addr) { uint32_t v; asm volatile("ld.shared.u32 %0, [%1];" : "=r"(v) : "r"(addr) : "memory"); return v; }
__device__ __forceinline__ float ex2(float x) { float y; asm("ex2.approx.ftz.f32 %0, %1;" : "=f"(y) : "f"(x)); return y; }
__device__ __forceinline__ uint32_t max4(uint32_t m, const uint4& v) { return __vimax3_u32(__vimax3_u32(m, v.x, v.y), v.z, v.w); }
__device__ __forceinline__ float rsq(float x) { float y; asm("rsqrt.approx.ftz.f32 %0, %1;" : "=f"(y) : "f"(x)); return y; }
__device__ __forceinline__ float rcp(float x) { float y; asm("rcp.approx.ftz.f32 %0, %1;" : "=f"(y) : "f"(x)); return y; }
__device__ __forceinline__ uint2 ld_rlx2(const void* p) { uint2 v; asm volatile("ld.relaxed.gpu.global.v2.u32 {%0,%1}, [%2];" : "=r"(v.x), "=r"(v.y) : "l"(p) : "memory"); return v; }
template <uint32_t O> __device__ __forceinline__ uint4 lds4_o(uint32_t addr) { uint4 v; asm volatile("ld.shared.v4.u32 {%0,%1,%2,%3}, [%4+%5];" : "=r"(v.x), "=r"(v.y), "=r"(v.z), "=r"(v.w) : "r"(addr), "n"(O) : "memory"); return v; }
__device__ __forceinline__ uint32_t hadd2(uint32_t a, uint32_t b) { uint32_t r; asm("add.rn.bf16x2 %0, %1, %2;" : "=r"(r) : "r"(a), "r"(b)); return r; }
__device__ __forceinline__ uint4 hadd8(const uint4& a, const uint4& b) { return make_uint4(hadd2(a.x, b.x), hadd2(a.y, b.y), hadd2(a.z, b.z), hadd2(a.w, b.w)); }
__device__ __forceinline__ bool hnan(uint32_t a) { return (a & 0x7FFF0000u) > 0x7F800000u; }
__device__ __forceinline__ uint32_t hfma2(uint32_t a, uint32_t b, uint32_t c) { uint32_t r; asm("fma.rn.bf16x2 %0, %1, %2, %3;" : "=r"(r) : "r"(a), "r"(b), "r"(c)); return r; }
__device__ __forceinline__ uint32_t ordered(float v) { const uint32_t u = __float_as_uint(v); return u ^ ((uint32_t)((int)u >> 31) | 0x80000000u); }
__device__ __forceinline__ uint32_t route(const uint4& v, float sw, int row, float2& pr) {
  const float mean = __uint_as_float(v.x) * (1.f / D_);
  pr.x = rsq(fmaxf(fmaf(-mean, mean, __uint_as_float(v.y) * (1.f / D_)), 0.f) + 1e-5f);
  pr.y = -mean * pr.x;
  return min(ordered(pr.x * fmaf(-mean, sw, __uint_as_float(v.z))) & ~2047u, 0xFFFFF000u) | (2047 - row);
}
__device__ __forceinline__ uint2 top2(uint32_t a, uint32_t b, uint32_t c, uint32_t d) {
  const uint32_t h0 = max(a, b), h1 = max(c, d), h = max(h0, h1), l = __vimax3_u32(min(h0, h1), min(a, b), min(c, d));
  const uint32_t m1 = __reduce_max_sync(~0u, h);
  return make_uint2(m1, __reduce_max_sync(~0u, h == m1 ? l : h));
}
__device__ __forceinline__ uint32_t hmul2(uint32_t a, uint32_t b) { uint32_t r; asm("mul.rn.bf16x2 %0, %1, %2;" : "=r"(r) : "r"(a), "r"(b)); return r; }
__device__ __forceinline__ uint32_t phi2(float u0, float u1, uint32_t r2, float rl) {
  uint32_t p, r;
  asm("cvt.rn.relu.bf16x2.f32 %0, %1, %2;" : "=r"(p) : "f"(u1), "f"(u0));
  asm("fma.rn.bf16x2 %0, %1, %2, %3;" : "=r"(r) : "r"(p), "r"(r2), "r"(pack2(__saturatef(ex2(u0 * rl) + 1e-6f), __saturatef(ex2(u1 * rl) + 1e-6f))));
  return r;
}

template<int TA, int TB, int OFF, int SZ> __device__ __forceinline__ void wgmma_n192_ss(float (&d)[SZ], uint64_t da, uint64_t db, int scale_d) {
  asm volatile("{\n.reg .pred p;\nsetp.ne.b32 p, %98, 0;\n"
    "wgmma.mma_async.sync.aligned.m64n192k16.f32.bf16.bf16 {%0,%1,%2,%3,%4,%5,%6,%7,%8,%9,%10,%11,%12,%13,%14,%15,%16,%17,%18,%19,%20,%21,%22,%23,%24,%25,%26,%27,%28,%29,%30,%31,%32,%33,%34,%35,%36,%37,%38,%39,%40,%41,%42,%43,%44,%45,%46,%47,%48,%49,%50,%51,%52,%53,%54,%55,%56,%57,%58,%59,%60,%61,%62,%63,%64,%65,%66,%67,%68,%69,%70,%71,%72,%73,%74,%75,%76,%77,%78,%79,%80,%81,%82,%83,%84,%85,%86,%87,%88,%89,%90,%91,%92,%93,%94,%95}, %96, %97, p, 1, 1, %99, %100;\n}\n"
    : "+f"(d[OFF+0]), "+f"(d[OFF+1]), "+f"(d[OFF+2]), "+f"(d[OFF+3]), "+f"(d[OFF+4]), "+f"(d[OFF+5]), "+f"(d[OFF+6]), "+f"(d[OFF+7]),
      "+f"(d[OFF+8]), "+f"(d[OFF+9]), "+f"(d[OFF+10]), "+f"(d[OFF+11]), "+f"(d[OFF+12]), "+f"(d[OFF+13]), "+f"(d[OFF+14]), "+f"(d[OFF+15]),
      "+f"(d[OFF+16]), "+f"(d[OFF+17]), "+f"(d[OFF+18]), "+f"(d[OFF+19]), "+f"(d[OFF+20]), "+f"(d[OFF+21]), "+f"(d[OFF+22]), "+f"(d[OFF+23]),
      "+f"(d[OFF+24]), "+f"(d[OFF+25]), "+f"(d[OFF+26]), "+f"(d[OFF+27]), "+f"(d[OFF+28]), "+f"(d[OFF+29]), "+f"(d[OFF+30]), "+f"(d[OFF+31]),
      "+f"(d[OFF+32]), "+f"(d[OFF+33]), "+f"(d[OFF+34]), "+f"(d[OFF+35]), "+f"(d[OFF+36]), "+f"(d[OFF+37]), "+f"(d[OFF+38]), "+f"(d[OFF+39]),
      "+f"(d[OFF+40]), "+f"(d[OFF+41]), "+f"(d[OFF+42]), "+f"(d[OFF+43]), "+f"(d[OFF+44]), "+f"(d[OFF+45]), "+f"(d[OFF+46]), "+f"(d[OFF+47]),
      "+f"(d[OFF+48]), "+f"(d[OFF+49]), "+f"(d[OFF+50]), "+f"(d[OFF+51]), "+f"(d[OFF+52]), "+f"(d[OFF+53]), "+f"(d[OFF+54]), "+f"(d[OFF+55]),
      "+f"(d[OFF+56]), "+f"(d[OFF+57]), "+f"(d[OFF+58]), "+f"(d[OFF+59]), "+f"(d[OFF+60]), "+f"(d[OFF+61]), "+f"(d[OFF+62]), "+f"(d[OFF+63]),
      "+f"(d[OFF+64]), "+f"(d[OFF+65]), "+f"(d[OFF+66]), "+f"(d[OFF+67]), "+f"(d[OFF+68]), "+f"(d[OFF+69]), "+f"(d[OFF+70]), "+f"(d[OFF+71]),
      "+f"(d[OFF+72]), "+f"(d[OFF+73]), "+f"(d[OFF+74]), "+f"(d[OFF+75]), "+f"(d[OFF+76]), "+f"(d[OFF+77]), "+f"(d[OFF+78]), "+f"(d[OFF+79]),
      "+f"(d[OFF+80]), "+f"(d[OFF+81]), "+f"(d[OFF+82]), "+f"(d[OFF+83]), "+f"(d[OFF+84]), "+f"(d[OFF+85]), "+f"(d[OFF+86]), "+f"(d[OFF+87]),
      "+f"(d[OFF+88]), "+f"(d[OFF+89]), "+f"(d[OFF+90]), "+f"(d[OFF+91]), "+f"(d[OFF+92]), "+f"(d[OFF+93]), "+f"(d[OFF+94]), "+f"(d[OFF+95])
    : "l"(da), "l"(db), "r"(scale_d), "n"(TA), "n"(TB));
}
template<int TA, int TB, int OFF, int SZ> __device__ __forceinline__ void wgmma_n128_ss(float (&d)[SZ], uint64_t da, uint64_t db, int scale_d) {
  asm volatile("{\n.reg .pred p;\nsetp.ne.b32 p, %66, 0;\n"
    "wgmma.mma_async.sync.aligned.m64n128k16.f32.bf16.bf16 {%0,%1,%2,%3,%4,%5,%6,%7,%8,%9,%10,%11,%12,%13,%14,%15,%16,%17,%18,%19,%20,%21,%22,%23,%24,%25,%26,%27,%28,%29,%30,%31,%32,%33,%34,%35,%36,%37,%38,%39,%40,%41,%42,%43,%44,%45,%46,%47,%48,%49,%50,%51,%52,%53,%54,%55,%56,%57,%58,%59,%60,%61,%62,%63}, %64, %65, p, 1, 1, %67, %68;\n}\n"
    : "+f"(d[OFF+0]), "+f"(d[OFF+1]), "+f"(d[OFF+2]), "+f"(d[OFF+3]), "+f"(d[OFF+4]), "+f"(d[OFF+5]), "+f"(d[OFF+6]), "+f"(d[OFF+7]),
      "+f"(d[OFF+8]), "+f"(d[OFF+9]), "+f"(d[OFF+10]), "+f"(d[OFF+11]), "+f"(d[OFF+12]), "+f"(d[OFF+13]), "+f"(d[OFF+14]), "+f"(d[OFF+15]),
      "+f"(d[OFF+16]), "+f"(d[OFF+17]), "+f"(d[OFF+18]), "+f"(d[OFF+19]), "+f"(d[OFF+20]), "+f"(d[OFF+21]), "+f"(d[OFF+22]), "+f"(d[OFF+23]),
      "+f"(d[OFF+24]), "+f"(d[OFF+25]), "+f"(d[OFF+26]), "+f"(d[OFF+27]), "+f"(d[OFF+28]), "+f"(d[OFF+29]), "+f"(d[OFF+30]), "+f"(d[OFF+31]),
      "+f"(d[OFF+32]), "+f"(d[OFF+33]), "+f"(d[OFF+34]), "+f"(d[OFF+35]), "+f"(d[OFF+36]), "+f"(d[OFF+37]), "+f"(d[OFF+38]), "+f"(d[OFF+39]),
      "+f"(d[OFF+40]), "+f"(d[OFF+41]), "+f"(d[OFF+42]), "+f"(d[OFF+43]), "+f"(d[OFF+44]), "+f"(d[OFF+45]), "+f"(d[OFF+46]), "+f"(d[OFF+47]),
      "+f"(d[OFF+48]), "+f"(d[OFF+49]), "+f"(d[OFF+50]), "+f"(d[OFF+51]), "+f"(d[OFF+52]), "+f"(d[OFF+53]), "+f"(d[OFF+54]), "+f"(d[OFF+55]),
      "+f"(d[OFF+56]), "+f"(d[OFF+57]), "+f"(d[OFF+58]), "+f"(d[OFF+59]), "+f"(d[OFF+60]), "+f"(d[OFF+61]), "+f"(d[OFF+62]), "+f"(d[OFF+63])
    : "l"(da), "l"(db), "r"(scale_d), "n"(TA), "n"(TB));
}
template<int TA, int TB, int OFF, int SZ> __device__ __forceinline__ void wgmma_n64_ss(float (&d)[SZ], uint64_t da, uint64_t db, int scale_d) {
  asm volatile("{\n.reg .pred p;\nsetp.ne.b32 p, %34, 0;\n"
    "wgmma.mma_async.sync.aligned.m64n64k16.f32.bf16.bf16 {%0,%1,%2,%3,%4,%5,%6,%7,%8,%9,%10,%11,%12,%13,%14,%15,%16,%17,%18,%19,%20,%21,%22,%23,%24,%25,%26,%27,%28,%29,%30,%31}, %32, %33, p, 1, 1, %35, %36;\n}\n"
    : "+f"(d[OFF+0]), "+f"(d[OFF+1]), "+f"(d[OFF+2]), "+f"(d[OFF+3]), "+f"(d[OFF+4]), "+f"(d[OFF+5]), "+f"(d[OFF+6]), "+f"(d[OFF+7]),
      "+f"(d[OFF+8]), "+f"(d[OFF+9]), "+f"(d[OFF+10]), "+f"(d[OFF+11]), "+f"(d[OFF+12]), "+f"(d[OFF+13]), "+f"(d[OFF+14]), "+f"(d[OFF+15]),
      "+f"(d[OFF+16]), "+f"(d[OFF+17]), "+f"(d[OFF+18]), "+f"(d[OFF+19]), "+f"(d[OFF+20]), "+f"(d[OFF+21]), "+f"(d[OFF+22]), "+f"(d[OFF+23]),
      "+f"(d[OFF+24]), "+f"(d[OFF+25]), "+f"(d[OFF+26]), "+f"(d[OFF+27]), "+f"(d[OFF+28]), "+f"(d[OFF+29]), "+f"(d[OFF+30]), "+f"(d[OFF+31])
    : "l"(da), "l"(db), "r"(scale_d), "n"(TA), "n"(TB));
}
template<int TB, int OFF, int SZ> __device__ __forceinline__ void wgmma_n64_rs(float (&d)[SZ], uint32_t a0, uint32_t a1, uint32_t a2, uint32_t a3, uint64_t db, int scale_d) {
  asm volatile("{\n.reg .pred p;\nsetp.ne.b32 p, %37, 0;\n"
    "wgmma.mma_async.sync.aligned.m64n64k16.f32.bf16.bf16 {%0,%1,%2,%3,%4,%5,%6,%7,%8,%9,%10,%11,%12,%13,%14,%15,%16,%17,%18,%19,%20,%21,%22,%23,%24,%25,%26,%27,%28,%29,%30,%31}, {%32,%33,%34,%35}, %36, p, 1, 1, %38;\n}\n"
    : "+f"(d[OFF+0]), "+f"(d[OFF+1]), "+f"(d[OFF+2]), "+f"(d[OFF+3]), "+f"(d[OFF+4]), "+f"(d[OFF+5]), "+f"(d[OFF+6]), "+f"(d[OFF+7]),
      "+f"(d[OFF+8]), "+f"(d[OFF+9]), "+f"(d[OFF+10]), "+f"(d[OFF+11]), "+f"(d[OFF+12]), "+f"(d[OFF+13]), "+f"(d[OFF+14]), "+f"(d[OFF+15]),
      "+f"(d[OFF+16]), "+f"(d[OFF+17]), "+f"(d[OFF+18]), "+f"(d[OFF+19]), "+f"(d[OFF+20]), "+f"(d[OFF+21]), "+f"(d[OFF+22]), "+f"(d[OFF+23]),
      "+f"(d[OFF+24]), "+f"(d[OFF+25]), "+f"(d[OFF+26]), "+f"(d[OFF+27]), "+f"(d[OFF+28]), "+f"(d[OFF+29]), "+f"(d[OFF+30]), "+f"(d[OFF+31])
    : "r"(a0), "r"(a1), "r"(a2), "r"(a3), "l"(db), "r"(scale_d), "n"(TB));
}
template<int TA, int TB, int OFF, int SZ> __device__ __forceinline__ void wgmma_n72_ss(float (&d)[SZ], uint64_t da, uint64_t db, int scale_d) {
  asm volatile("{\n.reg .pred p;\nsetp.ne.b32 p, %38, 0;\n"
    "wgmma.mma_async.sync.aligned.m64n72k16.f32.bf16.bf16 {%0,%1,%2,%3,%4,%5,%6,%7,%8,%9,%10,%11,%12,%13,%14,%15,%16,%17,%18,%19,%20,%21,%22,%23,%24,%25,%26,%27,%28,%29,%30,%31,%32,%33,%34,%35}, %36, %37, p, 1, 1, %39, %40;\n}\n"
    : "+f"(d[OFF+0]), "+f"(d[OFF+1]), "+f"(d[OFF+2]), "+f"(d[OFF+3]), "+f"(d[OFF+4]), "+f"(d[OFF+5]), "+f"(d[OFF+6]), "+f"(d[OFF+7]),
      "+f"(d[OFF+8]), "+f"(d[OFF+9]), "+f"(d[OFF+10]), "+f"(d[OFF+11]), "+f"(d[OFF+12]), "+f"(d[OFF+13]), "+f"(d[OFF+14]), "+f"(d[OFF+15]),
      "+f"(d[OFF+16]), "+f"(d[OFF+17]), "+f"(d[OFF+18]), "+f"(d[OFF+19]), "+f"(d[OFF+20]), "+f"(d[OFF+21]), "+f"(d[OFF+22]), "+f"(d[OFF+23]),
      "+f"(d[OFF+24]), "+f"(d[OFF+25]), "+f"(d[OFF+26]), "+f"(d[OFF+27]), "+f"(d[OFF+28]), "+f"(d[OFF+29]), "+f"(d[OFF+30]), "+f"(d[OFF+31]),
      "+f"(d[OFF+32]), "+f"(d[OFF+33]), "+f"(d[OFF+34]), "+f"(d[OFF+35])
    : "l"(da), "l"(db), "r"(scale_d), "n"(TA), "n"(TB));
}
template<int TB, int OFF, int SZ> __device__ __forceinline__ void wgmma_n40_rs(float (&d)[SZ], uint32_t a0, uint32_t a1, uint32_t a2, uint32_t a3, uint64_t db, int scale_d) {
  asm volatile("{\n.reg .pred p;\nsetp.ne.b32 p, %25, 0;\n"
    "wgmma.mma_async.sync.aligned.m64n40k16.f32.bf16.bf16 {%0,%1,%2,%3,%4,%5,%6,%7,%8,%9,%10,%11,%12,%13,%14,%15,%16,%17,%18,%19}, {%20,%21,%22,%23}, %24, p, 1, 1, %26;\n}\n"
    : "+f"(d[OFF+0]), "+f"(d[OFF+1]), "+f"(d[OFF+2]), "+f"(d[OFF+3]), "+f"(d[OFF+4]), "+f"(d[OFF+5]), "+f"(d[OFF+6]), "+f"(d[OFF+7]),
      "+f"(d[OFF+8]), "+f"(d[OFF+9]), "+f"(d[OFF+10]), "+f"(d[OFF+11]), "+f"(d[OFF+12]), "+f"(d[OFF+13]), "+f"(d[OFF+14]), "+f"(d[OFF+15]),
      "+f"(d[OFF+16]), "+f"(d[OFF+17]), "+f"(d[OFF+18]), "+f"(d[OFF+19])
    : "r"(a0), "r"(a1), "r"(a2), "r"(a3), "l"(db), "r"(scale_d), "n"(TB));
}
template<int TB, int OFF, int SZ> __device__ __forceinline__ void wgmma_n128_rs(float (&d)[SZ], uint32_t a0, uint32_t a1, uint32_t a2, uint32_t a3, uint64_t db, int scale_d) {
  asm volatile("{\n.reg .pred p;\nsetp.ne.b32 p, %69, 0;\n"
    "wgmma.mma_async.sync.aligned.m64n128k16.f32.bf16.bf16 {%0,%1,%2,%3,%4,%5,%6,%7,%8,%9,%10,%11,%12,%13,%14,%15,%16,%17,%18,%19,%20,%21,%22,%23,%24,%25,%26,%27,%28,%29,%30,%31,%32,%33,%34,%35,%36,%37,%38,%39,%40,%41,%42,%43,%44,%45,%46,%47,%48,%49,%50,%51,%52,%53,%54,%55,%56,%57,%58,%59,%60,%61,%62,%63}, {%64,%65,%66,%67}, %68, p, 1, 1, %70;\n}\n"
    : "+f"(d[OFF+0]), "+f"(d[OFF+1]), "+f"(d[OFF+2]), "+f"(d[OFF+3]), "+f"(d[OFF+4]), "+f"(d[OFF+5]), "+f"(d[OFF+6]), "+f"(d[OFF+7]),
      "+f"(d[OFF+8]), "+f"(d[OFF+9]), "+f"(d[OFF+10]), "+f"(d[OFF+11]), "+f"(d[OFF+12]), "+f"(d[OFF+13]), "+f"(d[OFF+14]), "+f"(d[OFF+15]),
      "+f"(d[OFF+16]), "+f"(d[OFF+17]), "+f"(d[OFF+18]), "+f"(d[OFF+19]), "+f"(d[OFF+20]), "+f"(d[OFF+21]), "+f"(d[OFF+22]), "+f"(d[OFF+23]),
      "+f"(d[OFF+24]), "+f"(d[OFF+25]), "+f"(d[OFF+26]), "+f"(d[OFF+27]), "+f"(d[OFF+28]), "+f"(d[OFF+29]), "+f"(d[OFF+30]), "+f"(d[OFF+31]),
      "+f"(d[OFF+32]), "+f"(d[OFF+33]), "+f"(d[OFF+34]), "+f"(d[OFF+35]), "+f"(d[OFF+36]), "+f"(d[OFF+37]), "+f"(d[OFF+38]), "+f"(d[OFF+39]),
      "+f"(d[OFF+40]), "+f"(d[OFF+41]), "+f"(d[OFF+42]), "+f"(d[OFF+43]), "+f"(d[OFF+44]), "+f"(d[OFF+45]), "+f"(d[OFF+46]), "+f"(d[OFF+47]),
      "+f"(d[OFF+48]), "+f"(d[OFF+49]), "+f"(d[OFF+50]), "+f"(d[OFF+51]), "+f"(d[OFF+52]), "+f"(d[OFF+53]), "+f"(d[OFF+54]), "+f"(d[OFF+55]),
      "+f"(d[OFF+56]), "+f"(d[OFF+57]), "+f"(d[OFF+58]), "+f"(d[OFF+59]), "+f"(d[OFF+60]), "+f"(d[OFF+61]), "+f"(d[OFF+62]), "+f"(d[OFF+63])
    : "r"(a0), "r"(a1), "r"(a2), "r"(a3), "l"(db), "r"(scale_d), "n"(TB));
}

struct Ptrs { const __nv_bfloat16 *x, *wqkv, *wo, *wr, *wg, *wu, *wd; __nv_bfloat16* out; };

__global__ void __cluster_dims__(2, 1, 1) __launch_bounds__(384, 1) fused_kernel(const __grid_constant__ CUtensorMap tmX, const __grid_constant__ CUtensorMap tmW,
                                                       const __grid_constant__ CUtensorMap tmO, const __grid_constant__ CUtensorMap tmG,
                                                       const __grid_constant__ CUtensorMap tmU, const __grid_constant__ CUtensorMap tmD,
                                                       const __grid_constant__ CUtensorMap tmM, const __grid_constant__ CUtensorMap tmPG,
                                                       const __grid_constant__ CUtensorMap tmPU, const __grid_constant__ CUtensorMap tmPD,
                                                       const Ptrs P) {
  extern __shared__ __align__(1024) uint8_t smem_raw[];
  if (TMPF && threadIdx.x == 0) { tmap_prefetch(&tmX); tmap_prefetch(&tmW); }
  const int tid = threadIdx.x, wid = __shfl_sync(~0u, tid >> 5, 0), wg = __shfl_sync(~0u, tid >> 7, 0), lane = tid & 31;
  const int pj = blockIdx.x >> 1, pi = pj - 36;
  const int b = (pj < 4 ? 32 + pj * 8 : pj < 36 ? pj - 4 : 33 + pi + ((pi * 37) >> 8)) * 2 + (blockIdx.x & 1);
  const int rb = b >> 4, cg = b & 15, hf = cg >> 3, c3 = cg & 7;
  const int jp = cg >> 1;
  const int fidx = jp == rb ? -1 : b - 2 * rb - (jp > rb ? 2 : 0);
  const uint32_t rank = b & 1, own = rank << 24;
  const uint32_t zero = gridDim.y - 1;
  const uint32_t sm = own + sb, mb = own + bars;
  auto chunk_of = [&](int p) { return (int)((0x1765432FEDCBA980ull >> (4 * p)) & 15) ^ (p == 0 || p == 15 ? cg : p < 9 ? cg & 8 : cg & 14); };
  const int kl = (jp & 3) * 256;
  auto k_of = [&](int kb) { return kb >= 12 ? kl + (kb - 12) * 64 : kb * 64 < kl ? kb * 64 : kb * 64 + 256; };
  auto load_w = [&](int kb) {
#pragma unroll
    for (int i = 0; i < 3; i++) tma_2d(sm + woff(kb & 3) + i * WSTR, &tmW, i * D_ + cg * 64, k_of(kb), mb + B_FULL + 8 * (kb & 3), EFW);
  };
  TS_DECL; TS(0); TSG(30);
  if (wid == 8) {
    if (elect_one()) {
      if (smem_u32(smem_raw) != sm) {
#pragma unroll
        for (int i = 0; i < PERT; i++) sts1(mb, lds1(mb));
        asm volatile("trap;");
      }
#pragma unroll
      for (int s = 0; s < 4; s++) mbar_init(mb + B_FULL + 8 * s, 1);
      asm volatile("fence.mbarrier_init.release.cluster;" ::: "memory");
      if (INIF) fence_async_smem();
    }
  } else if (wid == 9) {
    if (elect_one()) {
#pragma unroll
      for (int i = 4; i < 32; i++)
        if (i != 27) mbar_init(mb + 8 * i, i < 8 ? 8 : i == 8 ? 64 : i == 26 ? 2 : i == 29 ? 4 : 1);
      asm volatile("fence.mbarrier_init.release.cluster;" ::: "memory");
      if (INIF) fence_async_smem();
    }
  }
  __syncwarp();
  asm volatile("barrier.cluster.arrive.relaxed.aligned;" ::: "memory");
  if (wid == 8) {
    if (elect_one()) {
      mbar_expect_tx(mb + B_FULL, STAGE_B);
      tma_2d(sm + xoff(0, 0), &tmX, k_of(0), rb * 256, mb + B_FULL, EFX);
      tma_2d(sm + xoff(0, 1), &tmX, k_of(0), rb * 256 + 128, mb + B_FULL, EFX);
      load_w(0);
    }
    __syncwarp();
  }
  asm volatile("barrier.cluster.wait.aligned;" ::: "memory");

  if (wg == 2) {
    asm volatile("setmaxnreg.dec.sync.aligned.u32 56;");
    auto wait3 = [&](int i) { mbar_wait(sm + bar3(i), 0); };
    if (wid == 8) {
      if (elect_one()) {
        int np = fidx >= 0 ? 0 : 32;
        if (fidx >= 0) mbar_expect_tx(mb + B_FFN, 32 * 512);
#pragma unroll 1
        for (int kb = 1; kb < 16; kb++) {
          const uint32_t fb = mb + B_FULL + 8 * (kb & 3);
          mbar_wait(fb + B_EMPTY, ((kb >> 2) & 1) ^ 1);
          mbar_expect_tx(fb, STAGE_B);
          tma_2d_mc(sm + xoff(kb & 3, rank), &tmX, k_of(kb), rb * 256 + rank * 128, fb, EFX);
          load_w(kb);
          if (kb >= 12) asm volatile("mbarrier.arrive.shared::cta.b64 _, [%0], 7;" :: "r"(fb + B_EMPTY) : "memory");
#pragma unroll 1
          for (int n = ((NPK << 16) >> (4 * kb)) & 15; n > 0 && np < 32; n--, np++)
            tma_2d(sm + OFF_STATS + 512, (np & 1) ? &tmPU : &tmPG, (fidx >> 1) * 64, (np >> 1) * 64 + rank * 32, mb + B_FFN, false);
        }
        if (fidx >= 0) { mbar_wait(mb + B_FFN, 0); mbar_expect_tx(mb + B_FFN, 65536 + 8 * 512); mbar_expect_tx(mb + B_FFN + 8, 65536); }
#pragma unroll
        for (int p = 4; p < 8; p++) sts4(sm + OFF_STATS + p * 144, 0x3F803F80u, 0x3F803F80u, 0x3F803F80u, 0x3F803F80u);
        fence_async_smem();
        mbar_arrive(mb + B_LATE);
        PTS(2);
        mbar_expect_tx(mb + B_KVL, 36864);
        mbar_wait(mb + B_LATE, 0);
        wait3(60);
        delay(clk(), KDELAY);
        bulk_load(sm + 11 * SLOT_B, &G.kvp[cg * 2304], SLOT_B, mb + B_KVL);
        bulk_load(sm + 13 * SLOT_B, &G.kvp[cg * 2304 + 1024], SLOT_B, mb + B_KVL);
        bulk_load(sm + 2 * SLOT_B, &G.kvp[cg * 2304 + 2048], 4096, mb + B_KVL);
        PTS(3);
        const uint4* src = &G.obuf[(rb * 4 + rank * 2 + hf) * 64 * 128];
        wait3(48);
        const uint32_t t1 = clk();
#pragma unroll
        for (int p = 1; p < 5; p++) {
          delay(t1, ADELAY + (p - 1) * ASTEP);
          bulk_load_mc(sm + (10 + (p & 3)) * SLOT_B + rank * 8192, src + ((hf ^ 1) * 8 + p - 1) * 512, sm + bar3(p) + rank * 256, 3);
        }
        PTS(7);
#pragma unroll 1
        for (int i = 5; i < 17; i++) {
          const int p = min(i, 15);
          const uint32_t d = sm + (10 + (p & 3)) * SLOT_B + rank * 8192, fb = sm + bar3(0) + o3(p) + rank * 256;
          const uint4* q = src + chunk_of(i & 15) * 512;
          mbar_wait(sm + bar3(48) + o3(p - 4 + ((LATEP >> p) & 1)), 0);
          bulk_load_mc(d, q, fb, i < 15 ? 3 : 1 << ((i ^ rank ^ 1) & 1));
        }
        PTS(15);
      }
    } else {
      const int r4 = lane >> 3, c8 = lane & 7;
      const uint32_t eb = (lane << 24) + bars + B_EMPTY;
      auto tagged = [](float v, uint32_t tag) { return ((__float_as_uint(v) + 128) & ~255u) | tag; };
      auto gather = [&](uint32_t tag) {
        const int q = (wid - 9) * 24 + lane;
        const uint4* cp = lane < 24 ? &G.csp[cg * 8 * 48 + q] : &G.st1[rb * 8 * 48 + (wid - 9) * 8 + lane - 24];
        uint4 v[8];
        delay(clk(), GDELAY);
#pragma unroll 1
        for (int it = 0;; it++) {
#pragma unroll
          for (int i = 0; i < 8; i++) v[i] = ld_rlx4(cp + i * 48);
          uint32_t x = 0;
#pragma unroll
          for (int i = 0; i < 8; i++) { v[i].x ^= tag; v[i].y ^= tag; v[i].z ^= tag; v[i].w ^= tag; x |= v[i].x | v[i].y | v[i].z | v[i].w; }
          if (!__any_sync(~0u, (x & 255) != 0)) break;
          SPINCHK(it, 3);
        }
        float c[4] = {0.f, 0.f, 0.f, 0.f};
#pragma unroll
        for (int i = 0; i < 8; i++) { c[0] += __uint_as_float(v[i].x); c[1] += __uint_as_float(v[i].y); c[2] += __uint_as_float(v[i].z); c[3] += __uint_as_float(v[i].w); }
        const uint32_t h0 = pack2(c[0], c[1]), h1 = pack2(c[2], c[3]), ca = sm + OFF_COLSUM + (q >> 1) * 32 + (q & 1) * 8;
        if (lane < 24) {
          sts2f(ca, __uint_as_float(h0), __uint_as_float(h1));
          sts2f(ca + 16, __uint_as_float(pack2(c[0] - bf_lo(h0), c[1] - bf_hi(h0))), __uint_as_float(pack2(c[2] - bf_lo(h1), c[3] - bf_hi(h1))));
        }
        fence_async_smem();
        mbar_arrive(mb + B_AUX);
      };
      const int r2 = lane >> 4, c16 = lane & 15;
      float a[12];
#pragma unroll
      for (int i = 0; i < 12; i++) a[i] = 0.f;
      auto kb_of = [](int it) { return (int)(KORD >> (4 * it)) & 15; };
      if (wid == 9) {
        const uint32_t a0 = sm + rb * 1024 + r2 * 128 + (((c16 >> 1) ^ r2) << 4) + (c16 & 1) * 8;
        const uint2* gw = (const uint2*)(P.wqkv + (kl + rb * 8 + r2) * 3072 + cg * 64) + c16;
#pragma unroll 1
        for (int it = 0; it < 16; it++) {
          uint2 w[12];
          const int kb = kb_of(it);
          if (kb >= 12) {
#pragma unroll
            for (int j = 0; j < 12; j++) w[j] = ld_rlx2(gw + (j >> 2) * 256 + (j & 3) * 1536);
            gw += 64 * 768;
          } else {
            const uint32_t so = a0 + woff(kb & 3);
            mbar_wait(mb + B_FULL + 8 * (kb & 3), (kb >> 2) & 1);
            static_for<0, 12>([&](auto ic) { constexpr int i = decltype(ic)::value;
              const float2 v = lds2f_o<(i >> 2) * WSTR + (i & 3) * 256>(so ^ ((i & 3) << 5)); w[i] = make_uint2(__float_as_uint(v.x), __float_as_uint(v.y)); });
            uint32_t done = 0;
#pragma unroll
            for (int i = 0; i < 12; i++) done |= w[i].y;
            if (lane < 2) mbar_arrive_rem(eb + 8 * (kb & 3) + (done & zero));
          }
#pragma unroll
          for (int i = 0; i < 12; i++) { float* q = a + (i >> 2) * 4; q[0] += bf_lo(w[i].x); q[1] += bf_hi(w[i].x); q[2] += bf_lo(w[i].y); q[3] += bf_hi(w[i].y); }
        }
        if (lane == 0) PTS(8);
        float c[6];
#pragma unroll
        for (int i = 0; i < 6; i++) {
          const int o = (i >> 1) * 4 + (i & 1);
          c[i] = (r2 ? a[o + 2] : a[o]) + __shfl_xor_sync(~0u, r2 ? a[o] : a[o + 2], 16);
        }
        bar_sync(5, 96);
        if (lane == 0) PTS(5);
        const uint32_t tag = lds1(mb + B_SW + 4) & 255;
#pragma unroll
        for (int sg = 0; sg < 3; sg++) st_rlx2((uint2*)&G.csp[(cg * 8 + rb) * 48] + sg * 32 + c16 * 2 + r2, tagged(c[sg * 2], tag), tagged(c[sg * 2 + 1], tag));
      } else {
       if (wid == 10) {
        if (lane < 24 && (lane & 28) != 4) sts4(sm + OFF_STATS + (lane < 16 ? lane * 128 + c8 * 16 : c8 * 16), 0x3F803F80u, 0x3F803F80u, 0x3F803F80u, 0x3F803F80u);
       } else {
        mbar_wait(mb + B_FULL + 8 * PFST, 0);
        const uint32_t ep = ld_rlx(&G.epoch);
        uint4 v[4];
#pragma unroll
        for (int i = 0; i < 4; i++) v[i] = ld_cg4((const uint4*)P.wr + lane + i * 32);
        if (elect_one()) { tmap_prefetch(&tmO); tmap_prefetch(&tmG); tmap_prefetch(&tmU); tmap_prefetch(&tmD); tmap_prefetch(&tmPD); tmap_prefetch(&tmM); }
        __syncwarp();
        const uint4 sv = make_uint4(SENT, SENT, SENT, SENT);
#pragma unroll 1
        for (int i = 0; i < 9; i++) {
          uint4* q = i < 8 ? &G.obuf[((rb * 4 + (i >> 1)) * 64 + cg * 4) * 128 + (i & 1) * 256 + lane] : &G.kvp[cg * 2304 + rb * 288 + lane];
#pragma unroll
          for (int j = 0; j < 8; j++) q[j * 32] = sv;
          if (i == 8) q[256] = sv;
          else if (lane < ((i & 1) ? 24 : 16)) l2_prefetch((i & 1) ? P.wqkv + (kl + (i >> 1) * 64 + rb * 8 + c8) * 3072 + r4 * 1024 + cg * 64 : P.x + (b * 16 + lane) * D_ + kl + i * 32);
        }
        float s = 0.f;
#pragma unroll 1
        for (int i = 0; i < 4; i++) {
          s += (bf_lo(v[0].x) + bf_hi(v[0].x)) + (bf_lo(v[0].y) + bf_hi(v[0].y)) + (bf_lo(v[0].z) + bf_hi(v[0].z)) + (bf_lo(v[0].w) + bf_hi(v[0].w));
          v[0] = v[1]; v[1] = v[2]; v[2] = v[3];
        }
#pragma unroll
        for (int o = 16; o; o >>= 1) s += __shfl_xor_sync(~0u, s, o);
        if (lane == 0) sts2f(mb + B_SW, s, __uint_as_float(ep + 1));
       }
        const uint32_t xa = sm + (c3 * 16 + r4) * 128 + ((c8 ^ r4) << 4);
        const uint4* gx = (const uint4*)(P.x + (b * 16 + r4) * D_ + kl) + c8;
        uint32_t e[4] = {0, 0, 0, 0};
        uint4 wq;
#pragma unroll 1
        for (int kb = wid == 10 ? 0 : 12; kb < (wid == 10 ? 12 : 16); kb++) {
          uint4 v[4];
          if (!(kb & 3)) wq = ld_cg4((const uint4*)(P.wr + k_of(kb + r4)) + c8);
          if (kb >= 12) {
#pragma unroll
            for (int j = 0; j < 4; j++) v[j] = ld_cg4(gx + j * 512);
            gx += 8;
          } else {
            const uint32_t so = xa + xoff(kb & 3, hf);
            mbar_wait(mb + B_FULL + 8 * (kb & 3), (kb >> 2) & 1);
            v[0] = lds4_o<0>(so); v[1] = lds4_o<512>(so ^ 64); v[2] = lds4_o<1024>(so); v[3] = lds4_o<1536>(so ^ 64);
            if (lane < 2) mbar_arrive_rem(eb + 8 * (kb & 3) + ((v[0].x | v[1].x | v[2].x | v[3].x) & zero));
          }
#pragma unroll
          for (int j = 0; j < 16; j++) {
            const uint32_t u = (j & 3) == 0 ? v[j >> 2].x : (j & 3) == 1 ? v[j >> 2].y : (j & 3) == 2 ? v[j >> 2].z : v[j >> 2].w;
            const float d0 = bf_lo(u), d1 = bf_hi(u);
            a[j >> 2] += d0 + d1; a[4 + (j >> 2)] = fmaf(d0, d0, fmaf(d1, d1, a[4 + (j >> 2)]));
          }
          cut<1>(zero);
          const int sl = (kb & 3) * 8 + c8;
          const uint4 wn = make_uint4(__shfl_sync(~0u, wq.x, sl), __shfl_sync(~0u, wq.y, sl), __shfl_sync(~0u, wq.z, sl), __shfl_sync(~0u, wq.w, sl));
#pragma unroll
          for (int j = 0; j < 4; j++) e[j] = hfma2(v[j].x, wn.x, hfma2(v[j].y, wn.y, hfma2(v[j].z, wn.z, hfma2(v[j].w, wn.w, e[j]))));
        }
        float mean, pd;
#pragma unroll 1
        for (int h = 0; h < 2; h++) {
          float u[4], v[2];
#pragma unroll
          for (int i = 0; i < 4; i++) u[i] = ((lane & 4) ? a[4 + i] : a[i]) + __shfl_xor_sync(~0u, (lane & 4) ? a[i] : a[4 + i], 4);
#pragma unroll
          for (int i = 0; i < 2; i++) v[i] = ((lane & 2) ? u[2 + i] : u[i]) + __shfl_xor_sync(~0u, (lane & 2) ? u[i] : u[2 + i], 2);
          mean = pd;
          pd = ((lane & 1) ? v[1] : v[0]) + __shfl_xor_sync(~0u, (lane & 1) ? v[0] : v[1], 1);
#pragma unroll
          for (int j = 0; j < 4; j++) { a[j] = bf_lo(e[j]); a[4 + j] = bf_hi(e[j]); }
        }
        if (wid == 11) {
          sts2f(sm + OFF_COLSUM + 512 + lane * 8, mean, pd);
          fence_gpu();
          bar_arrive(5, 96); PTS(0);
          if (elect_one()) {
#pragma unroll 1
            for (int p = 0; p < 16; p++) {
              const uint32_t ad = sm + bar3(0) + o3(p);
              mbar_init(ad, 1); mbar_init(ad + 256, 1); mbar_init(ad + 448, 8); mbar_init(ad + 704, p == 0 ? 2 : p == 12 ? 1 : p == 15 ? 7 : 8);
              mbar_expect_tx(ad, 8192); mbar_expect_tx(ad + 256, 8192); mbar_expect_tx(mb + B_FULL3 + 8 * p, SLOT_B);
            }
            asm volatile("fence.mbarrier_init.release.cluster;" ::: "memory");
            fence_async_smem();
            mbar_arrive_rem(bars + B_LATE); mbar_arrive_rem((1u << 24) + bars + B_LATE);
          }
          __syncwarp();
        } else {
          if (lane == 0) PTS(1);
          bar_sync(5, 96);
          const float2 u = lds2f(sm + OFF_COLSUM + 512 + lane * 8), sw = lds2f(mb + B_SW);
          mean = (mean + u.x) * (1.f / D_);
          pd += u.y;
          pd += __shfl_xor_sync(~0u, pd, 4);
          const float var = fmaxf(fmaf(-mean, mean, __shfl_xor_sync(~0u, mean, 4)), 0.f);
          const uint32_t tag = __float_as_uint(sw.y) & 255;
          if (c8 < 4) {
            st_rlx2((uint2*)G.st1 + (b >> 1) * 96 + rank * 16 + r4 + 4 * c8, tagged(-mean, tag), tagged(rsq(var + 1e-5f), tag));
            st_rlx(&G.pred[b * 16 + r4 + 4 * c8], (ordered(fmaf(-mean, sw.x, pd)) & ~255u) | tag);
          }
        }
      }
      if (wid < 11) gather(lds1(mb + B_SW + 4) & 255);
      if (wid == 9) {
        if (lane == 0) PTS(6);
        {
          const uint4 sv = make_uint4(SENT, SENT, SENT, SENT);
          uint4* y = &G.ybuf[b * NFFN * 4 + lane];
#pragma unroll
          for (int i = 0; i < 14; i++) y[i * 32] = sv;
          if (lane < 16) G.st2[b * 16 + lane] = make_uint4(0, 0, 0, 0);
          G.hsel[b * 64 + lane] = sv; G.hsel[b * 64 + 32 + lane] = sv;
          if (b < 8) { G.cand[b * 32 + lane] = SENT; G.cst[b * 32 + lane] = make_uint4(0, 0, 0, 0); }
          fence_gpu();
          __syncwarp();
          if (lane == 0) mbar_arrive(mb + B_LATE);
        }
      } else if (wid == 10) {
        {
          mbar_wait(mb + B_FULL + 24, 1);
#pragma unroll 1
          for (int r = -4; r < (fidx >= 0 ? 16 : 0); r++) {
            l2_prefetch((r < 0 ? (const char*)P.wo + (b + 1) * 16384 : (const char*)P.wd + fidx * 65536) + r * 4096 + lane * 128);
            delay(clk(), PDT);
          }
          PTS(4);
        }
      }
      mbar_wait(mb + B_LATE, 0);
      if (wid == 9) {
        if (elect_one()) {
          wait3(60);
#pragma unroll 1
          for (int p = 0; p < 16; p++) {
            const bool mix = (unsigned)(p - 1) < 8;
            const int c1 = mix ? ((p - 1) >> 1) * 16 : 0, c2 = mix ? (hf ^ 1) * 8 + ((p - 1) & 1) * 4 : chunk_of(p) * 4;
            const uint32_t d = sm + (uint32_t)((WO_SLOTS >> (4 * p)) & 15) * SLOT_B;
            if ((0xFFE2 >> p) & 1) mbar_wait(p == 1 ? mb + B_EMPTY + 8 : sm + bar3(32) + o3(p - 5), p == 1);
            if (EFWO) asm volatile("cp.async.bulk.tensor.4d.shared::cluster.global.mbarrier::complete_tx::bytes.L2::cache_hint [%0], [%1, {0, %3, %4, %5}], [%2], %6;"
                         :: "r"(d), "l"(mix ? &tmM : &tmO), "r"(mb + B_FULL3 + 8 * p), "r"(c1), "r"(c2), "r"(c3 * 2), "l"(l2_stream()) : "memory");
            else asm volatile("cp.async.bulk.tensor.4d.shared::cluster.global.mbarrier::complete_tx::bytes [%0], [%1, {0, %3, %4, %5}], [%2];"
                         :: "r"(d), "l"(mix ? &tmM : &tmO), "r"(mb + B_FULL3 + 8 * p), "r"(c1), "r"(c2), "r"(c3 * 2) : "memory");
            if (p >= 10) PTS(7 + p);
          }
          if (fidx >= 0) {
#pragma unroll
            for (int i = 0; i < 4; i++) {
              if (i == 0 || ((DEV >> (4 * i)) & 15) != ((DEV >> (4 * i - 4)) & 15)) wait3(32 + ((DEV >> (4 * i)) & 15));
              tma_3d(sm + ((D_SLOTS >> (4 * i)) & 15) * SLOT_B, &tmD, 0, fidx * 32, i * 4, mb + B_FFN + 8, EFF);
            }
          }
        }
      } else if (wid == 11) {
        const uint2 w = ld_rlx2((const uint2*)(P.wr + c3 * 128) + lane);
        wait3(36);
        sts1(sm + OFF_LNP + (lane & 1) * 128 + (lane >> 1) * 4, w.x); sts1(sm + OFF_LNP + (lane & 1) * 128 + 64 + (lane >> 1) * 4, w.y);
        if (lane < 16) sts1(sm + OFF_LNP + 256 + lane * 4, 0x3F803F80u);
        const uint32_t tag = lds1(mb + B_SW + 4) & 255;
        uint4 k;
        for (int it = 0;; it++) {
          k = ld_rlx4((const uint4*)&G.pred[rb * 256 + hf * 64 + r2 * 128] + c16);
          k.x ^= tag; k.y ^= tag; k.z ^= tag; k.w ^= tag;
          if (!__any_sync(~0u, (k.x | k.y | k.z | k.w) & 255)) break;
          SPINCHK(it, 13);
        }
        const uint2 ahead = top2(k.x | (lane * 4), k.y | (lane * 4 + 1), k.z | (lane * 4 + 2), k.w | (lane * 4 + 3));
        if (lane == 0) sts2f(sm + OFF_MSC + 8, __uint_as_float((ahead.x & 127) ^ NOSPEC), __uint_as_float((ahead.y & 127) ^ NOSPEC));
        __syncwarp();
        if (lane == 0) mbar_arrive(mb + B_FULL3 + 8 * 15);
      } else if (fidx >= 0 && elect_one()) {
        wait3(60);
        mbar_expect_tx(mb + B_FULL, 65536);
#pragma unroll 1
        for (int h = 0; h < 2; h++) {
          const int up = h ^ hf ^ 1;
          mbar_wait(mb + B_EMPTY + 16 - 16 * h, 1);
#pragma unroll
          for (int i = 0; i < 4; i++) {
            const int f = (0x5140 >> (4 * i)) & 15;
            tma_2d(sm + ((GU_SLOTS >> (4 * f)) & 15) * SLOT_B + up * 8192, up ? &tmU : &tmG, fidx * 32, f * 128, mb + B_FULL, EFF);
            if (FDT) delay(clk(), FDT);
          }
          PTS(23 + h);
        }
#pragma unroll 1
        for (int j = 0; j < 8; j++) { mbar_wait(sm + bar3(32) + o3(PD0 + j * PDS / 2), 0); tma_2d(sm + OFF_COLSUM, &tmPD, 0, fidx * 256 + j * 32, mb + B_FFN, false); }
#pragma unroll 1
        for (int i = 0; i < 4; i++) {
          const int f = (0x7362 >> (4 * i)) & 15;
          const uint32_t d = sm + ((GU_SLOTS >> (4 * f)) & 15) * SLOT_B;
          mbar_wait(sm + bar3(32) + o3((GEV >> (4 * i)) & 15), 0);
          tma_2d(d, &tmG, fidx * 32, f * 128, mb + B_FFN, EFF);
          tma_2d(d + 8192, &tmU, fidx * 32, f * 128, mb + B_FFN, EFF);
          PTS(27 + i);
        }
      }
    }
    __syncwarp();
    const float sw = __uint_as_float(lds1(mb + B_SW));
    const int rr = lane >> 4, row00 = rb * 256 + hf * 64;
    uint2 pick;
    if (wid == 8) {
      wait3(61);
      delay(clk(), SDELAY);
      uint4 v;
      int id;
      for (int it = 0;; it++) {
        v = ld_rlx4(&G.cst[jp * 32 + lane]);
        id = __float2int_rn(__uint_as_float(v.w));
        if (!__any_sync(~0u, (id & 15) != 8)) break;
        SPINCHK(it, 14);
      }
      float2 pr;
      const uint32_t k = route(v, sw, id >> 4, pr);
      pick.x = __reduce_max_sync(~0u, k); pick.y = __reduce_max_sync(~0u, k == pick.x ? 0 : k);
      if (k == pick.x || k == pick.y) sts4(sm + OFF_MSC + 16 + (k == pick.y) * 16, k, lane, __float_as_uint(pr.x), __float_as_uint(pr.y));
      __syncwarp();
      if (lane == 0) { mbar_arrive(mb + B_SEL); PTS(16); }
    } else if (wid == 9) {
      wait3(61);
      delay(clk(), LDELAY);
      uint4 v[4];
      for (int it = 0;; it++) {
#pragma unroll
        for (int i = 0; i < 4; i++) v[i] = ld_rlx4(&G.st2[row00 + (i >> 1) * 128 + (i & 1) * 32 + lane]);
        if (!__any_sync(~0u, (v[0].w & v[1].w & v[2].w & v[3].w) != 0x41000000u)) break;
        SPINCHK(it, 6);
      }
      uint32_t k[4];
#pragma unroll
      for (int i = 0; i < 4; i++) {
        float2 pr;
        k[i] = route(v[i], sw, row00 + (i >> 1) * 128 + (i & 1) * 32 + lane, pr);
        const float nm = __uint_as_float(v[i].x) * (-1.f / D_);
        sts2f(sm + OFF_LNP + (i * 32 + lane) * 8, __uint_as_float(pack2(pr.x, pr.x)), __uint_as_float(pack2(nm, nm)));
      }
      const uint2 m = top2(k[0], k[1], k[2], k[3]);
      if (lane == 0) { st_rlx2(&G.cand[c3 * 32 + (rb * 2 + hf) * 2], m.x, m.y); sts2f(sm + OFF_MSC + 0, __uint_as_float(m.x), __uint_as_float(m.y)); }
      wait3(62);
      __syncwarp();
      if (lane == 0) { mbar_arrive(mb + B_OUT); PTS(12); }
      const int ca = 2047 - (((lane & 4) ? m.y : m.x) & 2047), ta = ((ca >> 1) & 64) + (ca & 63);
      uint32_t h0, h1, h2, h3;
      ldsm4_o<0>(sm + HST + ta * 256 + ((((lane & 3) * 4 + (lane >> 3)) ^ (ta & 7)) << 4), h0, h1, h2, h3);
      st_rlx4(&G.hsel[(32 + (rb * 2 + hf) * 2 + rr) * 128 + c3 * 16 + (lane & 15)], make_uint4(h0, h1, h2, h3));
    }
    mbar_wait(mb + B_OUT, 0);
    const float2 cf = lds2f(sm + OFF_MSC + 0);
    const int ca0 = ~__float_as_int(cf.x), ca1 = ~__float_as_int(cf.y), cand0 = ((ca0 >> 1) & 64) + (ca0 & 63), cand1 = ((ca1 >> 1) & 64) + (ca1 & 63);
    auto norm = [](const uint4& v, const float2& pr) {
      const uint32_t r = __float_as_uint(pr.x), m = __float_as_uint(pr.y);
      return make_uint4(hfma2(hadd2(v.x, m), r, v.x), hfma2(hadd2(v.y, m), r, v.y), hfma2(hadd2(v.z, m), r, v.z), hfma2(hadd2(v.w, m), r, v.w));
    };
    uint4* const og = (uint4*)(P.out + row00 * D_ + c3 * 128) + (lane & 15);
    if (wid == 8) {
      delay(clk(), CDELAY);
      uint32_t k;
      for (int it = 0;; it++) { k = ld_rlx(&G.cand[c3 * 32 + lane]); if (!__any_sync(~0u, k == SENT)) break; SPINCHK(it, 12); }
      const uint32_t m1 = __reduce_max_sync(~0u, k), m2 = __reduce_max_sync(~0u, k == m1 ? 0 : k);
      const uint32_t miss = ((m1 ^ pick.x) | (m2 ^ pick.y)) & 2047;
      if (miss && (k == m1 || k == m2)) {
        float2 pr;
        route(ld_rlx4(&G.st2[2047 - (k & 2047)]), sw, 0, pr);
        sts4(sm + OFF_MSC + 48 + (k == m2) * 16, k, 32 + lane, __float_as_uint(pr.x), __float_as_uint(pr.y));
      }
      if (lane == 0) sts1(sm + OFF_MSC + 80, miss);
      __syncwarp();
      if (lane == 0) { mbar_arrive(mb + B_SEL2); PTS(13); }
      const uint32_t kc = __float_as_uint(rr ? cf.y : cf.x);
      const int c = rr ? cand1 : cand0;
      if (kc != m1 && kc != m2) og[(c + (c & 64)) * 128] = norm(lds4(sm + HST + c * 256 + (((lane & 15) ^ (c & 7)) << 4)), lds2f(sm + OFF_LNP + c * 8));
    }
#pragma unroll 1
    for (int t0 = wid == 8 ? 120 : (11 - wid) * 8; t0 < (wid == 8 ? 128 : 120) * !NOOUT; t0 += 24) {
      uint4 v[4];
      float2 pr[4];
      const uint32_t ad = sm + HST + t0 * 256 + lane * 16;
      static_for<0, 4>([&](auto ic) { constexpr int i = decltype(ic)::value; v[i] = lds4_o<i * 512>(ad ^ (rr << 4) ^ (i << 5)); pr[i] = lds2f_o<i * 16>(sm + OFF_LNP + (t0 + rr) * 8); });
#pragma unroll
      for (int i = 0; i < 4; i++) v[i] = norm(v[i], pr[i]);
      if (t0 >= OHOLD) wait3(63);
#pragma unroll
      for (int i = 0; i < 4; i++) {
        const int tr = t0 + rr + 2 * i;
        if (tr != cand0 && tr != cand1) {
          if (OUTEF) asm volatile("st.global.L2::cache_hint.v4.u32 [%0], {%1,%2,%3,%4}, %5;" :: "l"(og + (tr + (tr & 64)) * 128), "r"(v[i].x), "r"(v[i].y), "r"(v[i].z), "r"(v[i].w), "l"(l2_stream()) : "memory");
          else og[(tr + (tr & 64)) * 128] = v[i];
        }
      }
    }
    if (wid == 11 && lane == 0) PTS(31);
  } else {
    asm volatile("setmaxnreg.inc.sync.aligned.u32 224;");
    const int t128 = tid & 127, warp = wid & 3, g = lane >> 2, t = lane & 3;
    const int mb3 = rb * 4 + wg * 2 + hf;
    float acc[64];
    uint4 abuf[3][4];
    uint32_t to;
    int tid2;
    {
      float acc0[96], acc1[96];
#pragma unroll
      for (int i = 0; i < 96; i++) { asm volatile("" : "=f"(acc0[i])); asm volatile("" : "=f"(acc1[i])); }
      const uint32_t xo0 = dlo(sb, 16) + hf * 512, xo1 = dlo(sb, 16) + (hf ^ 1) * 512;
      const uint32_t eb0 = (t128 << 24) + bars + B_EMPTY;
#pragma unroll 1
      for (int kb = 0; kb < 12; kb++) {
        const int s = kb & 3;
        mbar_wait(mb + B_FULL + 8 * s, (kb >> 2) & 1);
        if (LOCK) bar_sync(13, 256);
        if (kb == 0) TS(1);
        const uint32_t xs = xoff(s, wg) >> 4, ws = dlo(sb + woff(s), WSTR);
        pin(acc0); pin(acc1);
        wg_fence();
#pragma unroll
        for (int k = 0; k < 4; k++) {
          const uint64_t db = dsc<1024, 1>(ws + k * 128);
          const int sd = k == 0 ? kb : 1;
          wgmma_n192_ss<0, 1, 0>(acc0, dsc<1024, 1>(xs + xo0 + k * 2), db, sd);
          wgmma_n192_ss<0, 1, 0>(acc1, dsc<1024, 1>(xs + xo1 + k * 2), db, sd);
          if (k == RELK || k == 3) wg_commit();
          if (k == RELK) {
            wg_wait<1>();
            if (kb > 0 && t128 < 2) mbar_arrive_rem(eb0 + 8 * ((kb - 1) & 3));
          }
        }
        pin(acc0); pin(acc1);
      }
      float qa0[32], qa1[32], kv0[64], kv1[64];
#pragma unroll
      for (int i = 0; i < 96; i++) { if (i < 32) { qa0[i] = acc0[i]; qa1[i] = acc1[i]; } else { kv0[i - 32] = acc0[i]; kv1[i - 32] = acc1[i]; } }
      uint2 st[2][2];
      uint4 am;
      auto center = [&](float (&q)[32], float (&kv)[64], const uint2 (&v)[2]) {
        const uint32_t n0 = v[0].x & (t == 0 ? ~255u : 0u), n1 = v[1].x & (t == 0 ? ~255u : 0u);
        am = make_uint4(__byte_perm(n0, 0, 0x3232), __byte_perm(n1, 0, 0x3232),
                        __byte_perm(__float_as_uint(__uint_as_float(n0) - bf_hi(n0)), 0, 0x3232), __byte_perm(__float_as_uint(__uint_as_float(n1) - bf_hi(n1)), 0, 0x3232));
        wg_fence();
        wgmma_n64_rs<1, 0>(q, am.x, am.y, am.z, am.w, dsc<32, 0>(dlo(sb + OFF_COLSUM, 0)), 1);
        wgmma_n128_rs<1, 0>(kv, am.x, am.y, am.z, am.w, dsc<32, 0>(dlo(sb + OFF_COLSUM + 256, 0)), 1);
      };
      auto load_st = [&]() {
        mbar_wait(mb + B_AUX, 0);
#pragma unroll
        for (int i = 0; i < 4; i++) st[i >> 1][i & 1] = ld_rlx2((const uint2*)G.st1 + ((rb * 4 + wg * 2 + ((i >> 1) ^ hf)) * 2 + (warp >> 1)) * 96 + (warp & 1) * 16 + (i & 1) * 8 + g);
      };
      if (!wg) {
        wg_wait<0>();
        if (t128 < 2) mbar_arrive_rem(eb0 + 24);
        load_st();
#pragma unroll 1
        for (int s = 0; s < 4; s++) mbar_wait(mb + B_FULL + 8 * s, 1);
        bar_sync(6, 256);
      }
      static_for<0, 4>([&](auto sc) {
        constexpr int s = decltype(sc)::value;
        if (wg) mbar_wait(mb + B_FULL + 8 * s, 1);
        const uint32_t xs = (wg ? xoff(s, 1) : xoff(s, 0)) >> 4, ws = dlo(sb + woff(s) + WSTR, WSTR);
        pin(kv0); pin(kv1); pin(qa0); pin(qa1);
        wg_fence();
#pragma unroll
        for (int k = 0; k < 4; k++) {
          const uint64_t db = dsc<1024, 1>(ws + k * 128);
          wgmma_n128_ss<0, 1, 0>(kv0, dsc<1024, 1>(xs + xo0 + k * 2), db, 1);
          wgmma_n128_ss<0, 1, 0>(kv1, dsc<1024, 1>(xs + xo1 + k * 2), db, 1);
          if (k == 3 || (k == 2 && s == 0)) wg_commit();
          if (k == (s ? 3 : 2) && s < 3) {
            wg_wait<1>();
            if (s == 0) { if (wg && t128 < 2) mbar_arrive_rem(eb0 + 24); }
            else if (!wg) bar_arrive(8 + s, 256);
          }
        }
        if (s == STLD && wg) load_st();
      });
      center(qa0, kv0, st[0]);
      wg_commit();
      if (wg) bar_arrive(6, 256);
      float rl[2][2];
      uint32_t r2[2][2];
#pragma unroll
      for (int i = 0; i < 4; i++) { const float r = __uint_as_float(st[i >> 1][i & 1].y & ~255u); r2[i >> 1][i & 1] = pack2(r, r); rl[i >> 1][i & 1] = r * 1.4426950408889634f; }
      const uint32_t sad = sm + (wg ? 11 : 2) * SLOT_B + (warp * 16 + (lane & 15)) * 128 + (((lane >> 4) ^ (lane & 7)) << 4);
      wg_wait<0>();
      pin(kv0); pin(kv1); pin(qa0); pin(qa1); pin4(am);
      center(qa1, kv1, st[1]);
      wg_commit();
      if (wg) bar_arrive(11, 256);
      if (CUTS & 1) cut<2>(zero);
      TS(2);
      auto phi8 = [&](const float* a, int m) {
        return make_uint4(phi2(a[0], a[1], r2[m][0], rl[m][0]), phi2(a[2], a[3], r2[m][1], rl[m][1]), phi2(a[4], a[5], r2[m][0], rl[m][0]), phi2(a[6], a[7], r2[m][1], rl[m][1]));
      };
      auto stage = [&](float (&a)[64], auto mc) {
        constexpr int m = decltype(mc)::value;
        uint4 r[4];
#pragma unroll
        for (int j = 0; j < 4; j++) r[j] = phi8(a + j * 8, m);
        if (m == 0 || wg) bar_sync(wg ? 9 + m : 11, 256 + (r[SBAR].x & zero));
#pragma unroll
        for (int j = 0; j < 4; j++) {
          const int v = 32 + j * 8;
          stsm4_o<WSTR + m * 8192>(sad ^ (j << 5), hmul2(pack2(a[v], a[v + 1]), r2[m][0]), hmul2(pack2(a[v + 2], a[v + 3]), r2[m][1]),
                                                   hmul2(pack2(a[v + 4], a[v + 5]), r2[m][0]), hmul2(pack2(a[v + 6], a[v + 7]), r2[m][1]));
        }
#pragma unroll
        for (int j = 0; j < 4; j++) stsm4_o<m * 8192>(sad ^ (j << 5), r[j].x, r[j].y, r[j].z, r[j].w);
      };
      stage(kv0, std::integral_constant<int, 0>{});
      wg_wait<0>();
      pin(kv1); pin(qa1); pin4(am);
      stage(kv1, std::integral_constant<int, 1>{});
      fence_async_smem();
      TS(3);
      uint32_t xr[8][4];
      auto load_xr = [&]() {
        const uint32_t xa = sm + hf * 8192 + (warp * 16 + (lane & 15)) * 128 + (((lane >> 4) ^ (lane & 7)) << 4);
#pragma unroll
        for (int q = 0; q < 8; q++) ldsm4_o<0>((xa ^ ((q & 3) << 5)) + xoff(rank * 2 + (q >> 2), wg), xr[q][0], xr[q][1], xr[q][2], xr[q][3]);
      };
      if (!wg) { bar_arrive(4, 256); load_xr(); }
      else {
        float ka[36];
#pragma unroll
        for (int i = 0; i < 36; i++) ka[i] = 0.f;
        auto kv_mma = [&](auto ic) {
          constexpr int i = decltype(ic)::value;
          constexpr uint32_t o = sb + (i < 8 ? 11 : 2) * SLOT_B + (i & 7) * 2048;
          wgmma_n72_ss<1, 1, 0>(ka, dsc<1024, 1>(dlo(o, 8192)), dsc<1024, 1>(dlo(o + WSTR, sb + OFF_STATS - o - WSTR)), i);
        };
        mbar_wait(mb + B_LATE, 0);
        bar_sync(3, 128);
        wg_fence();
        static_for<0, 8>(kv_mma);
        wg_commit();
        uint4* dst = &G.kvp[cg * 2304 + rb * 32];
        if (CUTS & 4) cut<3>(zero);
        load_xr();
        bar_sync(4, 256);
        static_for<8, 16>(kv_mma);
        wg_commit();
        if (QHOLD == 1) bar_arrive(8, 256);
        wg_wait<0>();
        pin(ka);
        if (QHOLD == 2) bar_arrive(8, 256);
        TS(4);
        if (warp < 2) {
          st_rlx4(dst + warp * 512 + lane, make_uint4(pack2(ka[0], ka[1]), pack2(ka[4], ka[5]), pack2(ka[8], ka[9]), pack2(ka[12], ka[13])));
          st_rlx4(dst + warp * 512 + 256 + lane, make_uint4(pack2(ka[2], ka[3]), pack2(ka[6], ka[7]), pack2(ka[10], ka[11]), pack2(ka[14], ka[15])));
        } else {
          st_rlx4(dst + warp * 512 + lane, make_uint4(pack2(ka[16], ka[17]), pack2(ka[20], ka[21]), pack2(ka[24], ka[25]), pack2(ka[28], ka[29])));
          st_rlx4(dst + warp * 512 + 256 + lane, make_uint4(pack2(ka[18], ka[19]), pack2(ka[22], ka[23]), pack2(ka[26], ka[27]), pack2(ka[30], ka[31])));
        }
        st_rlx((uint32_t*)(dst + 2048) + t128, pack2(ka[32], ka[34]));
        if (QHOLD == 3) bar_arrive(8, 256);
        if (t128 == 0) mbar_arrive(sm + bar3(60));
      }
      TS(5);
      uint32_t pq[16];
      auto q_mma = [&](float (&q)[32], uint32_t xo, int next) {
#pragma unroll 1
        for (int s = 0; s < 4; s++) {
          const uint32_t xs = (xoff(s, wg) >> 4) + xo, ws = dlo(sb + woff(s), 8192);
          pin(q);
          wg_fence();
#pragma unroll
          for (int k = 0; k < 4; k++) wgmma_n64_ss<0, 1, 0>(q, dsc<1024, 1>(xs + k * 2), dsc<1024, 1>(ws + k * 128), 1);
          wg_commit();
        }
        if (next) bar_arrive(next, 256);
        wg_wait<0>();
        pin(q);
      };
      auto q_phi = [&](float (&q)[32], int m) {
#pragma unroll
        for (int j = 0; j < 4; j++) { const uint4 r = phi8(q + j * 8, m); pq[j * 4] = r.x; pq[j * 4 + 1] = r.y; pq[j * 4 + 2] = r.z; pq[j * 4 + 3] = r.w; }
      };
      auto o_of = [&](uint4 (&o)[4], uint4* first, bool pub) {
        float oa[2][20];
#pragma unroll
        for (int i = 0; i < 40; i++) oa[i / 20][i % 20] = 0.f;
        wg_fence();
#pragma unroll
        for (int ks = 0; ks < 4; ks++) {
          wgmma_n40_rs<1, 0>(oa[ks >> 1], pq[ks * 4], pq[ks * 4 + 1], pq[ks * 4 + 2], pq[ks * 4 + 3], dsc<1024, 1>(dlo(sb + OFF_KVB + ks * 2048, 8192)), ks & 1);
          if (ks & 1) wg_commit();
        }
#pragma unroll
        for (int h = 0; h < 2; h++) {
          if (h) wg_wait<0>(); else wg_wait<1>();
          pin(oa[h]);
          const float (&d)[20] = oa[h];
          const float i0 = rcp(d[16] + 1e-6f), i1 = rcp(d[18] + 1e-6f);
#pragma unroll
          for (int k2 = 0; k2 < 2; k2++) {
            o[h * 2 + k2] = make_uint4(pack2(d[k2 * 8] * i0, d[k2 * 8 + 1] * i0), pack2(d[k2 * 8 + 2] * i1, d[k2 * 8 + 3] * i1),
                                       pack2(d[k2 * 8 + 4] * i0, d[k2 * 8 + 5] * i0), pack2(d[k2 * 8 + 6] * i1, d[k2 * 8 + 7] * i1));
            if (pub && !h) st_rlx4(first + (h * 2 + k2) * 1024, o[h * 2 + k2]);
          }
        }
#pragma unroll
        for (int i = 0; i < 16; i++) asm volatile("" : "+r"(pq[i]) :: "memory");
      };
      bar_sync(wg ? 7 : 8, 256);
      q_mma(qa1, xo1, wg ? 8 : 7);
      if (tid == 0) mbar_arrive(mb + B_EMPTY + 16);
      cut<5>(zero);
      pin(qa1);
      q_phi(qa1, 1);
      tid2 = __shfl_sync(~0u, tid, lane);
      uint32_t done = 0;
#pragma unroll
      for (int j = 0; j < 8; j++) done |= pq[2 * j] | pq[2 * j + 1] | xr[j][3];
      bar_sync(wg ? 7 : 8, 256 + (done & zero));
      q_mma(qa0, xo0, wg ? 0 : 7);
      if (t128 == 0) mbar_arrive(mb + B_EMPTY + 8 * wg);
      TS(6);
      {
        uint4 a, v[8];
        uint32_t z[8], zs;
        const int blk = warp * 2 + wg;
        mbar_wait(mb + B_KVL, 0);
        static_for<0, 8>([&](auto ic) { constexpr int i = decltype(ic)::value; v[i] = lds4_o<sb + 11 * SLOT_B + i * 512>(own + (blk + (blk & 4)) * 4096 + lane * 16); });
#pragma unroll
        for (int i = 0; i < 8; i++) z[i] = lds1(sm + 2 * SLOT_B + i * 512 + t128 * 4);
#pragma unroll 1
        for (int it = 0;; it++) {
          zs = hadd2(hadd2(hadd2(z[0], z[1]), hadd2(z[2], z[3])), hadd2(hadd2(z[4], z[5]), hadd2(z[6], z[7])));
          a = hadd8(hadd8(hadd8(v[0], v[1]), hadd8(v[2], v[3])), hadd8(hadd8(v[4], v[5]), hadd8(v[6], v[7])));
          TSV(20, it + 1);
          if (!__any_sync(~0u, hnan(hadd2(hadd2(hadd2(a.x, a.y), hadd2(a.z, a.w)), zs)))) break;
          uint32_t mm = 0;
#pragma unroll
          for (int i = 0; i < 8; i++) mm = max4(max(mm, z[i]), v[i]);
          if (!__any_sync(~0u, mm == SENT)) break;
#pragma unroll
          for (int i = 0; i < 8; i++) { v[i] = ld_rlx4(&G.kvp[cg * 2304 + blk * 256 + i * 32 + lane]); z[i] = ld_rlx((const uint32_t*)&G.kvp[cg * 2304 + 2048 + i * 32] + t128); }
          SPINCHK(it, 4);
        }
        TS(23);
        const uint32_t kb0 = sm + OFF_KVB + blk * 1024 + (lane & 7) * 128;
        stsm4(kb0 + (((lane >> 3) ^ (lane & 7)) << 4), a.x, a.y, a.z, a.w);
        asm volatile("stmatrix.sync.aligned.m8n8.x1.shared.b16 [%0], {%1};" :: "r"(kb0 + ((4 ^ (lane & 7)) << 4)), "r"(zs >> (16 * wg)) : "memory");
        fence_async_smem();
        bar_sync(12, 256);
      }
      TS(7);
      if (t128 == 0) mbar_arrive_rem((wg << 24) + sb + bar3(48));
      to = clk();
      o_of(abuf[1], &G.obuf[((mb3 ^ 1) * 64 + hf * 32 + c3) * 128 + (tid2 & 127)], true);
      TS(29);
      cut<4>(zero);
      pin(qa0);
      q_phi(qa0, 0);
      o_of(abuf[0], nullptr, false);
#pragma unroll
      for (int q = 0; q < 32; q++) { asm volatile("" : "+r"(xr[q >> 2][q & 3])); acc[q * 2] = bf_lo(xr[q >> 2][q & 3]); acc[q * 2 + 1] = bf_hi(xr[q >> 2][q & 3]); }
      pin(acc);
    }
    {
    const int t128 = tid2 & 127, lane = tid2 & 31, g = lane >> 2, t = lane & 3;
    TS(8);
    uint32_t wa[32][4];
    auto load_gu = [&](int f) {
      const uint32_t ad = own + ((lane >> 3) & 1) * 8192 + ((lane >> 4) * 8 + (lane & 7)) * 64 + ((warp ^ ((lane >> 1) & 3)) << 4) + ((GU_SLOTS >> (16 * wg + 4 * f)) & 15) * SLOT_B;
      static_for<0, 8>([&](auto ic) { constexpr int i = decltype(ic)::value; ldsm4t_o<sb + i * 1024>(ad, wa[f * 8 + i]); });
    };
    {
      const uint32_t la = own + wg * 8192 + t128 * 16, fa = sm + wg * 256;
      int pv = tid2 & zero;
      auto step = [&](const int p, auto jc) {
        constexpr int j = decltype(jc)::value;
        uint4 (&a)[4] = abuf[j == 3 ? 0 : (j + 1) % 3];
        uint4 (&n)[4] = abuf[j == 3 ? 1 : (j + 2) % 3];
        auto fetch = [&]() {
          const uint32_t ra = la + ((p + 1) & 3) * SLOT_B;
          mbar_wait(fa + bar3(0) + o3(p + 1), 0);
          n[0] = lds4_o<sb + 10 * SLOT_B>(ra); n[1] = lds4_o<sb + 10 * SLOT_B + 2048>(ra); n[2] = lds4_o<sb + 10 * SLOT_B + 4096>(ra); n[3] = lds4_o<sb + 10 * SLOT_B + 6144>(ra);
        };
        const bool early = j == 0 ? p > 1 : j == 1 ? true : j == 2 ? p < 15 : false;
        const uint32_t bs = dlo(sb, 8192) + (uint32_t)((WO_SLOTS >> (4 * p)) & 15) * (SLOT_B >> 4);
        if (early) fetch();
        if (p == 1) TS(28);
        if (p == 2) TS(9);
        pin(acc);
        wg_fence();
#pragma unroll
        for (int k = 0; k < 4; k++) {
          wgmma_n128_rs<1, 0>(acc, a[k].x, a[k].y, a[k].z, a[k].w, dsc<1024, 1>(bs + k * 128), 1);
          if (k == 0) { if (j != 2 || p < 15) mbar_wait(mb + B_FULL3 + 8 * p + 8, 0); wg_fence(); }
        }
        wg_commit();
        if (j == 3) {
          delay(to, BDELAY);
#pragma unroll
          for (int k = 2; k < 4; k++) st_rlx4(&G.obuf[((mb3 ^ 1) * 64 + hf * 32 + c3) * 128 + t128 + k * 1024], n[k]);
          if (fidx >= 0) mbar_wait(mb + B_FULL, 0);
          load_gu(0); load_gu(1);
          TS(24);
          fetch();
          TS(27);
        } else if (j == 0 && p == 1) fetch();
        pv++;
        if (__any_sync(~0u, max(max4(max4(0, n[0]), n[1]), max4(max4(0, n[2]), n[3])) == SENT)) {
          const uint4* q = &G.obuf[(mb3 * 64 + chunk_of(pv) * 4) * 128 + t128];
#pragma unroll 1
          for (int it = 0;; it++) {
#pragma unroll
            for (int i = 0; i < 4; i++) n[i] = ld_rlx4(q + i * 128);
            TSV(21, _ts | 1 << pv);
            if (!__any_sync(~0u, max(max4(max4(0, n[0]), n[1]), max4(max4(0, n[2]), n[3])) == SENT)) break;
            SPINCHK(it, 5);
          }
        }
        if (lane == 0 && p < 11) mbar_arrive_rem((wg << 24) + sb + bar3(48) + o3(p + 1));
        wg_wait<1>();
        pin(acc);
        if (j < 3) {
#pragma unroll
          for (int i = 0; i < 4; i++) pin4(abuf[j][i]);
        }
        if (j == 3 || (j == 0 && p == 1)) {
#pragma unroll
          for (int k = 0; k < 4; k++) if ((k < W0N) == (j == 3)) st_rlx4(&G.obuf[(mb3 * 64 + cg * 4 + k) * 128 + t128], abuf[0][k]);
        }
        if (lane == 0) mbar_arrive(sm + bar3(32) + o3(p));
      };
      mbar_wait(mb + B_FULL3, 0);
      step(0, std::integral_constant<int, 3>{});
#pragma unroll
      for (int i = 0; i < 4; i++) abuf[2][i] = make_uint4(0, 0, 0, 0);
#pragma unroll 1
      for (int pp = 1; pp < 16; pp += 3) static_for<0, 3>([&](auto jc) { step(pp + decltype(jc)::value, jc); });
    }
    uint4 wb[4];
#pragma unroll
    for (int i = 0; i < 4; i++) wb[i] = lds4(sm + OFF_LNP + ((g & 1) ? t * 64 : 256) + i * 16);
    const float2 ah = lds2f(sm + OFF_MSC + 8);
    wg_wait<0>();
    pin(acc);
#pragma unroll
    for (int i = 0; i < 4; i++) pin4(abuf[0][i]);
    TS(10);
    const uint32_t msc = sm + OFF_MSC;
    uint32_t hp[8][4];
    {
      float se[2][4], q[4] = {0.f, 0.f, 0.f, 0.f};
#pragma unroll
      for (int i = 0; i < 8; i++) se[i >> 2][i & 3] = 0.f;
#pragma unroll
      for (int j = 0; j < 8; j++) {
#pragma unroll
        for (int i = 0; i < 4; i++) { const float a = acc[j * 8 + i * 2], c = acc[j * 8 + i * 2 + 1]; hp[j][i] = pack2(a, c); q[i] = fmaf(a, a, fmaf(c, c, q[i])); }
        mma16816(se[j & 1], hp[j], (j & 1) ? wb[j >> 1].z : wb[j >> 1].x, (j & 1) ? wb[j >> 1].w : wb[j >> 1].y);
      }
      const bool od = t & 1;
      const float q0 = q[0] + q[2], q1 = q[1] + q[3];
      float qq = (od ? q1 : q0) + __shfl_xor_sync(~0u, od ? q0 : q1, 1);
      qq += __shfl_xor_sync(~0u, qq, 2);
      const float ss = od ? se[0][2] + se[1][2] : se[0][0] + se[1][0], ee = od ? se[0][3] + se[1][3] : se[0][1] + se[1][1];
#pragma unroll 1
      for (int c = 0; c < 2; c++) {
        const int tr = __float_as_int(c ? ah.y : ah.x), slot = (rb * 2 + hf) * 2 + c;
        if ((tr >> 4) == wid) {
          const int sl = (tr & 7) * 4 + ((tr >> 3) & 1);
          const float s1 = __shfl_sync(~0u, ss, sl), s2 = __shfl_sync(~0u, qq, sl), s3 = __shfl_sync(~0u, ee, sl);
          red4(lane < 8, &G.cst[lane * 32 + slot], s1, s2, s3, c3 ? 1.f : (float)((mb3 * 64 + (tr & 63)) * 16 + 1));
          if (g == (tr & 7)) {
#pragma unroll
            for (int i = 0; i < 4; i++)
              st_rlx4(&G.hsel[slot * 128 + c3 * 16 + i * 4 + t], (tr & 8) ? make_uint4(hp[2 * i][1], hp[2 * i][3], hp[2 * i + 1][1], hp[2 * i + 1][3])
                                                                          : make_uint4(hp[2 * i][0], hp[2 * i][2], hp[2 * i + 1][0], hp[2 * i + 1][2]));
          }
        }
      }
      red4(t < 2, &G.st2[mb3 * 64 + warp * 16 + (t & 1) * 8 + g], ss, qq, ee, 1.f);
      if (lane == 0) mbar_arrive(sm + bar3(61));
      TS(11);
    }
    uint32_t wd[8][2][4];
    const uint32_t dw = sm + ((D_SLOTS >> (2 * (wid & 6))) & 15) * SLOT_B + (wid & 1) * 8192;
    const uint32_t da = dw + ((lane >> 4) * 8 + (lane & 7)) * 128 + ((((lane >> 3) & 1) ^ (lane & 7)) << 4);
    const uint32_t xl = own + ((D_SLOTS >> (8 * wg + ((lane & 16) >> 2))) & 15) * SLOT_B + (lane & 8) * 1024 + (lane & 7) * 16;
    float ya[8][4];
    int pass = 0;
    if (!GUPOS) { if (fidx >= 0) mbar_wait(mb + B_FFN, 1); load_gu(2); load_gu(3); }
    {
      bar_sync(1, 256);
      const uint32_t ha = sm + HST + wid * 4096 + (lane & 15) * 256 + (((lane >> 4) ^ (lane & 7)) << 4);
      static_for<0, 8>([&](auto jc) { constexpr int j = decltype(jc)::value; stsm4_o<(j >> 2) * 128>(ha ^ ((j & 3) << 5), hp[j][0], hp[j][1], hp[j][2], hp[j][3]); });
      asm volatile("fence.acq_rel.cta;" ::: "memory");
      __syncwarp();
      if (lane == 0) mbar_arrive(sm + bar3(62));
    }
    auto load_d1 = [&]() {
      if (fidx >= 0) mbar_wait(mb + B_FFN + 8, 0);
      static_for<0, 8>([&](auto ic) { constexpr int i = decltype(ic)::value; ldsm4t_o<(i & 1) * 2048>(da ^ ((i >> 1) << 5), wd[i >> 1][i & 1]); });
    };
    if (GUPOS) { if (fidx >= 0) mbar_wait(mb + B_FFN, 1); load_gu(2); load_gu(3); }
    if (!D1POS) load_d1();
#pragma unroll 1
    for (;; pass++) {
      TS(15);
      mbar_wait(mb + B_SEL, 0);
      const uint4 sx = lds4(msc + 16 + pass * 32 + (lane & 16));
      TS(26);
      const uint4* xp = &G.hsel[sx.y * 128 + wid * 16 + (lane & 15)];
      uint4 xv = ld_rlx4(xp);
      if (D1POS && !pass) load_d1();
#pragma unroll 1
      for (int it = 0; __any_sync(~0u, max4(0, xv) == SENT); it++) { xv = ld_rlx4(xp); SPINCHK(it, 7); }
      const float f = __uint_as_float(sx.z), n = __uint_as_float(sx.w);
      sts4(dw + ((lane & 12) * 2 + (lane >> 4) * 4 + t) * 16, pack2(fmaf(bf_lo(xv.x), f, n), fmaf(bf_hi(xv.x), f, n)), pack2(fmaf(bf_lo(xv.y), f, n), fmaf(bf_hi(xv.y), f, n)),
           pack2(fmaf(bf_lo(xv.z), f, n), fmaf(bf_hi(xv.z), f, n)), pack2(fmaf(bf_lo(xv.w), f, n), fmaf(bf_hi(xv.w), f, n)));
      if (wid == rb && (g & 3) == (cg >> 2)) sts4(msc + 96 + (lane >> 4) * 16 + t * 32, xv.x, xv.y, xv.z, xv.w);
      bar_sync(2 + wg, 128);
      TS(14);
      float gu[4][4];
#pragma unroll
      for (int i = 0; i < 16; i++) gu[i >> 2][i & 3] = 0.f;
      uint4 xb[4];
      static_for<0, 4>([&](auto ic) { constexpr int i = decltype(ic)::value; xb[i] = lds4_o<sb + i * 128>(xl); });
#pragma unroll
      for (int i = 0; i < 16; i++) {
        const int ks = i & 7;
        if (i == 14) {
#pragma unroll
          for (int j = 0; j < 8; j++) xb[3].x |= wd[4 + (j >> 1)][j & 1][3] & zero;
        }
#pragma unroll
        for (int j = i < 8 ? 2 : 0; j < (i < 8 ? 4 : 2); j++) mma16816(gu[j], wa[j * 8 + ks], (ks & 1) ? xb[ks >> 1].z : xb[ks >> 1].x, (ks & 1) ? xb[ks >> 1].w : xb[ks >> 1].y);
        if (i == 5) {
          const uint32_t dd = da | ((__float_as_uint(gu[2][0]) | __float_as_uint(gu[3][0])) & zero);
          static_for<0, 8>([&](auto jc) { constexpr int j = decltype(jc)::value; ldsm4t_o<4096 + (j & 1) * 2048>(dd ^ ((j >> 1) << 5), wd[4 + (j >> 1)][j & 1]); });
        }
      }
      {
        float o[4];
#pragma unroll
        for (int j = 0; j < 4; j++) o[j] = t == 0 ? gu[0][j] : t == 1 ? gu[1][j] : t == 2 ? gu[2][j] : gu[3][j];
        const float e0 = ((t & 2) ? o[2] : o[0]) + __shfl_xor_sync(~0u, (t & 2) ? o[0] : o[2], 2), e1 = ((t & 2) ? o[3] : o[1]) + __shfl_xor_sync(~0u, (t & 2) ? o[1] : o[3], 2);
        sts1(sm + (wg ? DS1 : DS0) * SLOT_B + 1024 + t128 * 4, __float_as_uint(((t & 1) ? e1 : e0) + __shfl_xor_sync(~0u, (t & 1) ? e0 : e1, 1)));
      }
      TS(25);
      bar_sync(1, 256);
      const uint4 p0 = lds4_o<sb + DS0 * SLOT_B + 1024>(own + lane * 16), p1 = lds4_o<sb + DS1 * SLOT_B + 1024>(own + lane * 16);
      const float g0 = __uint_as_float(p0.x) + __uint_as_float(p1.x), g1 = __uint_as_float(p0.y) + __uint_as_float(p1.y);
      const float u0 = __uint_as_float(p0.z) + __uint_as_float(p1.z), u1 = __uint_as_float(p0.w) + __uint_as_float(p1.w);
      const uint32_t act = pack2(g0 * rcp(1.f + ex2(-1.4426950408889634f * g0)) * u0, g1 * rcp(1.f + ex2(-1.4426950408889634f * g1)) * u1);
      uint32_t bq[4];
#pragma unroll
      for (int i = 0; i < 4; i++) {
        const uint32_t lo = __shfl_sync(~0u, act, i * 8 + 2 * t), hi = __shfl_sync(~0u, act, i * 8 + 2 * t + 1);
        bq[i] = __byte_perm(lo, hi, (g & 1) ? 0x7632 : 0x5410);
      }
      TS(16);
#pragma unroll
      for (int i = 0; i < 8; i++) { ya[i][0] = 0.f; ya[i][1] = 0.f; ya[i][2] = 0.f; ya[i][3] = 0.f; }
#pragma unroll
      for (int ks = 0; ks < 2; ks++)
#pragma unroll
        for (int i = 0; i < 8; i++) mma16816(ya[i], wd[i][ks], bq[ks * 2], bq[ks * 2 + 1]);
      mbar_wait(mb + B_SEL2, 0);
      if (pass || !lds1(msc + 80)) break;
      load_gu(2); load_gu(3);
      bar_sync(1, 256);
    }
    if (fidx >= 0) {
      uint2* const yp = (uint2*)&G.ybuf[((wid * 16 + t * 2) * NFFN + fidx) * 4] + g;
#pragma unroll
      for (int h = 0; h < 2; h++) {
        float o[4];
#pragma unroll
        for (int j = 0; j < 4; j++) o[j] = t == 0 ? ya[h * 4][j] : t == 1 ? ya[h * 4 + 1][j] : t == 2 ? ya[h * 4 + 2][j] : ya[h * 4 + 3][j];
        st_rlx2(yp + h * (8 * NFFN * 8), __float_as_uint(o[0]), __float_as_uint(o[1]));
        st_rlx2(yp + h * (8 * NFFN * 8) + NFFN * 8, __float_as_uint(o[2]), __float_as_uint(o[3]));
      }
    }
    TS(17);
    const uint32_t ty = clk();
    if (wid < 7) {
      const uint4* const yq = &G.ybuf[b * NFFN * 4 + wid * 64 + lane];
      const uint4 sel = lds4(msc + 16 + pass * 32 + (lane & 1) * 16);
      const uint32_t fh = lds1(msc + 96 + (lane & 1) * 16 + (g & 3) * 32 + (cg & 3) * 4);
      const float r = __uint_as_float(sel.x ^ (~(uint32_t)((int)sel.x >> 31) | 0x80000000u));
      float sg = rcp(1.f + ex2(-1.4426950408889634f * r)), base = fmaf((lane & 2) ? bf_hi(fh) : bf_lo(fh), 1.f + __uint_as_float(sel.z), __uint_as_float(sel.w));
      __nv_bfloat16* op = P.out + (size_t)(2047 - (sel.x & 2047)) * D_ + b * 8 + ((lane >> 1) & 7);
      asm volatile("" : "+f"(sg), "+f"(base), "+l"(op) :: "memory");
      delay(ty, YDELAY);
      uint4 v0, v1;
#pragma unroll 1
      for (int it = 0;; it++) {
        v0 = ld_rlx4(yq); v1 = ld_rlx4(yq + 32);
        TSV(22, it + 1);
        if (!__any_sync(~0u, max(max4(0, v0), max4(0, v1)) == SENT)) break;
        SPINCHK(it, 8);
      }
      if (lane == 0) mbar_arrive(sm + bar3(63));
      TS(18);
      float y0 = __uint_as_float(v0.x) + __uint_as_float(v1.x), y1 = __uint_as_float(v0.y) + __uint_as_float(v1.y);
      float y2 = __uint_as_float(v0.z) + __uint_as_float(v1.z), y3 = __uint_as_float(v0.w) + __uint_as_float(v1.w);
      float z0 = ((lane & 16) ? y2 : y0) + __shfl_xor_sync(~0u, (lane & 16) ? y0 : y2, 16), z1 = ((lane & 16) ? y3 : y1) + __shfl_xor_sync(~0u, (lane & 16) ? y1 : y3, 16);
      z0 = ((lane & 8) ? z1 : z0) + __shfl_xor_sync(~0u, (lane & 8) ? z0 : z1, 8);
      z0 += __shfl_xor_sync(~0u, z0, 4);
      const uint32_t yx = sm + OFF_COLSUM;
      if (!(lane & 4)) sts1(yx + (t * 4 + (lane >> 3)) * 32 + wid * 4, __float_as_uint(z0));
      if (wid) bar_arrive(1, 224);
      else {
        bar_sync(1, 224);
        const uint4 a = lds4(yx + (lane & 15) * 32), c = lds4(yx + (lane & 15) * 32 + 16);
        const float y = ((__uint_as_float(a.x) + __uint_as_float(a.y)) + (__uint_as_float(a.z) + __uint_as_float(a.w))) + ((__uint_as_float(c.x) + __uint_as_float(c.y)) + __uint_as_float(c.z));
        if (lane < 16) *op = __float2bfloat16(fmaf(y, sg, base));
        if (b == 0 && lane == 16) G.epoch = lds1(mb + B_SW + 4);
      }
    }
    }
    TS(19); TSG(31);
    if (warp == 0) TS_DUMP(wg);
  }
}

typedef CUresult (*EncodeFn)(CUtensorMap*, CUtensorMapDataType, cuuint32_t, void*, const cuuint64_t*, const cuuint64_t*, const cuuint32_t*,
                             const cuuint32_t*, CUtensorMapInterleave, CUtensorMapSwizzle, CUtensorMapL2promotion, CUtensorMapFloatOOBfill);
void make_map(EncodeFn enc, CUtensorMap* m, const void* p, uint64_t cols, uint64_t rows, uint64_t d0, uint32_t b0, uint32_t b1, uint32_t b2, CUtensorMapSwizzle sw,
              CUtensorMapL2promotion promo = CU_TENSOR_MAP_L2_PROMOTION_L2_128B) {
  cuuint64_t dims[3] = {d0, rows, cols / d0}, str[2] = {cols * 2, d0 * 2};
  cuuint32_t box[3] = {b0, b1, b2}, es[3] = {1, 1, 1};
  enc(m, CU_TENSOR_MAP_DATA_TYPE_BFLOAT16, b2 ? 3 : 2, const_cast<void*>(p), dims, str, box, es, CU_TENSOR_MAP_INTERLEAVE_NONE, sw,
      promo, CU_TENSOR_MAP_FLOAT_OOB_FILL_NONE);
}

}

extern "C" void kernel_launch(void* const* d_in, const int* in_sizes, int n_in, void* d_out, int out_size) {
  (void)in_sizes; (void)n_in; (void)out_size;
  Ptrs P;
  P.x = (const __nv_bfloat16*)d_in[0]; P.wqkv = (const __nv_bfloat16*)d_in[1]; P.wo = (const __nv_bfloat16*)d_in[2];
  P.wr = (const __nv_bfloat16*)d_in[4]; P.wg = (const __nv_bfloat16*)d_in[5]; P.wu = (const __nv_bfloat16*)d_in[6];
  P.wd = (const __nv_bfloat16*)d_in[7]; P.out = (__nv_bfloat16*)d_out;
  void* fn = nullptr;
  cudaDriverEntryPointQueryResult q;
  cudaGetDriverEntryPoint("cuTensorMapEncodeTiled", &fn, cudaEnableDefault, &q);
  EncodeFn enc = (EncodeFn)fn;
  CUtensorMap tmX, tmW, tmO, tmG, tmU, tmD, tmM, tmPG, tmPU, tmPD;
  make_map(enc, &tmX, P.x, D_, S_, D_, 64, 128, 0, CU_TENSOR_MAP_SWIZZLE_128B);
  make_map(enc, &tmW, P.wqkv, 3 * D_, D_, 3 * D_, 64, 64, 0, CU_TENSOR_MAP_SWIZZLE_128B);
  make_map(enc, &tmG, P.wg, F_, D_, F_, 32, 128, 0, CU_TENSOR_MAP_SWIZZLE_64B);
  make_map(enc, &tmU, P.wu, F_, D_, F_, 32, 128, 0, CU_TENSOR_MAP_SWIZZLE_64B);
  make_map(enc, &tmD, P.wd, D_, F_, 64, 64, 32, 4, CU_TENSOR_MAP_SWIZZLE_128B);
  make_map(enc, &tmPG, P.wg, F_, D_, F_, 8, 32, 0, CU_TENSOR_MAP_SWIZZLE_NONE);
  make_map(enc, &tmPU, P.wu, F_, D_, F_, 8, 32, 0, CU_TENSOR_MAP_SWIZZLE_NONE);
  make_map(enc, &tmPD, P.wd, 128, F_ * 8, 128, 8, 32, 0, CU_TENSOR_MAP_SWIZZLE_NONE, CU_TENSOR_MAP_L2_PROMOTION_L2_256B);
  for (int m = 0; m < 2; m++) {
    cuuint64_t dims[4] = {64, m ? 64u : 16u, m ? 16u : 64u, 16}, str[3] = {2 * D_, (m ? 128u : 32u) * D_, 128};
    cuuint32_t box[4] = {64, 16, 4, 2}, es[4] = {1, 1, 1, 1};
    enc(m ? &tmM : &tmO, CU_TENSOR_MAP_DATA_TYPE_BFLOAT16, 4, const_cast<__nv_bfloat16*>(P.wo), dims, str, box, es, CU_TENSOR_MAP_INTERLEAVE_NONE,
        CU_TENSOR_MAP_SWIZZLE_128B, CU_TENSOR_MAP_L2_PROMOTION_L2_128B, CU_TENSOR_MAP_FLOAT_OOB_FILL_NONE);
  }
  cudaFuncSetAttribute(fused_kernel, cudaFuncAttributeMaxDynamicSharedMemorySize, SMEM_BYTES);
  fused_kernel<<<NCTA, 384, SMEM_BYTES>>>(tmX, tmW, tmO, tmG, tmU, tmD, tmM, tmPG, tmPU, tmPD, P);
}
```

```cpp
#include <cuda_runtime.h>
#include <cuda.h>
#include <cuda_bf16.h>
#include <stdint.h>
#include <type_traits>

namespace {

constexpr int S_ = 2048, D_ = 1024, F_ = 3584;
constexpr int NCTA = 128, NFFN = 112;
constexpr uint32_t SENT = 0xFFFFFFFFu;
constexpr int SPIN_LIMIT = 1 << 20;

#define ADELAY 900
#define NPK 0x233333333333ull
#define KDELAY 700
#define SBAR 2
#define NOOUT 0
#define OHOLD 72
#define OUTEF 0
#define CUTS 2
#define EFO 0
#define EFWO 0
#define TMPF 1
#define INIF 0
#define DEV 0xFFEE
#define FDT 100
#define ASTEP 300
#define BDELAY 1500
#define LATEP 0x20
#define GEV 0xDCCB
#define PDS 2
#define D1POS 1
#define GUPOS 1
#define ASYM 2
#define GUP 2
#define PEEL 1
#define B6E 2
#define PD0 2
#define PDT 60
#define KORD 0xBA9F87E6D54C3210ull
#define SDELAY 450
#define LDELAY 500
#define NOSPEC 0
#define LOCK 1
#define STLD 2
#define RELK 1
#define PERT 3
#define QHOLD 3
#define CDELAY 0
#define YDELAY 500
#define EFX 0
#define EFW 1
#define EFF 1
#define GDELAY 800
#define PFST 1
#define W0N 2
constexpr uint32_t STAGE_B = 57344;
__host__ __device__ constexpr uint32_t xoff(int s, int w) { return ((0x87CA3651u >> (4 * (s + 4 * w))) & 15) * 16384; }
__host__ __device__ constexpr uint32_t woff(int s) { return (s < 2 ? 9 * 16384 : 0) + (s & 1) * 8192; }
constexpr uint32_t WSTR = 32768;
constexpr uint32_t OFF_BARS = 229376;
constexpr uint32_t OFF_COLSUM = 229632;
constexpr uint32_t OFF_STATS = 230400;
constexpr uint32_t SMEM_BYTES = 232448;
constexpr uint32_t B_FULL = 0, B_EMPTY = 32, B_AUX = 64, B_SEL2 = 72, B_KVL = 80, B_FULL3 = 88, B_SW = 216, B_OUT = 224, B_LATE = 232, B_SEL = B_FULL + 8, B_FFN = 240;
__host__ __device__ constexpr uint32_t o3(int p) { return p * 8 + (p & 8) * 8; }
__host__ __device__ constexpr uint32_t bar3(int i) { return OFF_STATS + 1024 + (i >> 3) * 128 + ((i & 32) ? 0 : 64) + (i & 7) * 8; }
constexpr uint32_t SLOT_B = 16384;
constexpr uint32_t sb = 1024;
constexpr uint32_t bars = sb + OFF_BARS;
constexpr uint64_t WO_SLOTS = 0x8794208794208794ull;
constexpr uint32_t GU_SLOTS = 0x35356161u, D_SLOTS = 0x9420, DS0 = D_SLOTS & 15, DS1 = (D_SLOTS >> 8) & 15;
constexpr uint32_t HST = 7 * SLOT_B;
constexpr uint32_t OFF_LNP = OFF_STATS;
constexpr uint32_t OFF_MSC = OFF_COLSUM + 512;
constexpr uint32_t OFF_KVB = 2 * SLOT_B + 8192;

struct Scratch {
  uint4 st1[64 * 48];
  uint4 csp[16 * 8 * 48];
  uint4 kvp[16 * 2304];
  uint4 obuf[32 * 64 * 128];
  uint4 st2[S_];
  uint32_t pred[S_];
  uint4 cst[8 * 32];
  uint4 hsel[64 * 128];
  uint32_t cand[8 * 32];
  uint4 ybuf[NCTA * NFFN * 4];
  unsigned epoch;
};
__device__ __align__(1024) Scratch G;
#define TS_DECL
#define TS(i)
#define TSG(i)
#define TSV(i, v)
#define TS_DUMP(slot)
#define PTS(i)

__device__ __forceinline__ uint32_t smem_u32(const void* p) { return (uint32_t)__cvta_generic_to_shared(p); }
__device__ __forceinline__ void mbar_init(uint32_t bar, uint32_t cnt) { asm volatile("mbarrier.init.shared::cta.b64 [%0], %1;" :: "r"(bar), "r"(cnt) : "memory"); }
__device__ __forceinline__ void mbar_expect_tx(uint32_t bar, uint32_t bytes) { asm volatile("mbarrier.arrive.expect_tx.shared::cta.b64 _, [%0], %1;" :: "r"(bar), "r"(bytes) : "memory"); }
__device__ __forceinline__ void mbar_arrive(uint32_t bar) { asm volatile("mbarrier.arrive.shared::cta.b64 _, [%0];" :: "r"(bar) : "memory"); }
#define SPINCHK(it, code) if ((it) > SPIN_LIMIT) break
__device__ __forceinline__ void mbar_wait(uint32_t bar, uint32_t parity) {
  asm volatile("{\n.reg .pred p;\n.reg .u32 c;\nmov.u32 c, 0;\n"
               "WL:\nmbarrier.try_wait.parity.shared::cta.b64 p, [%0], %1;\n@p bra WD;\n"
               "add.u32 c, c, 1;\nsetp.lt.u32 p, c, 1048576;\n@p bra WL;\nWD:\n}" :: "r"(bar), "r"(parity) : "memory");
}
__device__ __forceinline__ uint64_t l2_stream() { uint64_t p; asm("createpolicy.fractional.L2::evict_first.b64 %0, 1.0;" : "=l"(p)); return p; }
__device__ __forceinline__ void tma_2d(uint32_t dst, const CUtensorMap* tm, int c0, int c1, uint32_t bar, bool stream) {
  if (stream) asm volatile("cp.async.bulk.tensor.2d.shared::cluster.global.mbarrier::complete_tx::bytes.L2::cache_hint [%0], [%1, {%3, %4}], [%2], %5;"
                           :: "r"(dst), "l"(tm), "r"(bar), "r"(c0), "r"(c1), "l"(l2_stream()) : "memory");
  else asm volatile("cp.async.bulk.tensor.2d.shared::cluster.global.mbarrier::complete_tx::bytes [%0], [%1, {%3, %4}], [%2];"
                    :: "r"(dst), "l"(tm), "r"(bar), "r"(c0), "r"(c1) : "memory");
}
__device__ __forceinline__ void tma_3d(uint32_t dst, const CUtensorMap* tm, int c0, int c1, int c2, uint32_t bar, bool stream) {
  if (stream) asm volatile("cp.async.bulk.tensor.3d.shared::cluster.global.mbarrier::complete_tx::bytes.L2::cache_hint [%0], [%1, {%3, %4, %5}], [%2], %6;"
                           :: "r"(dst), "l"(tm), "r"(bar), "r"(c0), "r"(c1), "r"(c2), "l"(l2_stream()) : "memory");
  else asm volatile("cp.async.bulk.tensor.3d.shared::cluster.global.mbarrier::complete_tx::bytes [%0], [%1, {%3, %4, %5}], [%2];"
                    :: "r"(dst), "l"(tm), "r"(bar), "r"(c0), "r"(c1), "r"(c2) : "memory");
}
__device__ __forceinline__ void tma_2d_mc(uint32_t dst, const CUtensorMap* tm, int c0, int c1, uint32_t bar, bool stream) {
  if (stream) asm volatile("cp.async.bulk.tensor.2d.shared::cluster.global.mbarrier::complete_tx::bytes.multicast::cluster.L2::cache_hint [%0], [%1, {%3, %4}], [%2], %5, %6;"
                           :: "r"(dst), "l"(tm), "r"(bar), "r"(c0), "r"(c1), "h"((uint16_t)3), "l"(l2_stream()) : "memory");
  else asm volatile("cp.async.bulk.tensor.2d.shared::cluster.global.mbarrier::complete_tx::bytes.multicast::cluster [%0], [%1, {%3, %4}], [%2], %5;"
                    :: "r"(dst), "l"(tm), "r"(bar), "r"(c0), "r"(c1), "h"((uint16_t)3) : "memory");
}
__device__ __forceinline__ bool elect_one() {
  uint32_t p;
  asm volatile("{\n.reg .pred q;\nelect.sync _|q, 0xFFFFFFFF;\nselp.u32 %0, 1, 0, q;\n}" : "=r"(p));
  return p;
}
__device__ __forceinline__ void bulk_load_mc(uint32_t dst, const void* src, uint32_t bar, uint16_t mask) {
  if (EFO) asm volatile("cp.async.bulk.shared::cluster.global.mbarrier::complete_tx::bytes.multicast::cluster.L2::cache_hint [%0], [%1], 8192, [%2], %3, %4;"
               :: "r"(dst), "l"(src), "r"(bar), "h"(mask), "l"(l2_stream()) : "memory");
  else asm volatile("cp.async.bulk.shared::cluster.global.mbarrier::complete_tx::bytes.multicast::cluster [%0], [%1], 8192, [%2], %3;"
               :: "r"(dst), "l"(src), "r"(bar), "h"(mask) : "memory");
}
__device__ __forceinline__ void bulk_load(uint32_t dst, const void* src, uint32_t bytes, uint32_t bar) {
  asm volatile("cp.async.bulk.shared::cluster.global.mbarrier::complete_tx::bytes [%0], [%1], %2, [%3];" :: "r"(dst), "l"(src), "r"(bytes), "r"(bar) : "memory");
}
__device__ __forceinline__ void mbar_arrive_rem(uint32_t bar) { asm volatile("mbarrier.arrive.shared::cluster.b64 _, [%0];" :: "r"(bar) : "memory"); }
template <uint32_t O> __device__ __forceinline__ void ldsm4_o(uint32_t addr, uint32_t& a, uint32_t& b, uint32_t& c, uint32_t& d) {
  asm volatile("ldmatrix.sync.aligned.m8n8.x4.shared.b16 {%0,%1,%2,%3}, [%4+%5];" : "=r"(a), "=r"(b), "=r"(c), "=r"(d) : "r"(addr), "n"(O) : "memory");
}
template <uint32_t O> __device__ __forceinline__ void ldsm4t_o(uint32_t addr, uint32_t (&r)[4]) {
  asm volatile("ldmatrix.sync.aligned.m8n8.x4.trans.shared.b16 {%0,%1,%2,%3}, [%4+%5];" : "=r"(r[0]), "=r"(r[1]), "=r"(r[2]), "=r"(r[3]) : "r"(addr), "n"(O) : "memory");
}
__device__ __forceinline__ void mma16816(float (&c)[4], const uint32_t (&a)[4], uint32_t b0, uint32_t b1) {
  asm("mma.sync.aligned.m16n8k16.row.col.f32.bf16.bf16.f32 {%0,%1,%2,%3}, {%4,%5,%6,%7}, {%8,%9}, {%0,%1,%2,%3};"
      : "+f"(c[0]), "+f"(c[1]), "+f"(c[2]), "+f"(c[3]) : "r"(a[0]), "r"(a[1]), "r"(a[2]), "r"(a[3]), "r"(b0), "r"(b1));
}
__device__ __forceinline__ void l2_prefetch(const void* p) { asm volatile("prefetch.global.L2 [%0];" :: "l"(p) : "memory"); }
__device__ __forceinline__ uint32_t clk() { uint32_t t; asm volatile("mov.u32 %0, %%clock;" : "=r"(t) :: "memory"); return t; }
__device__ __forceinline__ void delay(uint32_t t0, uint32_t n) { while (clk() - t0 < n) {} }
template <int ID> __device__ __forceinline__ void cut(uint32_t zero) { asm volatile("{\n.reg .pred p;\nsetp.eq.u32 p, %0, %1;\nCUT:\n@p nanosleep.u32 1;\n@p bra.uni CUT;\n}" :: "r"(zero), "n"(ID) : "memory"); }
__device__ __forceinline__ void tmap_prefetch(const CUtensorMap* tm) { asm volatile("prefetch.tensormap [%0];" :: "l"(tm) : "memory"); }
__device__ __forceinline__ void wg_fence() { asm volatile("wgmma.fence.sync.aligned;" ::: "memory"); }
__device__ __forceinline__ void wg_commit() { asm volatile("wgmma.commit_group.sync.aligned;" ::: "memory"); }
template <int N> __device__ __forceinline__ void wg_wait() { asm volatile("wgmma.wait_group.sync.aligned %0;" :: "n"(N) : "memory"); }
template <int N> __device__ __forceinline__ void pin(float (&d)[N]) {
#pragma unroll
  for (int i = 0; i < N; i++) asm volatile("" : "+f"(d[i]) :: "memory");
}
__device__ __forceinline__ void pin4(uint4& v) { asm volatile("" : "+r"(v.x), "+r"(v.y), "+r"(v.z), "+r"(v.w) :: "memory"); }
template <uint32_t SBO, uint32_t SWZ> __device__ __forceinline__ uint64_t dsc(uint32_t lo) { return ((uint64_t)((SBO >> 4) | (SWZ << 30)) << 32) | lo; }
__host__ __device__ constexpr uint32_t dlo(uint32_t addr, uint32_t lbo) { return (addr >> 4) | ((lbo >> 4) << 16); }
__device__ __forceinline__ void bar_sync(int id, int n) { asm volatile("bar.sync %0, %1;" :: "r"(id), "r"(n) : "memory"); }
__device__ __forceinline__ void bar_arrive(int id, int n) { asm volatile("bar.arrive %0, %1;" :: "r"(id), "r"(n) : "memory"); }
__device__ __forceinline__ void fence_async_smem() { asm volatile("fence.proxy.async.shared::cta;" ::: "memory"); }
__device__ __forceinline__ void fence_gpu() { asm volatile("fence.acq_rel.gpu;" ::: "memory"); }
__device__ __forceinline__ uint4 ld_cg4(const void* p) { uint4 v; asm volatile("ld.global.cg.v4.u32 {%0,%1,%2,%3}, [%4];" : "=r"(v.x), "=r"(v.y), "=r"(v.z), "=r"(v.w) : "l"(p) : "memory"); return v; }
__device__ __forceinline__ uint4 ld_rlx4(const void* p) { uint4 v; asm volatile("ld.relaxed.gpu.global.v4.u32 {%0,%1,%2,%3}, [%4];" : "=r"(v.x), "=r"(v.y), "=r"(v.z), "=r"(v.w) : "l"(p) : "memory"); return v; }
__device__ __forceinline__ uint32_t ld_rlx(const void* p) { uint32_t v; asm volatile("ld.relaxed.gpu.global.u32 %0, [%1];" : "=r"(v) : "l"(p) : "memory"); return v; }
__device__ __forceinline__ void st_rlx4(void* p, uint4 v) { asm volatile("st.relaxed.gpu.global.v4.u32 [%0], {%1,%2,%3,%4};" :: "l"(p), "r"(v.x), "r"(v.y), "r"(v.z), "r"(v.w) : "memory"); }
__device__ __forceinline__ void st_rlx2(void* p, uint32_t a, uint32_t b) { asm volatile("st.relaxed.gpu.global.v2.u32 [%0], {%1,%2};" :: "l"(p), "r"(a), "r"(b) : "memory"); }
__device__ __forceinline__ void st_rlx(void* p, uint32_t a) { asm volatile("st.relaxed.gpu.global.u32 [%0], %1;" :: "l"(p), "r"(a) : "memory"); }
__device__ __forceinline__ void red4(bool on, void* p, float a, float b, float c, float d) {
  asm volatile("{\n.reg .pred q;\nsetp.ne.b32 q, %5, 0;\n@q red.relaxed.gpu.global.add.v4.f32 [%0], {%1,%2,%3,%4};\n}" :: "l"(p), "f"(a), "f"(b), "f"(c), "f"(d), "r"((int)on) : "memory");
}
__device__ __forceinline__ uint32_t pack2(float lo, float hi) { uint32_t r; asm("cvt.rn.bf16x2.f32 %0, %1, %2;" : "=r"(r) : "f"(hi), "f"(lo)); return r; }
__device__ __forceinline__ float bf_lo(uint32_t v) { return __uint_as_float(v << 16); }
__device__ __forceinline__ float bf_hi(uint32_t v) { return __uint_as_float(v & 0xFFFF0000u); }
__device__ __forceinline__ void stsm4(uint32_t addr, uint32_t a, uint32_t b, uint32_t c, uint32_t d) {
  asm volatile("stmatrix.sync.aligned.m8n8.x4.shared.b16 [%0], {%1,%2,%3,%4};" :: "r"(addr), "r"(a), "r"(b), "r"(c), "r"(d) : "memory");
}
template <uint32_t O> __device__ __forceinline__ void stsm4_o(uint32_t addr, uint32_t a, uint32_t b, uint32_t c, uint32_t d) {
  asm volatile("stmatrix.sync.aligned.m8n8.x4.shared.b16 [%0+%5], {%1,%2,%3,%4};" :: "r"(addr), "r"(a), "r"(b), "r"(c), "r"(d), "n"(O) : "memory");
}
__device__ __forceinline__ void sts4(uint32_t addr, uint32_t a, uint32_t b, uint32_t c, uint32_t d) { asm volatile("st.shared.v4.u32 [%0], {%1,%2,%3,%4};" :: "r"(addr), "r"(a), "r"(b), "r"(c), "r"(d) : "memory"); }
__device__ __forceinline__ void sts2f(uint32_t addr, float a, float b) { asm volatile("st.shared.v2.f32 [%0], {%1,%2};" :: "r"(addr), "f"(a), "f"(b) : "memory"); }
__device__ __forceinline__ void sts1(uint32_t addr, uint32_t a) { asm volatile("st.shared.u32 [%0], %1;" :: "r"(addr), "r"(a) : "memory"); }
__device__ __forceinline__ float2 lds2f(uint32_t addr) { float2 v; asm volatile("ld.shared.v2.f32 {%0,%1}, [%2];" : "=f"(v.x), "=f"(v.y) : "r"(addr) : "memory"); return v; }
template <uint32_t O> __device__ __forceinline__ float2 lds2f_o(uint32_t addr) { float2 v; asm volatile("ld.shared.v2.f32 {%0,%1}, [%2+%3];" : "=f"(v.x), "=f"(v.y) : "r"(addr), "n"(O) : "memory"); return v; }
template <int I, int N, class F> __device__ __forceinline__ void static_for(F&& f) { if constexpr (I < N) { f(std::integral_constant<int, I>{}); static_for<I + 1, N>(f); } }
__device__ __forceinline__ uint4 lds4(uint32_t addr) { uint4 v; asm volatile("ld.shared.v4.u32 {%0,%1,%2,%3}, [%4];" : "=r"(v.x), "=r"(v.y), "=r"(v.z), "=r"(v.w) : "r"(addr) : "memory"); return v; }
__device__ __forceinline__ uint32_t lds1(uint32_t addr) { uint32_t v; asm volatile("ld.shared.u32 %0, [%1];" : "=r"(v) : "r"(addr) : "memory"); return v; }
__device__ __forceinline__ float ex2(float x) { float y; asm("ex2.approx.ftz.f32 %0, %1;" : "=f"(y) : "f"(x)); return y; }
__device__ __forceinline__ uint32_t max4(uint32_t m, const uint4& v) { return __vimax3_u32(__vimax3_u32(m, v.x, v.y), v.z, v.w); }
__device__ __forceinline__ float rsq(float x) { float y; asm("rsqrt.approx.ftz.f32 %0, %1;" : "=f"(y) : "f"(x)); return y; }
__device__ __forceinline__ float rcp(float x) { float y; asm("rcp.approx.ftz.f32 %0, %1;" : "=f"(y) : "f"(x)); return y; }
__device__ __forceinline__ uint2 ld_rlx2(const void* p) { uint2 v; asm volatile("ld.relaxed.gpu.global.v2.u32 {%0,%1}, [%2];" : "=r"(v.x), "=r"(v.y) : "l"(p) : "memory"); return v; }
template <uint32_t O> __device__ __forceinline__ uint4 lds4_o(uint32_t addr) { uint4 v; asm volatile("ld.shared.v4.u32 {%0,%1,%2,%3}, [%4+%5];" : "=r"(v.x), "=r"(v.y), "=r"(v.z), "=r"(v.w) : "r"(addr), "n"(O) : "memory"); return v; }
__device__ __forceinline__ uint32_t hadd2(uint32_t a, uint32_t b) { uint32_t r; asm("add.rn.bf16x2 %0, %1, %2;" : "=r"(r) : "r"(a), "r"(b)); return r; }
__device__ __forceinline__ uint4 hadd8(const uint4& a, const uint4& b) { return make_uint4(hadd2(a.x, b.x), hadd2(a.y, b.y), hadd2(a.z, b.z), hadd2(a.w, b.w)); }
__device__ __forceinline__ bool hnan(uint32_t a) { return (a & 0x7FFF0000u) > 0x7F800000u; }
__device__ __forceinline__ uint32_t hfma2(uint32_t a, uint32_t b, uint32_t c) { uint32_t r; asm("fma.rn.bf16x2 %0, %1, %2, %3;" : "=r"(r) : "r"(a), "r"(b), "r"(c)); return r; }
__device__ __forceinline__ uint32_t ordered(float v) { const uint32_t u = __float_as_uint(v); return u ^ ((uint32_t)((int)u >> 31) | 0x80000000u); }
__device__ __forceinline__ uint32_t route(const uint4& v, float sw, int row, float2& pr) {
  const float mean = __uint_as_float(v.x) * (1.f / D_);
  pr.x = rsq(fmaxf(fmaf(-mean, mean, __uint_as_float(v.y) * (1.f / D_)), 0.f) + 1e-5f);
  pr.y = -mean * pr.x;
  return min(ordered(pr.x * fmaf(-mean, sw, __uint_as_float(v.z))) & ~2047u, 0xFFFFF000u) | (2047 - row);
}
__device__ __forceinline__ uint2 top2(uint32_t a, uint32_t b, uint32_t c, uint32_t d) {
  const uint32_t h0 = max(a, b), h1 = max(c, d), h = max(h0, h1), l = __vimax3_u32(min(h0, h1), min(a, b), min(c, d));
  const uint32_t m1 = __reduce_max_sync(~0u, h);
  return make_uint2(m1, __reduce_max_sync(~0u, h == m1 ? l : h));
}
__device__ __forceinline__ uint32_t hmul2(uint32_t a, uint32_t b) { uint32_t r; asm("mul.rn.bf16x2 %0, %1, %2;" : "=r"(r) : "r"(a), "r"(b)); return r; }
__device__ __forceinline__ uint32_t phi2(float u0, float u1, uint32_t r2, float rl) {
  uint32_t p, r;
  asm("cvt.rn.relu.bf16x2.f32 %0, %1, %2;" : "=r"(p) : "f"(u1), "f"(u0));
  asm("fma.rn.bf16x2 %0, %1, %2, %3;" : "=r"(r) : "r"(p), "r"(r2), "r"(pack2(__saturatef(ex2(u0 * rl) + 1e-6f), __saturatef(ex2(u1 * rl) + 1e-6f))));
  return r;
}

template<int TA, int TB, int OFF, int SZ> __device__ __forceinline__ void wgmma_n192_ss(float (&d)[SZ], uint64_t da, uint64_t db, int scale_d) {
  asm volatile("{\n.reg .pred p;\nsetp.ne.b32 p, %98, 0;\n"
    "wgmma.mma_async.sync.aligned.m64n192k16.f32.bf16.bf16 {%0,%1,%2,%3,%4,%5,%6,%7,%8,%9,%10,%11,%12,%13,%14,%15,%16,%17,%18,%19,%20,%21,%22,%23,%24,%25,%26,%27,%28,%29,%30,%31,%32,%33,%34,%35,%36,%37,%38,%39,%40,%41,%42,%43,%44,%45,%46,%47,%48,%49,%50,%51,%52,%53,%54,%55,%56,%57,%58,%59,%60,%61,%62,%63,%64,%65,%66,%67,%68,%69,%70,%71,%72,%73,%74,%75,%76,%77,%78,%79,%80,%81,%82,%83,%84,%85,%86,%87,%88,%89,%90,%91,%92,%93,%94,%95}, %96, %97, p, 1, 1, %99, %100;\n}\n"
    : "+f"(d[OFF+0]), "+f"(d[OFF+1]), "+f"(d[OFF+2]), "+f"(d[OFF+3]), "+f"(d[OFF+4]), "+f"(d[OFF+5]), "+f"(d[OFF+6]), "+f"(d[OFF+7]),
      "+f"(d[OFF+8]), "+f"(d[OFF+9]), "+f"(d[OFF+10]), "+f"(d[OFF+11]), "+f"(d[OFF+12]), "+f"(d[OFF+13]), "+f"(d[OFF+14]), "+f"(d[OFF+15]),
      "+f"(d[OFF+16]), "+f"(d[OFF+17]), "+f"(d[OFF+18]), "+f"(d[OFF+19]), "+f"(d[OFF+20]), "+f"(d[OFF+21]), "+f"(d[OFF+22]), "+f"(d[OFF+23]),
      "+f"(d[OFF+24]), "+f"(d[OFF+25]), "+f"(d[OFF+26]), "+f"(d[OFF+27]), "+f"(d[OFF+28]), "+f"(d[OFF+29]), "+f"(d[OFF+30]), "+f"(d[OFF+31]),
      "+f"(d[OFF+32]), "+f"(d[OFF+33]), "+f"(d[OFF+34]), "+f"(d[OFF+35]), "+f"(d[OFF+36]), "+f"(d[OFF+37]), "+f"(d[OFF+38]), "+f"(d[OFF+39]),
      "+f"(d[OFF+40]), "+f"(d[OFF+41]), "+f"(d[OFF+42]), "+f"(d[OFF+43]), "+f"(d[OFF+44]), "+f"(d[OFF+45]), "+f"(d[OFF+46]), "+f"(d[OFF+47]),
      "+f"(d[OFF+48]), "+f"(d[OFF+49]), "+f"(d[OFF+50]), "+f"(d[OFF+51]), "+f"(d[OFF+52]), "+f"(d[OFF+53]), "+f"(d[OFF+54]), "+f"(d[OFF+55]),
      "+f"(d[OFF+56]), "+f"(d[OFF+57]), "+f"(d[OFF+58]), "+f"(d[OFF+59]), "+f"(d[OFF+60]), "+f"(d[OFF+61]), "+f"(d[OFF+62]), "+f"(d[OFF+63]),
      "+f"(d[OFF+64]), "+f"(d[OFF+65]), "+f"(d[OFF+66]), "+f"(d[OFF+67]), "+f"(d[OFF+68]), "+f"(d[OFF+69]), "+f"(d[OFF+70]), "+f"(d[OFF+71]),
      "+f"(d[OFF+72]), "+f"(d[OFF+73]), "+f"(d[OFF+74]), "+f"(d[OFF+75]), "+f"(d[OFF+76]), "+f"(d[OFF+77]), "+f"(d[OFF+78]), "+f"(d[OFF+79]),
      "+f"(d[OFF+80]), "+f"(d[OFF+81]), "+f"(d[OFF+82]), "+f"(d[OFF+83]), "+f"(d[OFF+84]), "+f"(d[OFF+85]), "+f"(d[OFF+86]), "+f"(d[OFF+87]),
      "+f"(d[OFF+88]), "+f"(d[OFF+89]), "+f"(d[OFF+90]), "+f"(d[OFF+91]), "+f"(d[OFF+92]), "+f"(d[OFF+93]), "+f"(d[OFF+94]), "+f"(d[OFF+95])
    : "l"(da), "l"(db), "r"(scale_d), "n"(TA), "n"(TB));
}
template<int TA, int TB, int OFF, int SZ> __device__ __forceinline__ void wgmma_n128_ss(float (&d)[SZ], uint64_t da, uint64_t db, int scale_d) {
  asm volatile("{\n.reg .pred p;\nsetp.ne.b32 p, %66, 0;\n"
    "wgmma.mma_async.sync.aligned.m64n128k16.f32.bf16.bf16 {%0,%1,%2,%3,%4,%5,%6,%7,%8,%9,%10,%11,%12,%13,%14,%15,%16,%17,%18,%19,%20,%21,%22,%23,%24,%25,%26,%27,%28,%29,%30,%31,%32,%33,%34,%35,%36,%37,%38,%39,%40,%41,%42,%43,%44,%45,%46,%47,%48,%49,%50,%51,%52,%53,%54,%55,%56,%57,%58,%59,%60,%61,%62,%63}, %64, %65, p, 1, 1, %67, %68;\n}\n"
    : "+f"(d[OFF+0]), "+f"(d[OFF+1]), "+f"(d[OFF+2]), "+f"(d[OFF+3]), "+f"(d[OFF+4]), "+f"(d[OFF+5]), "+f"(d[OFF+6]), "+f"(d[OFF+7]),
      "+f"(d[OFF+8]), "+f"(d[OFF+9]), "+f"(d[OFF+10]), "+f"(d[OFF+11]), "+f"(d[OFF+12]), "+f"(d[OFF+13]), "+f"(d[OFF+14]), "+f"(d[OFF+15]),
      "+f"(d[OFF+16]), "+f"(d[OFF+17]), "+f"(d[OFF+18]), "+f"(d[OFF+19]), "+f"(d[OFF+20]), "+f"(d[OFF+21]), "+f"(d[OFF+22]), "+f"(d[OFF+23]),
      "+f"(d[OFF+24]), "+f"(d[OFF+25]), "+f"(d[OFF+26]), "+f"(d[OFF+27]), "+f"(d[OFF+28]), "+f"(d[OFF+29]), "+f"(d[OFF+30]), "+f"(d[OFF+31]),
      "+f"(d[OFF+32]), "+f"(d[OFF+33]), "+f"(d[OFF+34]), "+f"(d[OFF+35]), "+f"(d[OFF+36]), "+f"(d[OFF+37]), "+f"(d[OFF+38]), "+f"(d[OFF+39]),
      "+f"(d[OFF+40]), "+f"(d[OFF+41]), "+f"(d[OFF+42]), "+f"(d[OFF+43]), "+f"(d[OFF+44]), "+f"(d[OFF+45]), "+f"(d[OFF+46]), "+f"(d[OFF+47]),
      "+f"(d[OFF+48]), "+f"(d[OFF+49]), "+f"(d[OFF+50]), "+f"(d[OFF+51]), "+f"(d[OFF+52]), "+f"(d[OFF+53]), "+f"(d[OFF+54]), "+f"(d[OFF+55]),
      "+f"(d[OFF+56]), "+f"(d[OFF+57]), "+f"(d[OFF+58]), "+f"(d[OFF+59]), "+f"(d[OFF+60]), "+f"(d[OFF+61]), "+f"(d[OFF+62]), "+f"(d[OFF+63])
    : "l"(da), "l"(db), "r"(scale_d), "n"(TA), "n"(TB));
}
template<int TA, int TB, int OFF, int SZ> __device__ __forceinline__ void wgmma_n64_ss(float (&d)[SZ], uint64_t da, uint64_t db, int scale_d) {
  asm volatile("{\n.reg .pred p;\nsetp.ne.b32 p, %34, 0;\n"
    "wgmma.mma_async.sync.aligned.m64n64k16.f32.bf16.bf16 {%0,%1,%2,%3,%4,%5,%6,%7,%8,%9,%10,%11,%12,%13,%14,%15,%16,%17,%18,%19,%20,%21,%22,%23,%24,%25,%26,%27,%28,%29,%30,%31}, %32, %33, p, 1, 1, %35, %36;\n}\n"
    : "+f"(d[OFF+0]), "+f"(d[OFF+1]), "+f"(d[OFF+2]), "+f"(d[OFF+3]), "+f"(d[OFF+4]), "+f"(d[OFF+5]), "+f"(d[OFF+6]), "+f"(d[OFF+7]),
      "+f"(d[OFF+8]), "+f"(d[OFF+9]), "+f"(d[OFF+10]), "+f"(d[OFF+11]), "+f"(d[OFF+12]), "+f"(d[OFF+13]), "+f"(d[OFF+14]), "+f"(d[OFF+15]),
      "+f"(d[OFF+16]), "+f"(d[OFF+17]), "+f"(d[OFF+18]), "+f"(d[OFF+19]), "+f"(d[OFF+20]), "+f"(d[OFF+21]), "+f"(d[OFF+22]), "+f"(d[OFF+23]),
      "+f"(d[OFF+24]), "+f"(d[OFF+25]), "+f"(d[OFF+26]), "+f"(d[OFF+27]), "+f"(d[OFF+28]), "+f"(d[OFF+29]), "+f"(d[OFF+30]), "+f"(d[OFF+31])
    : "l"(da), "l"(db), "r"(scale_d), "n"(TA), "n"(TB));
}
template<int TB, int OFF, int SZ> __device__ __forceinline__ void wgmma_n64_rs(float (&d)[SZ], uint32_t a0, uint32_t a1, uint32_t a2, uint32_t a3, uint64_t db, int scale_d) {
  asm volatile("{\n.reg .pred p;\nsetp.ne.b32 p, %37, 0;\n"
    "wgmma.mma_async.sync.aligned.m64n64k16.f32.bf16.bf16 {%0,%1,%2,%3,%4,%5,%6,%7,%8,%9,%10,%11,%12,%13,%14,%15,%16,%17,%18,%19,%20,%21,%22,%23,%24,%25,%26,%27,%28,%29,%30,%31}, {%32,%33,%34,%35}, %36, p, 1, 1, %38;\n}\n"
    : "+f"(d[OFF+0]), "+f"(d[OFF+1]), "+f"(d[OFF+2]), "+f"(d[OFF+3]), "+f"(d[OFF+4]), "+f"(d[OFF+5]), "+f"(d[OFF+6]), "+f"(d[OFF+7]),
      "+f"(d[OFF+8]), "+f"(d[OFF+9]), "+f"(d[OFF+10]), "+f"(d[OFF+11]), "+f"(d[OFF+12]), "+f"(d[OFF+13]), "+f"(d[OFF+14]), "+f"(d[OFF+15]),
      "+f"(d[OFF+16]), "+f"(d[OFF+17]), "+f"(d[OFF+18]), "+f"(d[OFF+19]), "+f"(d[OFF+20]), "+f"(d[OFF+21]), "+f"(d[OFF+22]), "+f"(d[OFF+23]),
      "+f"(d[OFF+24]), "+f"(d[OFF+25]), "+f"(d[OFF+26]), "+f"(d[OFF+27]), "+f"(d[OFF+28]), "+f"(d[OFF+29]), "+f"(d[OFF+30]), "+f"(d[OFF+31])
    : "r"(a0), "r"(a1), "r"(a2), "r"(a3), "l"(db), "r"(scale_d), "n"(TB));
}
template<int TA, int TB, int OFF, int SZ> __device__ __forceinline__ void wgmma_n72_ss(float (&d)[SZ], uint64_t da, uint64_t db, int scale_d) {
  asm volatile("{\n.reg .pred p;\nsetp.ne.b32 p, %38, 0;\n"
    "wgmma.mma_async.sync.aligned.m64n72k16.f32.bf16.bf16 {%0,%1,%2,%3,%4,%5,%6,%7,%8,%9,%10,%11,%12,%13,%14,%15,%16,%17,%18,%19,%20,%21,%22,%23,%24,%25,%26,%27,%28,%29,%30,%31,%32,%33,%34,%35}, %36, %37, p, 1, 1, %39, %40;\n}\n"
    : "+f"(d[OFF+0]), "+f"(d[OFF+1]), "+f"(d[OFF+2]), "+f"(d[OFF+3]), "+f"(d[OFF+4]), "+f"(d[OFF+5]), "+f"(d[OFF+6]), "+f"(d[OFF+7]),
      "+f"(d[OFF+8]), "+f"(d[OFF+9]), "+f"(d[OFF+10]), "+f"(d[OFF+11]), "+f"(d[OFF+12]), "+f"(d[OFF+13]), "+f"(d[OFF+14]), "+f"(d[OFF+15]),
      "+f"(d[OFF+16]), "+f"(d[OFF+17]), "+f"(d[OFF+18]), "+f"(d[OFF+19]), "+f"(d[OFF+20]), "+f"(d[OFF+21]), "+f"(d[OFF+22]), "+f"(d[OFF+23]),
      "+f"(d[OFF+24]), "+f"(d[OFF+25]), "+f"(d[OFF+26]), "+f"(d[OFF+27]), "+f"(d[OFF+28]), "+f"(d[OFF+29]), "+f"(d[OFF+30]), "+f"(d[OFF+31]),
      "+f"(d[OFF+32]), "+f"(d[OFF+33]), "+f"(d[OFF+34]), "+f"(d[OFF+35])
    : "l"(da), "l"(db), "r"(scale_d), "n"(TA), "n"(TB));
}
template<int TB, int OFF, int SZ> __device__ __forceinline__ void wgmma_n40_rs(float (&d)[SZ], uint32_t a0, uint32_t a1, uint32_t a2, uint32_t a3, uint64_t db, int scale_d) {
  asm volatile("{\n.reg .pred p;\nsetp.ne.b32 p, %25, 0;\n"
    "wgmma.mma_async.sync.aligned.m64n40k16.f32.bf16.bf16 {%0,%1,%2,%3,%4,%5,%6,%7,%8,%9,%10,%11,%12,%13,%14,%15,%16,%17,%18,%19}, {%20,%21,%22,%23}, %24, p, 1, 1, %26;\n}\n"
    : "+f"(d[OFF+0]), "+f"(d[OFF+1]), "+f"(d[OFF+2]), "+f"(d[OFF+3]), "+f"(d[OFF+4]), "+f"(d[OFF+5]), "+f"(d[OFF+6]), "+f"(d[OFF+7]),
      "+f"(d[OFF+8]), "+f"(d[OFF+9]), "+f"(d[OFF+10]), "+f"(d[OFF+11]), "+f"(d[OFF+12]), "+f"(d[OFF+13]), "+f"(d[OFF+14]), "+f"(d[OFF+15]),
      "+f"(d[OFF+16]), "+f"(d[OFF+17]), "+f"(d[OFF+18]), "+f"(d[OFF+19])
    : "r"(a0), "r"(a1), "r"(a2), "r"(a3), "l"(db), "r"(scale_d), "n"(TB));
}
template<int TB, int OFF, int SZ> __device__ __forceinline__ void wgmma_n128_rs(float (&d)[SZ], uint32_t a0, uint32_t a1, uint32_t a2, uint32_t a3, uint64_t db, int scale_d) {
  asm volatile("{\n.reg .pred p;\nsetp.ne.b32 p, %69, 0;\n"
    "wgmma.mma_async.sync.aligned.m64n128k16.f32.bf16.bf16 {%0,%1,%2,%3,%4,%5,%6,%7,%8,%9,%10,%11,%12,%13,%14,%15,%16,%17,%18,%19,%20,%21,%22,%23,%24,%25,%26,%27,%28,%29,%30,%31,%32,%33,%34,%35,%36,%37,%38,%39,%40,%41,%42,%43,%44,%45,%46,%47,%48,%49,%50,%51,%52,%53,%54,%55,%56,%57,%58,%59,%60,%61,%62,%63}, {%64,%65,%66,%67}, %68, p, 1, 1, %70;\n}\n"
    : "+f"(d[OFF+0]), "+f"(d[OFF+1]), "+f"(d[OFF+2]), "+f"(d[OFF+3]), "+f"(d[OFF+4]), "+f"(d[OFF+5]), "+f"(d[OFF+6]), "+f"(d[OFF+7]),
      "+f"(d[OFF+8]), "+f"(d[OFF+9]), "+f"(d[OFF+10]), "+f"(d[OFF+11]), "+f"(d[OFF+12]), "+f"(d[OFF+13]), "+f"(d[OFF+14]), "+f"(d[OFF+15]),
      "+f"(d[OFF+16]), "+f"(d[OFF+17]), "+f"(d[OFF+18]), "+f"(d[OFF+19]), "+f"(d[OFF+20]), "+f"(d[OFF+21]), "+f"(d[OFF+22]), "+f"(d[OFF+23]),
      "+f"(d[OFF+24]), "+f"(d[OFF+25]), "+f"(d[OFF+26]), "+f"(d[OFF+27]), "+f"(d[OFF+28]), "+f"(d[OFF+29]), "+f"(d[OFF+30]), "+f"(d[OFF+31]),
      "+f"(d[OFF+32]), "+f"(d[OFF+33]), "+f"(d[OFF+34]), "+f"(d[OFF+35]), "+f"(d[OFF+36]), "+f"(d[OFF+37]), "+f"(d[OFF+38]), "+f"(d[OFF+39]),
      "+f"(d[OFF+40]), "+f"(d[OFF+41]), "+f"(d[OFF+42]), "+f"(d[OFF+43]), "+f"(d[OFF+44]), "+f"(d[OFF+45]), "+f"(d[OFF+46]), "+f"(d[OFF+47]),
      "+f"(d[OFF+48]), "+f"(d[OFF+49]), "+f"(d[OFF+50]), "+f"(d[OFF+51]), "+f"(d[OFF+52]), "+f"(d[OFF+53]), "+f"(d[OFF+54]), "+f"(d[OFF+55]),
      "+f"(d[OFF+56]), "+f"(d[OFF+57]), "+f"(d[OFF+58]), "+f"(d[OFF+59]), "+f"(d[OFF+60]), "+f"(d[OFF+61]), "+f"(d[OFF+62]), "+f"(d[OFF+63])
    : "r"(a0), "r"(a1), "r"(a2), "r"(a3), "l"(db), "r"(scale_d), "n"(TB));
}

struct Ptrs { const __nv_bfloat16 *x, *wqkv, *wo, *wr, *wg, *wu, *wd; __nv_bfloat16* out; };

__global__ void __cluster_dims__(2, 1, 1) __launch_bounds__(384, 1) fused_kernel(const __grid_constant__ CUtensorMap tmX, const __grid_constant__ CUtensorMap tmW,
                                                       const __grid_constant__ CUtensorMap tmO, const __grid_constant__ CUtensorMap tmG,
                                                       const __grid_constant__ CUtensorMap tmU, const __grid_constant__ CUtensorMap tmD,
                                                       const __grid_constant__ CUtensorMap tmM, const __grid_constant__ CUtensorMap tmPG,
                                                       const __grid_constant__ CUtensorMap tmPU, const __grid_constant__ CUtensorMap tmPD,
                                                       const Ptrs P) {
  extern __shared__ __align__(1024) uint8_t smem_raw[];
  if (TMPF && threadIdx.x == 0) { tmap_prefetch(&tmX); tmap_prefetch(&tmW); }
  const int tid = threadIdx.x, wid = __shfl_sync(~0u, tid >> 5, 0), wg = __shfl_sync(~0u, tid >> 7, 0), lane = tid & 31;
  const int pj = blockIdx.x >> 1, pi = pj - 36;
  const int b = (pj < 4 ? 32 + pj * 8 : pj < 36 ? pj - 4 : 33 + pi + ((pi * 37) >> 8)) * 2 + (blockIdx.x & 1);
  const int rb = b >> 4, cg = b & 15, hf = cg >> 3, c3 = cg & 7;
  const int jp = cg >> 1;
  const int fidx = jp == rb ? -1 : b - 2 * rb - (jp > rb ? 2 : 0);
  const uint32_t rank = b & 1, own = rank << 24;
  const uint32_t zero = gridDim.y - 1;
  const uint32_t sm = own + sb, mb = own + bars;
  auto chunk_of = [&](int p) { return (int)((0x1765432FEDCBA980ull >> (4 * p)) & 15) ^ (p == 0 || p == 15 ? cg : p < 9 ? cg & 8 : cg & 14); };
  const int kl = (jp & 3) * 256;
  auto k_of = [&](int kb) { return kb >= 12 ? kl + (kb - 12) * 64 : kb * 64 < kl ? kb * 64 : kb * 64 + 256; };
  auto load_w = [&](int kb) {
#pragma unroll
    for (int i = 0; i < 3; i++) tma_2d(sm + woff(kb & 3) + i * WSTR, &tmW, i * D_ + cg * 64, k_of(kb), mb + B_FULL + 8 * (kb & 3), EFW);
  };
  TS_DECL; TS(0); TSG(30);
  if (wid == 8) {
    if (elect_one()) {
      if (smem_u32(smem_raw) != sm) {
#pragma unroll
        for (int i = 0; i < PERT; i++) sts1(mb, lds1(mb));
        asm volatile("trap;");
      }
#pragma unroll
      for (int s = 0; s < 4; s++) mbar_init(mb + B_FULL + 8 * s, 1);
      asm volatile("fence.mbarrier_init.release.cluster;" ::: "memory");
      if (INIF) fence_async_smem();
    }
  } else if (wid == 9) {
    if (elect_one()) {
#pragma unroll
      for (int i = 4; i < 32; i++)
        if (i != 27) mbar_init(mb + 8 * i, i < 8 ? 8 : i == 8 ? 64 : i == 26 ? 2 : i == 29 ? 4 : 1);
      asm volatile("fence.mbarrier_init.release.cluster;" ::: "memory");
      if (INIF) fence_async_smem();
    }
  }
  __syncwarp();
  asm volatile("barrier.cluster.arrive.relaxed.aligned;" ::: "memory");
  if (wid == 8) {
    if (elect_one()) {
      mbar_expect_tx(mb + B_FULL, STAGE_B);
      tma_2d(sm + xoff(0, 0), &tmX, k_of(0), rb * 256, mb + B_FULL, EFX);
      tma_2d(sm + xoff(0, 1), &tmX, k_of(0), rb * 256 + 128, mb + B_FULL, EFX);
      load_w(0);
    }
    __syncwarp();
  }
  asm volatile("barrier.cluster.wait.aligned;" ::: "memory");

  if (wg == 2) {
    asm volatile("setmaxnreg.dec.sync.aligned.u32 56;");
    auto wait3 = [&](int i) { mbar_wait(sm + bar3(i), 0); };
    if (wid == 8) {
      if (elect_one()) {
        int np = fidx >= 0 ? 0 : 32;
        if (fidx >= 0) mbar_expect_tx(mb + B_FFN, 32 * 512);
#pragma unroll 1
        for (int kb = 1; kb < 16 - PEEL; kb++) {
          const uint32_t fb = mb + B_FULL + 8 * (kb & 3);
          mbar_wait(fb + B_EMPTY, ((kb >> 2) & 1) ^ 1);
          mbar_expect_tx(fb, STAGE_B);
          tma_2d_mc(sm + xoff(kb & 3, rank), &tmX, k_of(kb), rb * 256 + rank * 128, fb, EFX);
          load_w(kb);
          if (kb >= 12) asm volatile("mbarrier.arrive.shared::cta.b64 _, [%0], 7;" :: "r"(fb + B_EMPTY) : "memory");
#pragma unroll 1
          for (int n = ((NPK << 16) >> (4 * kb)) & 15; n > 0 && np < 32; n--, np++)
            tma_2d(sm + OFF_STATS + 512, (np & 1) ? &tmPU : &tmPG, (fidx >> 1) * 64, (np >> 1) * 64 + rank * 32, mb + B_FFN, false);
        }
        if (PEEL) {
          mbar_wait(mb + B_EMPTY + 24, 0);
          tma_2d_mc(sm + xoff(3, rank), &tmX, kl + 192, rb * 256 + rank * 128, mb + B_FULL + 24, EFX);
          load_w(15);
          mbar_expect_tx(mb + B_FULL + 24, STAGE_B);
        }
        if (fidx >= 0) { mbar_wait(mb + B_FFN, 0); mbar_expect_tx(mb + B_FFN, 65536 + 8 * 512); mbar_expect_tx(mb + B_FFN + 8, 65536); }
#pragma unroll
        for (int p = 4; p < 8; p++) sts4(sm + OFF_STATS + p * 144, 0x3F803F80u, 0x3F803F80u, 0x3F803F80u, 0x3F803F80u);
        fence_async_smem();
        mbar_arrive(mb + B_LATE);
        PTS(2);
        mbar_expect_tx(mb + B_KVL, 36864);
        mbar_wait(mb + B_LATE, 0);
        wait3(60);
        delay(clk(), KDELAY);
        bulk_load(sm + 11 * SLOT_B, &G.kvp[cg * 2304], SLOT_B, mb + B_KVL);
        bulk_load(sm + 13 * SLOT_B, &G.kvp[cg * 2304 + 1024], SLOT_B, mb + B_KVL);
        bulk_load(sm + 2 * SLOT_B, &G.kvp[cg * 2304 + 2048], 4096, mb + B_KVL);
        PTS(3);
        const uint4* src = &G.obuf[(rb * 4 + rank * 2 + hf) * 64 * 128];
        wait3(48);
        const uint32_t t1 = clk();
#pragma unroll
        for (int p = 1; p < 5; p++) {
          delay(t1, ADELAY + (p - 1) * ASTEP);
          bulk_load_mc(sm + (10 + (p & 3)) * SLOT_B + rank * 8192, src + ((hf ^ 1) * 8 + p - 1) * 512, sm + bar3(p) + rank * 256, 3);
        }
        PTS(7);
#pragma unroll 1
        for (int i = 5; i < 17; i++) {
          const int p = min(i, 15);
          const uint32_t d = sm + (10 + (p & 3)) * SLOT_B + rank * 8192, fb = sm + bar3(0) + o3(p) + rank * 256;
          const uint4* q = src + chunk_of(i & 15) * 512;
          mbar_wait(sm + bar3(48) + o3(p - 4 + ((LATEP >> p) & 1)), 0);
          bulk_load_mc(d, q, fb, i < 15 ? 3 : 1 << ((i ^ rank ^ 1) & 1));
        }
        PTS(15);
      }
    } else {
      const int r4 = lane >> 3, c8 = lane & 7;
      const uint32_t eb = (lane << 24) + bars + B_EMPTY;
      auto tagged = [](float v, uint32_t tag) { return ((__float_as_uint(v) + 128) & ~255u) | tag; };
      auto gather = [&](uint32_t tag) {
        const int q = (wid - 9) * 24 + lane;
        const uint4* cp = lane < 24 ? &G.csp[cg * 8 * 48 + q] : &G.st1[rb * 8 * 48 + (wid - 9) * 8 + lane - 24];
        uint4 v[8];
        delay(clk(), GDELAY);
#pragma unroll 1
        for (int it = 0;; it++) {
#pragma unroll
          for (int i = 0; i < 8; i++) v[i] = ld_rlx4(cp + i * 48);
          uint32_t x = 0;
#pragma unroll
          for (int i = 0; i < 8; i++) { v[i].x ^= tag; v[i].y ^= tag; v[i].z ^= tag; v[i].w ^= tag; x |= v[i].x | v[i].y | v[i].z | v[i].w; }
          if (!__any_sync(~0u, (x & 255) != 0)) break;
          SPINCHK(it, 3);
        }
        float c[4] = {0.f, 0.f, 0.f, 0.f};
#pragma unroll
        for (int i = 0; i < 8; i++) { c[0] += __uint_as_float(v[i].x); c[1] += __uint_as_float(v[i].y); c[2] += __uint_as_float(v[i].z); c[3] += __uint_as_float(v[i].w); }
        const uint32_t h0 = pack2(c[0], c[1]), h1 = pack2(c[2], c[3]), ca = sm + OFF_COLSUM + (q >> 1) * 32 + (q & 1) * 8;
        if (lane < 24) {
          sts2f(ca, __uint_as_float(h0), __uint_as_float(h1));
          sts2f(ca + 16, __uint_as_float(pack2(c[0] - bf_lo(h0), c[1] - bf_hi(h0))), __uint_as_float(pack2(c[2] - bf_lo(h1), c[3] - bf_hi(h1))));
        }
        fence_async_smem();
        mbar_arrive(mb + B_AUX);
      };
      const int r2 = lane >> 4, c16 = lane & 15;
      float a[12];
#pragma unroll
      for (int i = 0; i < 12; i++) a[i] = 0.f;
      auto kb_of = [](int it) { return (int)(KORD >> (4 * it)) & 15; };
      if (wid == 9) {
        const uint32_t a0 = sm + rb * 1024 + r2 * 128 + (((c16 >> 1) ^ r2) << 4) + (c16 & 1) * 8;
        const uint2* gw = (const uint2*)(P.wqkv + (kl + rb * 8 + r2) * 3072 + cg * 64) + c16;
#pragma unroll 1
        for (int it = 0; it < 16; it++) {
          uint2 w[12];
          const int kb = kb_of(it);
          if (kb >= 12) {
#pragma unroll
            for (int j = 0; j < 12; j++) w[j] = ld_rlx2(gw + (j >> 2) * 256 + (j & 3) * 1536);
            gw += 64 * 768;
          } else {
            const uint32_t so = a0 + woff(kb & 3);
            mbar_wait(mb + B_FULL + 8 * (kb & 3), (kb >> 2) & 1);
            static_for<0, 12>([&](auto ic) { constexpr int i = decltype(ic)::value;
              const float2 v = lds2f_o<(i >> 2) * WSTR + (i & 3) * 256>(so ^ ((i & 3) << 5)); w[i] = make_uint2(__float_as_uint(v.x), __float_as_uint(v.y)); });
            uint32_t done = 0;
#pragma unroll
            for (int i = 0; i < 12; i++) done |= w[i].y;
            if (lane < 2) mbar_arrive_rem(eb + 8 * (kb & 3) + (done & zero));
          }
#pragma unroll
          for (int i = 0; i < 12; i++) { float* q = a + (i >> 2) * 4; q[0] += bf_lo(w[i].x); q[1] += bf_hi(w[i].x); q[2] += bf_lo(w[i].y); q[3] += bf_hi(w[i].y); }
        }
        if (lane == 0) PTS(8);
        float c[6];
#pragma unroll
        for (int i = 0; i < 6; i++) {
          const int o = (i >> 1) * 4 + (i & 1);
          c[i] = (r2 ? a[o + 2] : a[o]) + __shfl_xor_sync(~0u, r2 ? a[o] : a[o + 2], 16);
        }
        bar_sync(5, 96);
        if (lane == 0) PTS(5);
        const uint32_t tag = lds1(mb + B_SW + 4) & 255;
#pragma unroll
        for (int sg = 0; sg < 3; sg++) st_rlx2((uint2*)&G.csp[(cg * 8 + rb) * 48] + sg * 32 + c16 * 2 + r2, tagged(c[sg * 2], tag), tagged(c[sg * 2 + 1], tag));
      } else {
       if (wid == 10) {
        if (lane < 24 && (lane & 28) != 4) sts4(sm + OFF_STATS + (lane < 16 ? lane * 128 + c8 * 16 : c8 * 16), 0x3F803F80u, 0x3F803F80u, 0x3F803F80u, 0x3F803F80u);
       } else {
        mbar_wait(mb + B_FULL + 8 * PFST, 0);
        const uint32_t ep = ld_rlx(&G.epoch);
        uint4 v[4];
#pragma unroll
        for (int i = 0; i < 4; i++) v[i] = ld_cg4((const uint4*)P.wr + lane + i * 32);
        if (elect_one()) { tmap_prefetch(&tmO); tmap_prefetch(&tmG); tmap_prefetch(&tmU); tmap_prefetch(&tmD); tmap_prefetch(&tmPD); tmap_prefetch(&tmM); }
        __syncwarp();
        const uint4 sv = make_uint4(SENT, SENT, SENT, SENT);
#pragma unroll 1
        for (int i = 0; i < 9; i++) {
          uint4* q = i < 8 ? &G.obuf[((rb * 4 + (i >> 1)) * 64 + cg * 4) * 128 + (i & 1) * 256 + lane] : &G.kvp[cg * 2304 + rb * 288 + lane];
#pragma unroll
          for (int j = 0; j < 8; j++) q[j * 32] = sv;
          if (i == 8) q[256] = sv;
          else if (lane < ((i & 1) ? 24 : 16)) l2_prefetch((i & 1) ? P.wqkv + (kl + (i >> 1) * 64 + rb * 8 + c8) * 3072 + r4 * 1024 + cg * 64 : P.x + (b * 16 + lane) * D_ + kl + i * 32);
        }
        float s = 0.f;
#pragma unroll 1
        for (int i = 0; i < 4; i++) {
          s += (bf_lo(v[0].x) + bf_hi(v[0].x)) + (bf_lo(v[0].y) + bf_hi(v[0].y)) + (bf_lo(v[0].z) + bf_hi(v[0].z)) + (bf_lo(v[0].w) + bf_hi(v[0].w));
          v[0] = v[1]; v[1] = v[2]; v[2] = v[3];
        }
#pragma unroll
        for (int o = 16; o; o >>= 1) s += __shfl_xor_sync(~0u, s, o);
        if (lane == 0) sts2f(mb + B_SW, s, __uint_as_float(ep + 1));
       }
        const uint32_t xa = sm + (c3 * 16 + r4) * 128 + ((c8 ^ r4) << 4);
        const uint4* gx = (const uint4*)(P.x + (b * 16 + r4) * D_ + kl) + c8;
        uint32_t e[4] = {0, 0, 0, 0};
        uint4 wq;
#pragma unroll 1
        for (int kb = wid == 10 ? 0 : 12; kb < (wid == 10 ? 12 : 16); kb++) {
          uint4 v[4];
          if (!(kb & 3)) wq = ld_cg4((const uint4*)(P.wr + k_of(kb + r4)) + c8);
          if (kb >= 12) {
#pragma unroll
            for (int j = 0; j < 4; j++) v[j] = ld_cg4(gx + j * 512);
            gx += 8;
          } else {
            const uint32_t so = xa + xoff(kb & 3, hf);
            mbar_wait(mb + B_FULL + 8 * (kb & 3), (kb >> 2) & 1);
            v[0] = lds4_o<0>(so); v[1] = lds4_o<512>(so ^ 64); v[2] = lds4_o<1024>(so); v[3] = lds4_o<1536>(so ^ 64);
            if (lane < 2) mbar_arrive_rem(eb + 8 * (kb & 3) + ((v[0].x | v[1].x | v[2].x | v[3].x) & zero));
          }
#pragma unroll
          for (int j = 0; j < 16; j++) {
            const uint32_t u = (j & 3) == 0 ? v[j >> 2].x : (j & 3) == 1 ? v[j >> 2].y : (j & 3) == 2 ? v[j >> 2].z : v[j >> 2].w;
            const float d0 = bf_lo(u), d1 = bf_hi(u);
            a[j >> 2] += d0 + d1; a[4 + (j >> 2)] = fmaf(d0, d0, fmaf(d1, d1, a[4 + (j >> 2)]));
          }
          cut<1>(zero);
          const int sl = (kb & 3) * 8 + c8;
          const uint4 wn = make_uint4(__shfl_sync(~0u, wq.x, sl), __shfl_sync(~0u, wq.y, sl), __shfl_sync(~0u, wq.z, sl), __shfl_sync(~0u, wq.w, sl));
#pragma unroll
          for (int j = 0; j < 4; j++) e[j] = hfma2(v[j].x, wn.x, hfma2(v[j].y, wn.y, hfma2(v[j].z, wn.z, hfma2(v[j].w, wn.w, e[j]))));
        }
        float mean, pd;
#pragma unroll 1
        for (int h = 0; h < 2; h++) {
          float u[4], v[2];
#pragma unroll
          for (int i = 0; i < 4; i++) u[i] = ((lane & 4) ? a[4 + i] : a[i]) + __shfl_xor_sync(~0u, (lane & 4) ? a[i] : a[4 + i], 4);
#pragma unroll
          for (int i = 0; i < 2; i++) v[i] = ((lane & 2) ? u[2 + i] : u[i]) + __shfl_xor_sync(~0u, (lane & 2) ? u[i] : u[2 + i], 2);
          mean = pd;
          pd = ((lane & 1) ? v[1] : v[0]) + __shfl_xor_sync(~0u, (lane & 1) ? v[0] : v[1], 1);
#pragma unroll
          for (int j = 0; j < 4; j++) { a[j] = bf_lo(e[j]); a[4 + j] = bf_hi(e[j]); }
        }
        if (wid == 11) {
          sts2f(sm + OFF_COLSUM + 512 + lane * 8, mean, pd);
          fence_gpu();
          bar_arrive(5, 96); PTS(0);
          if (elect_one()) {
#pragma unroll 1
            for (int p = 0; p < 16; p++) {
              const uint32_t ad = sm + bar3(0) + o3(p);
              mbar_init(ad, 1); mbar_init(ad + 256, 1); mbar_init(ad + 448, 8); mbar_init(ad + 704, p == 0 ? 2 : p == 12 ? 1 : p == 15 ? 7 : 8);
              mbar_expect_tx(ad, 8192); mbar_expect_tx(ad + 256, 8192); mbar_expect_tx(mb + B_FULL3 + 8 * p, SLOT_B);
            }
            asm volatile("fence.mbarrier_init.release.cluster;" ::: "memory");
            fence_async_smem();
            mbar_arrive_rem(bars + B_LATE); mbar_arrive_rem((1u << 24) + bars + B_LATE);
          }
          __syncwarp();
        } else {
          if (lane == 0) PTS(1);
          bar_sync(5, 96);
          const float2 u = lds2f(sm + OFF_COLSUM + 512 + lane * 8), sw = lds2f(mb + B_SW);
          mean = (mean + u.x) * (1.f / D_);
          pd += u.y;
          pd += __shfl_xor_sync(~0u, pd, 4);
          const float var = fmaxf(fmaf(-mean, mean, __shfl_xor_sync(~0u, mean, 4)), 0.f);
          const uint32_t tag = __float_as_uint(sw.y) & 255;
          if (c8 < 4) {
            st_rlx2((uint2*)G.st1 + (b >> 1) * 96 + rank * 16 + r4 + 4 * c8, tagged(-mean, tag), tagged(rsq(var + 1e-5f), tag));
            st_rlx(&G.pred[b * 16 + r4 + 4 * c8], (ordered(fmaf(-mean, sw.x, pd)) & ~255u) | tag);
          }
        }
      }
      if (wid < 11) gather(lds1(mb + B_SW + 4) & 255);
      if (wid == 9) {
        if (lane == 0) PTS(6);
        {
          const uint4 sv = make_uint4(SENT, SENT, SENT, SENT);
          uint4* y = &G.ybuf[b * NFFN * 4 + lane];
#pragma unroll
          for (int i = 0; i < 14; i++) y[i * 32] = sv;
          if (lane < 16) G.st2[b * 16 + lane] = make_uint4(0, 0, 0, 0);
          G.hsel[b * 64 + lane] = sv; G.hsel[b * 64 + 32 + lane] = sv;
          if (b < 8) { G.cand[b * 32 + lane] = SENT; G.cst[b * 32 + lane] = make_uint4(0, 0, 0, 0); }
          fence_gpu();
          __syncwarp();
          if (lane == 0) mbar_arrive(mb + B_LATE);
        }
      } else if (wid == 10) {
        {
          mbar_wait(mb + B_FULL + 24, 1);
#pragma unroll 1
          for (int r = -4; r < (fidx >= 0 ? 16 : 0); r++) {
            l2_prefetch((r < 0 ? (const char*)P.wo + (b + 1) * 16384 : (const char*)P.wd + fidx * 65536) + r * 4096 + lane * 128);
            delay(clk(), PDT);
          }
          PTS(4);
        }
      }
      mbar_wait(mb + B_LATE, 0);
      if (wid == 9) {
        if (elect_one()) {
          wait3(60);
#pragma unroll 1
          for (int p = 0; p < 16; p++) {
            const bool mix = (unsigned)(p - 1) < 8;
            const int c1 = mix ? ((p - 1) >> 1) * 16 : 0, c2 = mix ? (hf ^ 1) * 8 + ((p - 1) & 1) * 4 : chunk_of(p) * 4;
            const uint32_t d = sm + (uint32_t)((WO_SLOTS >> (4 * p)) & 15) * SLOT_B;
            if ((0xFFE2 >> p) & 1) mbar_wait(p == 1 ? mb + B_EMPTY + 8 : sm + bar3(32) + o3(p - 5), p == 1);
            if (EFWO) asm volatile("cp.async.bulk.tensor.4d.shared::cluster.global.mbarrier::complete_tx::bytes.L2::cache_hint [%0], [%1, {0, %3, %4, %5}], [%2], %6;"
                         :: "r"(d), "l"(mix ? &tmM : &tmO), "r"(mb + B_FULL3 + 8 * p), "r"(c1), "r"(c2), "r"(c3 * 2), "l"(l2_stream()) : "memory");
            else asm volatile("cp.async.bulk.tensor.4d.shared::cluster.global.mbarrier::complete_tx::bytes [%0], [%1, {0, %3, %4, %5}], [%2];"
                         :: "r"(d), "l"(mix ? &tmM : &tmO), "r"(mb + B_FULL3 + 8 * p), "r"(c1), "r"(c2), "r"(c3 * 2) : "memory");
            if (p >= 10) PTS(7 + p);
          }
          if (fidx >= 0) {
#pragma unroll
            for (int i = 0; i < 4; i++) {
              if (i == 0 || ((DEV >> (4 * i)) & 15) != ((DEV >> (4 * i - 4)) & 15)) wait3(32 + ((DEV >> (4 * i)) & 15));
              tma_3d(sm + ((D_SLOTS >> (4 * i)) & 15) * SLOT_B, &tmD, 0, fidx * 32, i * 4, mb + B_FFN + 8, EFF);
            }
          }
        }
      } else if (wid == 11) {
        const uint2 w = ld_rlx2((const uint2*)(P.wr + c3 * 128) + lane);
        wait3(36);
        sts1(sm + OFF_LNP + (lane & 1) * 128 + (lane >> 1) * 4, w.x); sts1(sm + OFF_LNP + (lane & 1) * 128 + 64 + (lane >> 1) * 4, w.y);
        if (lane < 16) sts1(sm + OFF_LNP + 256 + lane * 4, 0x3F803F80u);
        const uint32_t tag = lds1(mb + B_SW + 4) & 255;
        uint4 k;
        for (int it = 0;; it++) {
          k = ld_rlx4((const uint4*)&G.pred[rb * 256 + hf * 64 + r2 * 128] + c16);
          k.x ^= tag; k.y ^= tag; k.z ^= tag; k.w ^= tag;
          if (!__any_sync(~0u, (k.x | k.y | k.z | k.w) & 255)) break;
          SPINCHK(it, 13);
        }
        const uint2 ahead = top2(k.x | (lane * 4), k.y | (lane * 4 + 1), k.z | (lane * 4 + 2), k.w | (lane * 4 + 3));
        if (lane == 0) sts2f(sm + OFF_MSC + 8, __uint_as_float((ahead.x & 127) ^ NOSPEC), __uint_as_float((ahead.y & 127) ^ NOSPEC));
        __syncwarp();
        if (lane == 0) mbar_arrive(mb + B_FULL3 + 8 * 15);
      } else if (fidx >= 0 && elect_one()) {
        wait3(60);
        mbar_expect_tx(mb + B_FULL, 65536);
#pragma unroll 1
        for (int h = 0; h < 2; h++) {
          const int up = h ^ hf ^ 1;
          mbar_wait(mb + B_EMPTY + 16 - 16 * h, 1);
#pragma unroll
          for (int i = 0; i < 4; i++) {
            const int f = (0x5140 >> (4 * i)) & 15;
            tma_2d(sm + ((GU_SLOTS >> (4 * f)) & 15) * SLOT_B + up * 8192, up ? &tmU : &tmG, fidx * 32, f * 128, mb + B_FULL, EFF);
            if (FDT) delay(clk(), FDT);
          }
          PTS(23 + h);
        }
#pragma unroll 1
        for (int j = 0; j < 8; j++) { mbar_wait(sm + bar3(32) + o3(PD0 + j * PDS / 2), 0); tma_2d(sm + OFF_COLSUM, &tmPD, 0, fidx * 256 + j * 32, mb + B_FFN, false); }
#pragma unroll 1
        for (int i = 0; i < 4; i++) {
          const int f = (0x7362 >> (4 * i)) & 15;
          const uint32_t d = sm + ((GU_SLOTS >> (4 * f)) & 15) * SLOT_B;
          mbar_wait(sm + bar3(32) + o3((GEV >> (4 * i)) & 15), 0);
          tma_2d(d, &tmG, fidx * 32, f * 128, mb + B_FFN, EFF);
          tma_2d(d + 8192, &tmU, fidx * 32, f * 128, mb + B_FFN, EFF);
          PTS(27 + i);
        }
      }
    }
    __syncwarp();
    const float sw = __uint_as_float(lds1(mb + B_SW));
    const int rr = lane >> 4, row00 = rb * 256 + hf * 64;
    uint2 pick;
    if (wid == 8) {
      wait3(61);
      delay(clk(), SDELAY);
      uint4 v;
      int id;
      for (int it = 0;; it++) {
        v = ld_rlx4(&G.cst[jp * 32 + lane]);
        id = __float2int_rn(__uint_as_float(v.w));
        if (!__any_sync(~0u, (id & 15) != 8)) break;
        SPINCHK(it, 14);
      }
      float2 pr;
      const uint32_t k = route(v, sw, id >> 4, pr);
      pick.x = __reduce_max_sync(~0u, k); pick.y = __reduce_max_sync(~0u, k == pick.x ? 0 : k);
      if (k == pick.x || k == pick.y) sts4(sm + OFF_MSC + 16 + (k == pick.y) * 16, k, lane, __float_as_uint(pr.x), __float_as_uint(pr.y));
      __syncwarp();
      if (lane == 0) { mbar_arrive(mb + B_SEL); PTS(16); }
    } else if (wid == 9) {
      wait3(61);
      delay(clk(), LDELAY);
      uint4 v[4];
      for (int it = 0;; it++) {
#pragma unroll
        for (int i = 0; i < 4; i++) v[i] = ld_rlx4(&G.st2[row00 + (i >> 1) * 128 + (i & 1) * 32 + lane]);
        if (!__any_sync(~0u, (v[0].w & v[1].w & v[2].w & v[3].w) != 0x41000000u)) break;
        SPINCHK(it, 6);
      }
      uint32_t k[4];
#pragma unroll
      for (int i = 0; i < 4; i++) {
        float2 pr;
        k[i] = route(v[i], sw, row00 + (i >> 1) * 128 + (i & 1) * 32 + lane, pr);
        const float nm = __uint_as_float(v[i].x) * (-1.f / D_);
        sts2f(sm + OFF_LNP + (i * 32 + lane) * 8, __uint_as_float(pack2(pr.x, pr.x)), __uint_as_float(pack2(nm, nm)));
      }
      const uint2 m = top2(k[0], k[1], k[2], k[3]);
      if (lane == 0) { st_rlx2(&G.cand[c3 * 32 + (rb * 2 + hf) * 2], m.x, m.y); sts2f(sm + OFF_MSC + 0, __uint_as_float(m.x), __uint_as_float(m.y)); }
      wait3(62);
      __syncwarp();
      if (lane == 0) { mbar_arrive(mb + B_OUT); PTS(12); }
      const int ca = 2047 - (((lane & 4) ? m.y : m.x) & 2047), ta = ((ca >> 1) & 64) + (ca & 63);
      uint32_t h0, h1, h2, h3;
      ldsm4_o<0>(sm + HST + ta * 256 + ((((lane & 3) * 4 + (lane >> 3)) ^ (ta & 7)) << 4), h0, h1, h2, h3);
      st_rlx4(&G.hsel[(32 + (rb * 2 + hf) * 2 + rr) * 128 + c3 * 16 + (lane & 15)], make_uint4(h0, h1, h2, h3));
    }
    mbar_wait(mb + B_OUT, 0);
    const float2 cf = lds2f(sm + OFF_MSC + 0);
    const int ca0 = ~__float_as_int(cf.x), ca1 = ~__float_as_int(cf.y), cand0 = ((ca0 >> 1) & 64) + (ca0 & 63), cand1 = ((ca1 >> 1) & 64) + (ca1 & 63);
    auto norm = [](const uint4& v, const float2& pr) {
      const uint32_t r = __float_as_uint(pr.x), m = __float_as_uint(pr.y);
      return make_uint4(hfma2(hadd2(v.x, m), r, v.x), hfma2(hadd2(v.y, m), r, v.y), hfma2(hadd2(v.z, m), r, v.z), hfma2(hadd2(v.w, m), r, v.w));
    };
    uint4* const og = (uint4*)(P.out + row00 * D_ + c3 * 128) + (lane & 15);
    if (wid == 8) {
      delay(clk(), CDELAY);
      uint32_t k;
      for (int it = 0;; it++) { k = ld_rlx(&G.cand[c3 * 32 + lane]); if (!__any_sync(~0u, k == SENT)) break; SPINCHK(it, 12); }
      const uint32_t m1 = __reduce_max_sync(~0u, k), m2 = __reduce_max_sync(~0u, k == m1 ? 0 : k);
      const uint32_t miss = ((m1 ^ pick.x) | (m2 ^ pick.y)) & 2047;
      if (miss && (k == m1 || k == m2)) {
        float2 pr;
        route(ld_rlx4(&G.st2[2047 - (k & 2047)]), sw, 0, pr);
        sts4(sm + OFF_MSC + 48 + (k == m2) * 16, k, 32 + lane, __float_as_uint(pr.x), __float_as_uint(pr.y));
      }
      if (lane == 0) sts1(sm + OFF_MSC + 80, miss);
      __syncwarp();
      if (lane == 0) { mbar_arrive(mb + B_SEL2); PTS(13); }
      const uint32_t kc = __float_as_uint(rr ? cf.y : cf.x);
      const int c = rr ? cand1 : cand0;
      if (kc != m1 && kc != m2) og[(c + (c & 64)) * 128] = norm(lds4(sm + HST + c * 256 + (((lane & 15) ^ (c & 7)) << 4)), lds2f(sm + OFF_LNP + c * 8));
    }
#pragma unroll 1
    for (int t0 = wid == 8 ? 120 : (11 - wid) * 8; t0 < (wid == 8 ? 128 : 120) * !NOOUT; t0 += 24) {
      uint4 v[4];
      float2 pr[4];
      const uint32_t ad = sm + HST + t0 * 256 + lane * 16;
      static_for<0, 4>([&](auto ic) { constexpr int i = decltype(ic)::value; v[i] = lds4_o<i * 512>(ad ^ (rr << 4) ^ (i << 5)); pr[i] = lds2f_o<i * 16>(sm + OFF_LNP + (t0 + rr) * 8); });
#pragma unroll
      for (int i = 0; i < 4; i++) v[i] = norm(v[i], pr[i]);
      if (t0 >= OHOLD) wait3(63);
#pragma unroll
      for (int i = 0; i < 4; i++) {
        const int tr = t0 + rr + 2 * i;
        if (tr != cand0 && tr != cand1) {
          if (OUTEF) asm volatile("st.global.L2::cache_hint.v4.u32 [%0], {%1,%2,%3,%4}, %5;" :: "l"(og + (tr + (tr & 64)) * 128), "r"(v[i].x), "r"(v[i].y), "r"(v[i].z), "r"(v[i].w), "l"(l2_stream()) : "memory");
          else og[(tr + (tr & 64)) * 128] = v[i];
        }
      }
    }
    if (wid == 11 && lane == 0) PTS(31);
  } else {
    asm volatile("setmaxnreg.inc.sync.aligned.u32 224;");
    const int t128 = tid & 127, warp = wid & 3, g = lane >> 2, t = lane & 3;
    const int mb3 = rb * 4 + wg * 2 + hf;
    float acc[64];
    uint4 abuf[3][4];
    uint32_t to;
    int tid2;
    {
      float acc0[96], acc1[96];
#pragma unroll
      for (int i = 0; i < 96; i++) { asm volatile("" : "=f"(acc0[i])); asm volatile("" : "=f"(acc1[i])); }
      const uint32_t xo0 = dlo(sb, 16) + hf * 512, xo1 = dlo(sb, 16) + (hf ^ 1) * 512;
      const uint32_t eb0 = (t128 << 24) + bars + B_EMPTY;
#pragma unroll 1
      for (int kb = 0; kb < 12; kb++) {
        const int s = kb & 3;
        mbar_wait(mb + B_FULL + 8 * s, (kb >> 2) & 1);
        if (LOCK) bar_sync(13, 256);
        if (kb == 0) TS(1);
        const uint32_t xs = xoff(s, wg) >> 4, ws = dlo(sb + woff(s), WSTR);
        pin(acc0); pin(acc1);
        wg_fence();
#pragma unroll
        for (int k = 0; k < 4; k++) {
          const uint64_t db = dsc<1024, 1>(ws + k * 128);
          const int sd = k == 0 ? kb : 1;
          wgmma_n192_ss<0, 1, 0>(acc0, dsc<1024, 1>(xs + xo0 + k * 2), db, sd);
          wgmma_n192_ss<0, 1, 0>(acc1, dsc<1024, 1>(xs + xo1 + k * 2), db, sd);
          if (k == RELK || k == 3) wg_commit();
          if (k == RELK) {
            wg_wait<1>();
            if (kb > 0 && t128 < 2) mbar_arrive_rem(eb0 + 8 * ((kb - 1) & 3));
          }
        }
        pin(acc0); pin(acc1);
      }
      float qa0[32], qa1[32], kv0[64], kv1[64];
#pragma unroll
      for (int i = 0; i < 96; i++) { if (i < 32) { qa0[i] = acc0[i]; qa1[i] = acc1[i]; } else { kv0[i - 32] = acc0[i]; kv1[i - 32] = acc1[i]; } }
      uint2 st[2][2];
      uint4 am;
      auto center = [&](float (&q)[32], float (&kv)[64], const uint2 (&v)[2]) {
        const uint32_t n0 = v[0].x & (t == 0 ? ~255u : 0u), n1 = v[1].x & (t == 0 ? ~255u : 0u);
        am = make_uint4(__byte_perm(n0, 0, 0x3232), __byte_perm(n1, 0, 0x3232),
                        __byte_perm(__float_as_uint(__uint_as_float(n0) - bf_hi(n0)), 0, 0x3232), __byte_perm(__float_as_uint(__uint_as_float(n1) - bf_hi(n1)), 0, 0x3232));
        wg_fence();
        wgmma_n64_rs<1, 0>(q, am.x, am.y, am.z, am.w, dsc<32, 0>(dlo(sb + OFF_COLSUM, 0)), 1);
        wgmma_n128_rs<1, 0>(kv, am.x, am.y, am.z, am.w, dsc<32, 0>(dlo(sb + OFF_COLSUM + 256, 0)), 1);
      };
      auto load_st = [&]() {
        mbar_wait(mb + B_AUX, 0);
#pragma unroll
        for (int i = 0; i < 4; i++) st[i >> 1][i & 1] = ld_rlx2((const uint2*)G.st1 + ((rb * 4 + wg * 2 + ((i >> 1) ^ hf)) * 2 + (warp >> 1)) * 96 + (warp & 1) * 16 + (i & 1) * 8 + g);
      };
      if (!wg) {
        wg_wait<0>();
        if (t128 < 2) mbar_arrive_rem(eb0 + 24);
        load_st();
#pragma unroll 1
        for (int s = 0; s < (B6E < 3 ? 3 : 4); s++) mbar_wait(mb + B_FULL + 8 * s, 1);
        bar_sync(6, 256);
      }
      static_for<0, 4>([&](auto sc) {
        constexpr int s = decltype(sc)::value;
        if (wg || (B6E < 3 && s == 3)) mbar_wait(mb + B_FULL + 8 * s, 1);
        const uint32_t xs = (wg ? xoff(s, 1) : xoff(s, 0)) >> 4, ws = dlo(sb + woff(s) + WSTR, WSTR);
        pin(kv0); pin(kv1); pin(qa0); pin(qa1);
        wg_fence();
#pragma unroll
        for (int k = 0; k < 4; k++) {
          const uint64_t db = dsc<1024, 1>(ws + k * 128);
          wgmma_n128_ss<0, 1, 0>(kv0, dsc<1024, 1>(xs + xo0 + k * 2), db, 1);
          wgmma_n128_ss<0, 1, 0>(kv1, dsc<1024, 1>(xs + xo1 + k * 2), db, 1);
          if (k == 3 || (k == 2 && s == 0)) wg_commit();
          if (k == (s ? 3 : 2) && s < 3) {
            wg_wait<1>();
            if (s == 0) { if (wg && t128 < 2) mbar_arrive_rem(eb0 + 24); }
            else if (!wg) bar_arrive(8 + s, 256);
          }
        }
        if (s == B6E && wg) bar_arrive(6, 256);
        if (s == STLD && wg) load_st();
      });
      if (CUTS & 2) {
        cut<6>(zero);
#pragma unroll
        for (int i = 0; i < 4; i++) asm volatile("" : "+r"(st[i >> 1][i & 1].x), "+r"(st[i >> 1][i & 1].y) :: "memory");
      }
      center(qa0, kv0, st[0]);
      wg_commit();
      if (B6E > 3 && wg) bar_arrive(6, 256);
      float rs[2][2];
#pragma unroll
      for (int i = 0; i < 4; i++) rs[i >> 1][i & 1] = __uint_as_float(st[i >> 1][i & 1].y & ~255u);
      const uint32_t sad = sm + (wg ? 11 : 2) * SLOT_B + (warp * 16 + (lane & 15)) * 128 + (((lane >> 4) ^ (lane & 7)) << 4);
      wg_wait<0>();
      pin(kv0); pin(kv1); pin(qa0); pin(qa1); pin4(am);
      center(qa1, kv1, st[1]);
      wg_commit();
      if (wg) bar_arrive(11, 256);
      if (CUTS & 1) cut<2>(zero);
      TS(2);
      float rl[2];
      uint32_t r2[2];
      auto scales = [&](int m, uint32_t z) {
#pragma unroll
        for (int h = 0; h < 2; h++) { const float r = __uint_as_float(__float_as_uint(rs[m][h]) + z); r2[h] = pack2(r, r); rl[h] = r * 1.4426950408889634f; }
      };
      auto phi8 = [&](const float* a) {
        return make_uint4(phi2(a[0], a[1], r2[0], rl[0]), phi2(a[2], a[3], r2[1], rl[1]), phi2(a[4], a[5], r2[0], rl[0]), phi2(a[6], a[7], r2[1], rl[1]));
      };
      auto stage = [&](float (&a)[64], auto mc) {
        constexpr int m = decltype(mc)::value;
        uint4 r[4];
        scales(m, 0);
#pragma unroll
        for (int j = 0; j < 4; j++) r[j] = phi8(a + j * 8);
        if (m == 0 || wg) bar_sync(wg ? 9 + m : 11, 256 + (r[SBAR].x & zero));
#pragma unroll
        for (int j = 0; j < 4; j++) {
          const int v = 32 + j * 8;
          stsm4_o<WSTR + m * 8192>(sad ^ (j << 5), hmul2(pack2(a[v], a[v + 1]), r2[0]), hmul2(pack2(a[v + 2], a[v + 3]), r2[1]),
                                                   hmul2(pack2(a[v + 4], a[v + 5]), r2[0]), hmul2(pack2(a[v + 6], a[v + 7]), r2[1]));
        }
#pragma unroll
        for (int j = 0; j < 4; j++) stsm4_o<m * 8192>(sad ^ (j << 5), r[j].x, r[j].y, r[j].z, r[j].w);
      };
      stage(kv0, std::integral_constant<int, 0>{});
      wg_wait<0>();
      pin(kv1); pin(qa1); pin4(am);
      stage(kv1, std::integral_constant<int, 1>{});
      fence_async_smem();
      TS(3);
      uint32_t xr[8][4];
      auto load_xr = [&]() {
        const uint32_t xa = sm + hf * 8192 + (warp * 16 + (lane & 15)) * 128 + (((lane >> 4) ^ (lane & 7)) << 4);
#pragma unroll
        for (int q = 0; q < 8; q++) ldsm4_o<0>((xa ^ ((q & 3) << 5)) + xoff(rank * 2 + (q >> 2), wg), xr[q][0], xr[q][1], xr[q][2], xr[q][3]);
      };
      if (!wg) { bar_arrive(4, 256); load_xr(); }
      else {
        float ka[36];
#pragma unroll
        for (int i = 0; i < 36; i++) ka[i] = 0.f;
        auto kv_mma = [&](auto ic) {
          constexpr int i = decltype(ic)::value;
          constexpr uint32_t o = sb + (i < 8 ? 11 : 2) * SLOT_B + (i & 7) * 2048;
          wgmma_n72_ss<1, 1, 0>(ka, dsc<1024, 1>(dlo(o, 8192)), dsc<1024, 1>(dlo(o + WSTR, sb + OFF_STATS - o - WSTR)), i);
        };
        mbar_wait(mb + B_LATE, 0);
        bar_sync(3, 128);
        wg_fence();
        static_for<0, 8>(kv_mma);
        wg_commit();
        uint4* dst = &G.kvp[cg * 2304 + rb * 32];
        if (CUTS & 4) cut<3>(zero);
        load_xr();
        bar_sync(4, 256);
        static_for<8, 16>(kv_mma);
        wg_commit();
        if (QHOLD == 1) bar_arrive(8, 256);
        wg_wait<0>();
        pin(ka);
        if (QHOLD == 2) bar_arrive(8, 256);
        TS(4);
        if (warp < 2) {
          st_rlx4(dst + warp * 512 + lane, make_uint4(pack2(ka[0], ka[1]), pack2(ka[4], ka[5]), pack2(ka[8], ka[9]), pack2(ka[12], ka[13])));
          st_rlx4(dst + warp * 512 + 256 + lane, make_uint4(pack2(ka[2], ka[3]), pack2(ka[6], ka[7]), pack2(ka[10], ka[11]), pack2(ka[14], ka[15])));
        } else {
          st_rlx4(dst + warp * 512 + lane, make_uint4(pack2(ka[16], ka[17]), pack2(ka[20], ka[21]), pack2(ka[24], ka[25]), pack2(ka[28], ka[29])));
          st_rlx4(dst + warp * 512 + 256 + lane, make_uint4(pack2(ka[18], ka[19]), pack2(ka[22], ka[23]), pack2(ka[26], ka[27]), pack2(ka[30], ka[31])));
        }
        st_rlx((uint32_t*)(dst + 2048) + t128, pack2(ka[32], ka[34]));
        if (QHOLD == 3) bar_arrive(8, 256);
        if (t128 == 0) mbar_arrive(sm + bar3(60));
      }
      TS(5);
      uint32_t pq[16], pq0[16];
      auto q_mma = [&](float (&q)[32], uint32_t xo, int next) {
#pragma unroll 1
        for (int s = 0; s < 4; s++) {
          const uint32_t xs = (xoff(s, wg) >> 4) + xo, ws = dlo(sb + woff(s), 8192);
          pin(q);
          wg_fence();
#pragma unroll
          for (int k = 0; k < 4; k++) wgmma_n64_ss<0, 1, 0>(q, dsc<1024, 1>(xs + k * 2), dsc<1024, 1>(ws + k * 128), 1);
          wg_commit();
        }
        if (next) bar_arrive(next, 256);
        wg_wait<0>();
        pin(q);
      };
      auto q_phi = [&](float (&q)[32], int m, uint32_t (&pq)[16], int lo, int hi) {
        scales(m, zero);
#pragma unroll
        for (int j = lo; j < hi; j++) { const uint4 r = phi8(q + j * 8); pq[j * 4] = r.x; pq[j * 4 + 1] = r.y; pq[j * 4 + 2] = r.z; pq[j * 4 + 3] = r.w; }
      };
      auto o_of = [&](uint32_t (&pq)[16], uint4 (&o)[4], uint4* first, bool pub) {
        float oa[2][20];
#pragma unroll
        for (int i = 0; i < 40; i++) oa[i / 20][i % 20] = 0.f;
        wg_fence();
#pragma unroll
        for (int ks = 0; ks < 4; ks++) {
          wgmma_n40_rs<1, 0>(oa[ks >> 1], pq[ks * 4], pq[ks * 4 + 1], pq[ks * 4 + 2], pq[ks * 4 + 3], dsc<1024, 1>(dlo(sb + OFF_KVB + ks * 2048, 8192)), ks & 1);
          if (ks & 1) wg_commit();
        }
#pragma unroll
        for (int h = 0; h < 2; h++) {
          if (h) wg_wait<0>(); else wg_wait<1>();
          pin(oa[h]);
          const float (&d)[20] = oa[h];
          const float i0 = rcp(d[16] + 1e-6f), i1 = rcp(d[18] + 1e-6f);
#pragma unroll
          for (int k2 = 0; k2 < 2; k2++) {
            o[h * 2 + k2] = make_uint4(pack2(d[k2 * 8] * i0, d[k2 * 8 + 1] * i0), pack2(d[k2 * 8 + 2] * i1, d[k2 * 8 + 3] * i1),
                                       pack2(d[k2 * 8 + 4] * i0, d[k2 * 8 + 5] * i0), pack2(d[k2 * 8 + 6] * i1, d[k2 * 8 + 7] * i1));
            if (pub && !h) st_rlx4(first + (h * 2 + k2) * 1024, o[h * 2 + k2]);
          }
        }
#pragma unroll
        for (int i = 0; i < 16; i++) asm volatile("" : "+r"(pq[i]) :: "memory");
      };
      bar_sync(wg ? 7 : 8, 256);
      q_mma(qa1, xo1, wg ? 8 : 7);
      if (tid == 0) mbar_arrive(mb + B_EMPTY + 16);
      cut<5>(zero);
      pin(qa1);
      q_phi(qa1, 1, pq, 0, 4);
      tid2 = __shfl_sync(~0u, tid, lane);
      uint32_t done = 0;
#pragma unroll
      for (int j = 0; j < 8; j++) done |= pq[2 * j] | pq[2 * j + 1] | xr[j][3];
      bar_sync(wg ? 7 : 8, 256 + (done & zero));
      q_mma(qa0, xo0, wg ? 0 : 7);
      if (t128 == 0) mbar_arrive(mb + B_EMPTY + 8 * wg);
      TS(6);
#pragma unroll
      for (int i = 0; i < 16; i++) pq0[i] = 0;
#pragma unroll 1
      for (int r = 0;; r++) {
      if (r == wg) { pin(qa0); q_phi(qa0, 0, pq0, 0, ASYM); }
      if (r) break;
      {
        uint4 a, v[8];
        uint32_t z[8], zs;
        const int blk = warp * 2 + wg;
        mbar_wait(mb + B_KVL, 0);
        static_for<0, 8>([&](auto ic) { constexpr int i = decltype(ic)::value; v[i] = lds4_o<sb + 11 * SLOT_B + i * 512>(own + (blk + (blk & 4)) * 4096 + lane * 16); });
#pragma unroll
        for (int i = 0; i < 8; i++) z[i] = lds1(sm + 2 * SLOT_B + i * 512 + t128 * 4);
#pragma unroll 1
        for (int it = 0;; it++) {
          zs = hadd2(hadd2(hadd2(z[0], z[1]), hadd2(z[2], z[3])), hadd2(hadd2(z[4], z[5]), hadd2(z[6], z[7])));
          a = hadd8(hadd8(hadd8(v[0], v[1]), hadd8(v[2], v[3])), hadd8(hadd8(v[4], v[5]), hadd8(v[6], v[7])));
          TSV(20, it + 1);
          if (!__any_sync(~0u, hnan(hadd2(hadd2(hadd2(a.x, a.y), hadd2(a.z, a.w)), zs)))) break;
          uint32_t mm = 0;
#pragma unroll
          for (int i = 0; i < 8; i++) mm = max4(max(mm, z[i]), v[i]);
          if (!__any_sync(~0u, mm == SENT)) break;
#pragma unroll
          for (int i = 0; i < 8; i++) { v[i] = ld_rlx4(&G.kvp[cg * 2304 + blk * 256 + i * 32 + lane]); z[i] = ld_rlx((const uint32_t*)&G.kvp[cg * 2304 + 2048 + i * 32] + t128); }
          SPINCHK(it, 4);
        }
        TS(23);
        const uint32_t kb0 = sm + OFF_KVB + blk * 1024 + (lane & 7) * 128;
        stsm4(kb0 + (((lane >> 3) ^ (lane & 7)) << 4), a.x, a.y, a.z, a.w);
        asm volatile("stmatrix.sync.aligned.m8n8.x1.shared.b16 [%0], {%1};" :: "r"(kb0 + ((4 ^ (lane & 7)) << 4)), "r"(zs >> (16 * wg)) : "memory");
        fence_async_smem();
        bar_sync(12, 256);
      }
      TS(7);
      if (t128 == 0) mbar_arrive_rem((wg << 24) + sb + bar3(48));
      to = clk();
      o_of(pq, abuf[1], &G.obuf[((mb3 ^ 1) * 64 + hf * 32 + c3) * 128 + (tid2 & 127)], true);
      TS(29);
      }
      pin(qa0);
      q_phi(qa0, 0, pq0, ASYM, 4);
      o_of(pq0, abuf[0], nullptr, false);
#pragma unroll
      for (int q = 0; q < 32; q++) { asm volatile("" : "+r"(xr[q >> 2][q & 3])); acc[q * 2] = bf_lo(xr[q >> 2][q & 3]); acc[q * 2 + 1] = bf_hi(xr[q >> 2][q & 3]); }
      pin(acc);
    }
    {
    const int t128 = tid2 & 127, lane = tid2 & 31, g = lane >> 2, t = lane & 3;
    TS(8);
    uint32_t wa[32][4];
    auto load_gu = [&](int f, int lo = 0, int hi = 8) {
      const uint32_t ad = own + ((lane >> 3) & 1) * 8192 + ((lane >> 4) * 8 + (lane & 7)) * 64 + ((warp ^ ((lane >> 1) & 3)) << 4) + ((GU_SLOTS >> (16 * wg + 4 * f)) & 15) * SLOT_B;
      static_for<0, 8>([&](auto ic) { constexpr int i = decltype(ic)::value; if (i >= lo && i < hi) ldsm4t_o<sb + i * 1024>(ad, wa[f * 8 + i]); });
    };
    {
      const uint32_t la = own + wg * 8192 + t128 * 16, fa = sm + wg * 256;
      int pv = tid2 & zero;
      auto step = [&](const int p, auto jc) {
        constexpr int j = decltype(jc)::value;
        uint4 (&a)[4] = abuf[j == 3 ? 0 : (j + 1) % 3];
        uint4 (&n)[4] = abuf[j == 3 ? 1 : (j + 2) % 3];
        auto fetch = [&]() {
          const uint32_t ra = la + ((p + 1) & 3) * SLOT_B;
          mbar_wait(fa + bar3(0) + o3(p + 1), 0);
          n[0] = lds4_o<sb + 10 * SLOT_B>(ra); n[1] = lds4_o<sb + 10 * SLOT_B + 2048>(ra); n[2] = lds4_o<sb + 10 * SLOT_B + 4096>(ra); n[3] = lds4_o<sb + 10 * SLOT_B + 6144>(ra);
        };
        const bool early = j == 0 ? p > 1 : j == 1 ? true : j == 2 ? p < 15 : false;
        const uint32_t bs = dlo(sb, 8192) + (uint32_t)((WO_SLOTS >> (4 * p)) & 15) * (SLOT_B >> 4);
        if (early) fetch();
        if (p == 1) TS(28);
        if (p == 2) TS(9);
        pin(acc);
        wg_fence();
#pragma unroll
        for (int k = 0; k < 4; k++) {
          wgmma_n128_rs<1, 0>(acc, a[k].x, a[k].y, a[k].z, a[k].w, dsc<1024, 1>(bs + k * 128), 1);
          if (k == 0) { if (j != 2 || p < 15) mbar_wait(mb + B_FULL3 + 8 * p + 8, 0); wg_fence(); }
        }
        wg_commit();
        if (j == 3) {
#pragma unroll
          for (int i = 0; i < 4; i++) { abuf[2][i] = make_uint4(zero, zero, zero, zero); pin4(abuf[2][i]); }
          if (GUP == 0) { if (fidx >= 0) mbar_wait(mb + B_FULL, 0); load_gu(0); }
          if (GUP < 2) load_gu(1);
          delay(to, BDELAY);
#pragma unroll
          for (int k = 2; k < 4; k++) st_rlx4(&G.obuf[((mb3 ^ 1) * 64 + hf * 32 + c3) * 128 + t128 + k * 1024], n[k]);
          TS(24);
          fetch();
          TS(27);
        } else if (j == 0 && p == 1) fetch();
        pv++;
        if (__any_sync(~0u, max(max4(max4(0, n[0]), n[1]), max4(max4(0, n[2]), n[3])) == SENT)) {
          const uint4* q = &G.obuf[(mb3 * 64 + chunk_of(pv) * 4) * 128 + t128];
#pragma unroll 1
          for (int it = 0;; it++) {
#pragma unroll
            for (int i = 0; i < 4; i++) n[i] = ld_rlx4(q + i * 128);
            TSV(21, _ts | 1 << pv);
            if (!__any_sync(~0u, max(max4(max4(0, n[0]), n[1]), max4(max4(0, n[2]), n[3])) == SENT)) break;
            SPINCHK(it, 5);
          }
        }
        if (lane == 0 && p < 11) mbar_arrive_rem((wg << 24) + sb + bar3(48) + o3(p + 1));
        wg_wait<1>();
        pin(acc);
        if (j < 3) {
#pragma unroll
          for (int i = 0; i < 4; i++) pin4(abuf[j][i]);
        }
        if (j == 3 || (j == 0 && p == 1)) {
#pragma unroll
          for (int k = 0; k < 4; k++) if ((k < W0N) == (j == 3)) st_rlx4(&G.obuf[(mb3 * 64 + cg * 4 + k) * 128 + t128], abuf[0][k]);
        }
        if (lane == 0) mbar_arrive(sm + bar3(32) + o3(p));
      };
      if (GUP > 0) { if (fidx >= 0) mbar_wait(mb + B_FULL, 0); load_gu(0); }
      if (GUP == 2) load_gu(1);
      mbar_wait(mb + B_FULL3, 0);
      step(0, std::integral_constant<int, 3>{});
#pragma unroll 1
      for (int pp = 1; pp < 16; pp += 3) static_for<0, 3>([&](auto jc) { step(pp + decltype(jc)::value, jc); });
    }
    uint4 wb[4];
#pragma unroll
    for (int i = 0; i < 4; i++) wb[i] = lds4(sm + OFF_LNP + ((g & 1) ? t * 64 : 256) + i * 16);
    const float2 ah = lds2f(sm + OFF_MSC + 8);
    wg_wait<0>();
    pin(acc);
#pragma unroll
    for (int i = 0; i < 4; i++) pin4(abuf[0][i]);
    TS(10);
    const uint32_t msc = sm + OFF_MSC;
    uint32_t hp[8][4];
    {
      float se[2][4], q[4] = {0.f, 0.f, 0.f, 0.f};
#pragma unroll
      for (int i = 0; i < 8; i++) se[i >> 2][i & 3] = 0.f;
#pragma unroll
      for (int j = 0; j < 8; j++) {
#pragma unroll
        for (int i = 0; i < 4; i++) { const float a = acc[j * 8 + i * 2], c = acc[j * 8 + i * 2 + 1]; hp[j][i] = pack2(a, c); q[i] = fmaf(a, a, fmaf(c, c, q[i])); }
        mma16816(se[j & 1], hp[j], (j & 1) ? wb[j >> 1].z : wb[j >> 1].x, (j & 1) ? wb[j >> 1].w : wb[j >> 1].y);
      }
      const bool od = t & 1;
      const float q0 = q[0] + q[2], q1 = q[1] + q[3];
      float qq = (od ? q1 : q0) + __shfl_xor_sync(~0u, od ? q0 : q1, 1);
      qq += __shfl_xor_sync(~0u, qq, 2);
      const float ss = od ? se[0][2] + se[1][2] : se[0][0] + se[1][0], ee = od ? se[0][3] + se[1][3] : se[0][1] + se[1][1];
#pragma unroll 1
      for (int c = 0; c < 2; c++) {
        const int tr = __float_as_int(c ? ah.y : ah.x), slot = (rb * 2 + hf) * 2 + c;
        if ((tr >> 4) == wid) {
          const int sl = (tr & 7) * 4 + ((tr >> 3) & 1);
          const float s1 = __shfl_sync(~0u, ss, sl), s2 = __shfl_sync(~0u, qq, sl), s3 = __shfl_sync(~0u, ee, sl);
          red4(lane < 8, &G.cst[lane * 32 + slot], s1, s2, s3, c3 ? 1.f : (float)((mb3 * 64 + (tr & 63)) * 16 + 1));
          if (g == (tr & 7)) {
#pragma unroll
            for (int i = 0; i < 4; i++)
              st_rlx4(&G.hsel[slot * 128 + c3 * 16 + i * 4 + t], (tr & 8) ? make_uint4(hp[2 * i][1], hp[2 * i][3], hp[2 * i + 1][1], hp[2 * i + 1][3])
                                                                          : make_uint4(hp[2 * i][0], hp[2 * i][2], hp[2 * i + 1][0], hp[2 * i + 1][2]));
          }
        }
      }
      red4(t < 2, &G.st2[mb3 * 64 + warp * 16 + (t & 1) * 8 + g], ss, qq, ee, 1.f);
      if (lane == 0) mbar_arrive(sm + bar3(61));
      TS(11);
    }
    uint32_t wd[8][2][4];
    const uint32_t dw = sm + ((D_SLOTS >> (2 * (wid & 6))) & 15) * SLOT_B + (wid & 1) * 8192;
    const uint32_t da = dw + ((lane >> 4) * 8 + (lane & 7)) * 128 + ((((lane >> 3) & 1) ^ (lane & 7)) << 4);
    const uint32_t xl = own + ((D_SLOTS >> (8 * wg + ((lane & 16) >> 2))) & 15) * SLOT_B + (lane & 8) * 1024 + (lane & 7) * 16;
    float ya[8][4];
    int pass = 0;
    if (!GUPOS) { if (fidx >= 0) mbar_wait(mb + B_FFN, 1); load_gu(2); load_gu(3); }
    {
      bar_sync(1, 256);
      const uint32_t ha = sm + HST + wid * 4096 + (lane & 15) * 256 + (((lane >> 4) ^ (lane & 7)) << 4);
      static_for<0, 8>([&](auto jc) { constexpr int j = decltype(jc)::value; stsm4_o<(j >> 2) * 128>(ha ^ ((j & 3) << 5), hp[j][0], hp[j][1], hp[j][2], hp[j][3]); });
      asm volatile("fence.acq_rel.cta;" ::: "memory");
      __syncwarp();
      if (lane == 0) mbar_arrive(sm + bar3(62));
    }
    auto load_d1 = [&]() {
      if (fidx >= 0) mbar_wait(mb + B_FFN + 8, 0);
      static_for<0, 8>([&](auto ic) { constexpr int i = decltype(ic)::value; ldsm4t_o<(i & 1) * 2048>(da ^ ((i >> 1) << 5), wd[i >> 1][i & 1]); });
    };
    if (GUPOS) { if (fidx >= 0) mbar_wait(mb + B_FFN, 1); load_gu(2); load_gu(3); }
    if (!D1POS) load_d1();
#pragma unroll 1
    for (;; pass++) {
      TS(15);
      mbar_wait(mb + B_SEL, 0);
      const uint4 sx = lds4(msc + 16 + pass * 32 + (lane & 16));
      TS(26);
      const uint4* xp = &G.hsel[sx.y * 128 + wid * 16 + (lane & 15)];
      uint4 xv = ld_rlx4(xp);
      if (D1POS && !pass) load_d1();
#pragma unroll 1
      for (int it = 0; __any_sync(~0u, max4(0, xv) == SENT); it++) { xv = ld_rlx4(xp); SPINCHK(it, 7); }
      const float f = __uint_as_float(sx.z), n = __uint_as_float(sx.w);
      sts4(dw + ((lane & 12) * 2 + (lane >> 4) * 4 + t) * 16, pack2(fmaf(bf_lo(xv.x), f, n), fmaf(bf_hi(xv.x), f, n)), pack2(fmaf(bf_lo(xv.y), f, n), fmaf(bf_hi(xv.y), f, n)),
           pack2(fmaf(bf_lo(xv.z), f, n), fmaf(bf_hi(xv.z), f, n)), pack2(fmaf(bf_lo(xv.w), f, n), fmaf(bf_hi(xv.w), f, n)));
      if (wid == rb && (g & 3) == (cg >> 2)) sts4(msc + 96 + (lane >> 4) * 16 + t * 32, xv.x, xv.y, xv.z, xv.w);
      bar_sync(2 + wg, 128);
      TS(14);
      float gu[4][4];
#pragma unroll
      for (int i = 0; i < 16; i++) gu[i >> 2][i & 3] = 0.f;
      uint4 xb[4];
      static_for<0, 4>([&](auto ic) { constexpr int i = decltype(ic)::value; xb[i] = lds4_o<sb + i * 128>(xl); });
#pragma unroll
      for (int i = 0; i < 16; i++) {
        const int ks = i & 7;
        if (i == 14) {
#pragma unroll
          for (int j = 0; j < 8; j++) xb[3].x |= wd[4 + (j >> 1)][j & 1][3] & zero;
        }
#pragma unroll
        for (int j = i < 8 ? 2 : 0; j < (i < 8 ? 4 : 2); j++) mma16816(gu[j], wa[j * 8 + ks], (ks & 1) ? xb[ks >> 1].z : xb[ks >> 1].x, (ks & 1) ? xb[ks >> 1].w : xb[ks >> 1].y);
        if (i == 5) {
          const uint32_t dd = da | ((__float_as_uint(gu[2][0]) | __float_as_uint(gu[3][0])) & zero);
          static_for<0, 8>([&](auto jc) { constexpr int j = decltype(jc)::value; ldsm4t_o<4096 + (j & 1) * 2048>(dd ^ ((j >> 1) << 5), wd[4 + (j >> 1)][j & 1]); });
        }
      }
      {
        float o[4];
#pragma unroll
        for (int j = 0; j < 4; j++) o[j] = t == 0 ? gu[0][j] : t == 1 ? gu[1][j] : t == 2 ? gu[2][j] : gu[3][j];
        const float e0 = ((t & 2) ? o[2] : o[0]) + __shfl_xor_sync(~0u, (t & 2) ? o[0] : o[2], 2), e1 = ((t & 2) ? o[3] : o[1]) + __shfl_xor_sync(~0u, (t & 2) ? o[1] : o[3], 2);
        sts1(sm + (wg ? DS1 : DS0) * SLOT_B + 1024 + t128 * 4, __float_as_uint(((t & 1) ? e1 : e0) + __shfl_xor_sync(~0u, (t & 1) ? e0 : e1, 1)));
      }
      TS(25);
      bar_sync(1, 256);
      const uint4 p0 = lds4_o<sb + DS0 * SLOT_B + 1024>(own + lane * 16), p1 = lds4_o<sb + DS1 * SLOT_B + 1024>(own + lane * 16);
      const float g0 = __uint_as_float(p0.x) + __uint_as_float(p1.x), g1 = __uint_as_float(p0.y) + __uint_as_float(p1.y);
      const float u0 = __uint_as_float(p0.z) + __uint_as_float(p1.z), u1 = __uint_as_float(p0.w) + __uint_as_float(p1.w);
      const uint32_t act = pack2(g0 * rcp(1.f + ex2(-1.4426950408889634f * g0)) * u0, g1 * rcp(1.f + ex2(-1.4426950408889634f * g1)) * u1);
      uint32_t bq[4];
#pragma unroll
      for (int i = 0; i < 4; i++) {
        const uint32_t lo = __shfl_sync(~0u, act, i * 8 + 2 * t), hi = __shfl_sync(~0u, act, i * 8 + 2 * t + 1);
        bq[i] = __byte_perm(lo, hi, (g & 1) ? 0x7632 : 0x5410);
      }
      TS(16);
#pragma unroll
      for (int i = 0; i < 8; i++) { ya[i][0] = 0.f; ya[i][1] = 0.f; ya[i][2] = 0.f; ya[i][3] = 0.f; }
#pragma unroll
      for (int ks = 0; ks < 2; ks++)
#pragma unroll
        for (int i = 0; i < 8; i++) mma16816(ya[i], wd[i][ks], bq[ks * 2], bq[ks * 2 + 1]);
      mbar_wait(mb + B_SEL2, 0);
      if (pass || !lds1(msc + 80)) break;
      load_gu(2); load_gu(3);
      bar_sync(1, 256);
    }
    if (fidx >= 0) {
      uint2* const yp = (uint2*)&G.ybuf[((wid * 16 + t * 2) * NFFN + fidx) * 4] + g;
#pragma unroll
      for (int h = 0; h < 2; h++) {
        float o[4];
#pragma unroll
        for (int j = 0; j < 4; j++) o[j] = t == 0 ? ya[h * 4][j] : t == 1 ? ya[h * 4 + 1][j] : t == 2 ? ya[h * 4 + 2][j] : ya[h * 4 + 3][j];
        st_rlx2(yp + h * (8 * NFFN * 8), __float_as_uint(o[0]), __float_as_uint(o[1]));
        st_rlx2(yp + h * (8 * NFFN * 8) + NFFN * 8, __float_as_uint(o[2]), __float_as_uint(o[3]));
      }
    }
    TS(17);
    const uint32_t ty = clk();
    if (wid < 7) {
      const uint4* const yq = &G.ybuf[b * NFFN * 4 + wid * 64 + lane];
      const uint4 sel = lds4(msc + 16 + pass * 32 + (lane & 1) * 16);
      const uint32_t fh = lds1(msc + 96 + (lane & 1) * 16 + (g & 3) * 32 + (cg & 3) * 4);
      const float r = __uint_as_float(sel.x ^ (~(uint32_t)((int)sel.x >> 31) | 0x80000000u));
      float sg = rcp(1.f + ex2(-1.4426950408889634f * r)), base = fmaf((lane & 2) ? bf_hi(fh) : bf_lo(fh), 1.f + __uint_as_float(sel.z), __uint_as_float(sel.w));
      __nv_bfloat16* op = P.out + (size_t)(2047 - (sel.x & 2047)) * D_ + b * 8 + ((lane >> 1) & 7);
      asm volatile("" : "+f"(sg), "+f"(base), "+l"(op) :: "memory");
      delay(ty, YDELAY);
      uint4 v0, v1;
#pragma unroll 1
      for (int it = 0;; it++) {
        v0 = ld_rlx4(yq); v1 = ld_rlx4(yq + 32);
        TSV(22, it + 1);
        if (!__any_sync(~0u, max(max4(0, v0), max4(0, v1)) == SENT)) break;
        SPINCHK(it, 8);
      }
      if (lane == 0) mbar_arrive(sm + bar3(63));
      TS(18);
      float y0 = __uint_as_float(v0.x) + __uint_as_float(v1.x), y1 = __uint_as_float(v0.y) + __uint_as_float(v1.y);
      float y2 = __uint_as_float(v0.z) + __uint_as_float(v1.z), y3 = __uint_as_float(v0.w) + __uint_as_float(v1.w);
      float z0 = ((lane & 16) ? y2 : y0) + __shfl_xor_sync(~0u, (lane & 16) ? y0 : y2, 16), z1 = ((lane & 16) ? y3 : y1) + __shfl_xor_sync(~0u, (lane & 16) ? y1 : y3, 16);
      z0 = ((lane & 8) ? z1 : z0) + __shfl_xor_sync(~0u, (lane & 8) ? z0 : z1, 8);
      z0 += __shfl_xor_sync(~0u, z0, 4);
      const uint32_t yx = sm + OFF_COLSUM;
      if (!(lane & 4)) sts1(yx + (t * 4 + (lane >> 3)) * 32 + wid * 4, __float_as_uint(z0));
      if (wid) bar_arrive(1, 224);
      else {
        bar_sync(1, 224);
        const uint4 a = lds4(yx + (lane & 15) * 32), c = lds4(yx + (lane & 15) * 32 + 16);
        const float y = ((__uint_as_float(a.x) + __uint_as_float(a.y)) + (__uint_as_float(a.z) + __uint_as_float(a.w))) + ((__uint_as_float(c.x) + __uint_as_float(c.y)) + __uint_as_float(c.z));
        if (lane < 16) *op = __float2bfloat16(fmaf(y, sg, base));
        if (b == 0 && lane == 16) G.epoch = lds1(mb + B_SW + 4);
      }
    }
    }
    TS(19); TSG(31);
    if (warp == 0) TS_DUMP(wg);
  }
}

typedef CUresult (*EncodeFn)(CUtensorMap*, CUtensorMapDataType, cuuint32_t, void*, const cuuint64_t*, const cuuint64_t*, const cuuint32_t*,
                             const cuuint32_t*, CUtensorMapInterleave, CUtensorMapSwizzle, CUtensorMapL2promotion, CUtensorMapFloatOOBfill);
void make_map(EncodeFn enc, CUtensorMap* m, const void* p, uint64_t cols, uint64_t rows, uint64_t d0, uint32_t b0, uint32_t b1, uint32_t b2, CUtensorMapSwizzle sw,
              CUtensorMapL2promotion promo = CU_TENSOR_MAP_L2_PROMOTION_L2_128B) {
  cuuint64_t dims[3] = {d0, rows, cols / d0}, str[2] = {cols * 2, d0 * 2};
  cuuint32_t box[3] = {b0, b1, b2}, es[3] = {1, 1, 1};
  enc(m, CU_TENSOR_MAP_DATA_TYPE_BFLOAT16, b2 ? 3 : 2, const_cast<void*>(p), dims, str, box, es, CU_TENSOR_MAP_INTERLEAVE_NONE, sw,
      promo, CU_TENSOR_MAP_FLOAT_OOB_FILL_NONE);
}

}

extern "C" void kernel_launch(void* const* d_in, const int* in_sizes, int n_in, void* d_out, int out_size) {
  (void)in_sizes; (void)n_in; (void)out_size;
  Ptrs P;
  P.x = (const __nv_bfloat16*)d_in[0]; P.wqkv = (const __nv_bfloat16*)d_in[1]; P.wo = (const __nv_bfloat16*)d_in[2];
  P.wr = (const __nv_bfloat16*)d_in[4]; P.wg = (const __nv_bfloat16*)d_in[5]; P.wu = (const __nv_bfloat16*)d_in[6];
  P.wd = (const __nv_bfloat16*)d_in[7]; P.out = (__nv_bfloat16*)d_out;
  void* fn = nullptr;
  cudaDriverEntryPointQueryResult q;
  cudaGetDriverEntryPoint("cuTensorMapEncodeTiled", &fn, cudaEnableDefault, &q);
  EncodeFn enc = (EncodeFn)fn;
  CUtensorMap tmX, tmW, tmO, tmG, tmU, tmD, tmM, tmPG, tmPU, tmPD;
  make_map(enc, &tmX, P.x, D_, S_, D_, 64, 128, 0, CU_TENSOR_MAP_SWIZZLE_128B);
  make_map(enc, &tmW, P.wqkv, 3 * D_, D_, 3 * D_, 64, 64, 0, CU_TENSOR_MAP_SWIZZLE_128B);
  make_map(enc, &tmG, P.wg, F_, D_, F_, 32, 128, 0, CU_TENSOR_MAP_SWIZZLE_64B);
  make_map(enc, &tmU, P.wu, F_, D_, F_, 32, 128, 0, CU_TENSOR_MAP_SWIZZLE_64B);
  make_map(enc, &tmD, P.wd, D_, F_, 64, 64, 32, 4, CU_TENSOR_MAP_SWIZZLE_128B);
  make_map(enc, &tmPG, P.wg, F_, D_, F_, 8, 32, 0, CU_TENSOR_MAP_SWIZZLE_NONE);
  make_map(enc, &tmPU, P.wu, F_, D_, F_, 8, 32, 0, CU_TENSOR_MAP_SWIZZLE_NONE);
  make_map(enc, &tmPD, P.wd, 128, F_ * 8, 128, 8, 32, 0, CU_TENSOR_MAP_SWIZZLE_NONE, CU_TENSOR_MAP_L2_PROMOTION_L2_256B);
  for (int m = 0; m < 2; m++) {
    cuuint64_t dims[4] = {64, m ? 64u : 16u, m ? 16u : 64u, 16}, str[3] = {2 * D_, (m ? 128u : 32u) * D_, 128};
    cuuint32_t box[4] = {64, 16, 4, 2}, es[4] = {1, 1, 1, 1};
    enc(m ? &tmM : &tmO, CU_TENSOR_MAP_DATA_TYPE_BFLOAT16, 4, const_cast<__nv_bfloat16*>(P.wo), dims, str, box, es, CU_TENSOR_MAP_INTERLEAVE_NONE,
        CU_TENSOR_MAP_SWIZZLE_128B, CU_TENSOR_MAP_L2_PROMOTION_L2_128B, CU_TENSOR_MAP_FLOAT_OOB_FILL_NONE);
  }
  cudaFuncSetAttribute(fused_kernel, cudaFuncAttributeMaxDynamicSharedMemorySize, SMEM_BYTES);
  fused_kernel<<<NCTA, 384, SMEM_BYTES>>>(tmX, tmW, tmO, tmG, tmU, tmD, tmM, tmPG, tmPU, tmPD, P);
}
```

```cpp
#include <cuda_runtime.h>
#include <cuda.h>
#include <cuda_bf16.h>
#include <stdint.h>
#include <type_traits>

namespace {

constexpr int S_ = 2048, D_ = 1024, F_ = 3584;
constexpr int NCTA = 128, NFFN = 112;
constexpr uint32_t SENT = 0xFFFFFFFFu;
constexpr int SPIN_LIMIT = 1 << 20;

#define ADELAY 900
#define NPK 0x233333333333ull
#define KDELAY 700
#define SBAR 2
#define NOOUT 0
#define OHOLD 72
#define OUTEF 0
#define CUTS 2
#define EFO 0
#define EFWO 0
#define TMPF 1
#define INIF 0
#define DEV 0xFFEE
#define FDT 100
#define ASTEP 300
#define BDELAY 1500
#define LATEP 0x20
#define GEV 0xDCCB
#define PDS 2
#define D1POS 1
#define GUPOS 1
#define ASYM 2
#define GUP 2
#define PEEL 1
#define B6E 2
#define D2I 5
#define T1 1
#define T4 1
#define QX 0
#define B6H 2
#define PD0 2
#define PDT 60
#define KORD 0xBA9F87E6D54C3210ull
#define SDELAY 450
#define LDELAY 500
#define NOSPEC 0
#define LOCK 1
#define STLD 2
#define RELK 1
#define PERT 2
#define QHOLD 3
#define CDELAY 0
#define YDELAY 500
#define EFX 0
#define EFW 1
#define EFF 1
#define GDELAY 800
#define PFST 1
#define W0N 2
constexpr uint32_t STAGE_B = 57344;
__host__ __device__ constexpr uint32_t xoff(int s, int w) { return ((0x87CA3651u >> (4 * (s + 4 * w))) & 15) * 16384; }
__host__ __device__ constexpr uint32_t woff(int s) { return (s < 2 ? 9 * 16384 : 0) + (s & 1) * 8192; }
constexpr uint32_t WSTR = 32768;
constexpr uint32_t OFF_BARS = 229376;
constexpr uint32_t OFF_COLSUM = 229632;
constexpr uint32_t OFF_STATS = 230400;
constexpr uint32_t SMEM_BYTES = 232448;
constexpr uint32_t B_FULL = 0, B_EMPTY = 32, B_AUX = 64, B_SEL2 = 72, B_KVL = 80, B_FULL3 = 88, B_SW = 216, B_OUT = 224, B_LATE = 232, B_SEL = B_FULL + 8, B_FFN = 240;
__host__ __device__ constexpr uint32_t o3(int p) { return p * 8 + (p & 8) * 8; }
__host__ __device__ constexpr uint32_t bar3(int i) { return OFF_STATS + 1024 + (i >> 3) * 128 + ((i & 32) ? 0 : 64) + (i & 7) * 8; }
constexpr uint32_t SLOT_B = 16384;
constexpr uint32_t sb = 1024;
constexpr uint32_t bars = sb + OFF_BARS;
constexpr uint64_t WO_SLOTS = 0x8794208794208794ull;
constexpr uint32_t GU_SLOTS = 0x35356161u, D_SLOTS = 0x9420, DS0 = D_SLOTS & 15, DS1 = (D_SLOTS >> 8) & 15;
constexpr uint32_t HST = 7 * SLOT_B;
constexpr uint32_t OFF_LNP = OFF_STATS;
constexpr uint32_t OFF_MSC = OFF_COLSUM + 512;
constexpr uint32_t OFF_KVB = 2 * SLOT_B + 8192;

struct Scratch {
  uint4 st1[64 * 48];
  uint4 csp[16 * 8 * 48];
  uint4 kvp[16 * 2304];
  uint4 obuf[32 * 64 * 128];
  uint4 st2[S_];
  uint32_t pred[S_];
  uint4 cst[8 * 32];
  uint4 hsel[64 * 128];
  uint32_t cand[8 * 32];
  uint4 ybuf[NCTA * NFFN * 4];
  unsigned epoch;
};
__device__ __align__(1024) Scratch G;
#define TS_DECL
#define TS(i)
#define TSG(i)
#define TSV(i, v)
#define TS_DUMP(slot)
#define PTS(i)

__device__ __forceinline__ uint32_t smem_u32(const void* p) { return (uint32_t)__cvta_generic_to_shared(p); }
__device__ __forceinline__ void mbar_init(uint32_t bar, uint32_t cnt) { asm volatile("mbarrier.init.shared::cta.b64 [%0], %1;" :: "r"(bar), "r"(cnt) : "memory"); }
__device__ __forceinline__ void mbar_expect_tx(uint32_t bar, uint32_t bytes) { asm volatile("mbarrier.arrive.expect_tx.shared::cta.b64 _, [%0], %1;" :: "r"(bar), "r"(bytes) : "memory"); }
__device__ __forceinline__ void mbar_arrive(uint32_t bar) { asm volatile("mbarrier.arrive.shared::cta.b64 _, [%0];" :: "r"(bar) : "memory"); }
#define SPINCHK(it, code) if ((it) > SPIN_LIMIT) break
__device__ __forceinline__ void mbar_wait(uint32_t bar, uint32_t parity) {
  asm volatile("{\n.reg .pred p;\n.reg .u32 c;\nmov.u32 c, 0;\n"
               "WL:\nmbarrier.try_wait.parity.shared::cta.b64 p, [%0], %1;\n@p bra WD;\n"
               "add.u32 c, c, 1;\nsetp.lt.u32 p, c, 1048576;\n@p bra WL;\nWD:\n}" :: "r"(bar), "r"(parity) : "memory");
}
__device__ __forceinline__ uint64_t l2_stream() { uint64_t p; asm("createpolicy.fractional.L2::evict_first.b64 %0, 1.0;" : "=l"(p)); return p; }
__device__ __forceinline__ void tma_2d(uint32_t dst, const CUtensorMap* tm, int c0, int c1, uint32_t bar, bool stream) {
  if (stream) asm volatile("cp.async.bulk.tensor.2d.shared::cluster.global.mbarrier::complete_tx::bytes.L2::cache_hint [%0], [%1, {%3, %4}], [%2], %5;"
                           :: "r"(dst), "l"(tm), "r"(bar), "r"(c0), "r"(c1), "l"(l2_stream()) : "memory");
  else asm volatile("cp.async.bulk.tensor.2d.shared::cluster.global.mbarrier::complete_tx::bytes [%0], [%1, {%3, %4}], [%2];"
                    :: "r"(dst), "l"(tm), "r"(bar), "r"(c0), "r"(c1) : "memory");
}
__device__ __forceinline__ void tma_3d(uint32_t dst, const CUtensorMap* tm, int c0, int c1, int c2, uint32_t bar, bool stream) {
  if (stream) asm volatile("cp.async.bulk.tensor.3d.shared::cluster.global.mbarrier::complete_tx::bytes.L2::cache_hint [%0], [%1, {%3, %4, %5}], [%2], %6;"
                           :: "r"(dst), "l"(tm), "r"(bar), "r"(c0), "r"(c1), "r"(c2), "l"(l2_stream()) : "memory");
  else asm volatile("cp.async.bulk.tensor.3d.shared::cluster.global.mbarrier::complete_tx::bytes [%0], [%1, {%3, %4, %5}], [%2];"
                    :: "r"(dst), "l"(tm), "r"(bar), "r"(c0), "r"(c1), "r"(c2) : "memory");
}
__device__ __forceinline__ void tma_2d_mc(uint32_t dst, const CUtensorMap* tm, int c0, int c1, uint32_t bar, bool stream) {
  if (stream) asm volatile("cp.async.bulk.tensor.2d.shared::cluster.global.mbarrier::complete_tx::bytes.multicast::cluster.L2::cache_hint [%0], [%1, {%3, %4}], [%2], %5, %6;"
                           :: "r"(dst), "l"(tm), "r"(bar), "r"(c0), "r"(c1), "h"((uint16_t)3), "l"(l2_stream()) : "memory");
  else asm volatile("cp.async.bulk.tensor.2d.shared::cluster.global.mbarrier::complete_tx::bytes.multicast::cluster [%0], [%1, {%3, %4}], [%2], %5;"
                    :: "r"(dst), "l"(tm), "r"(bar), "r"(c0), "r"(c1), "h"((uint16_t)3) : "memory");
}
__device__ __forceinline__ bool elect_one() {
  uint32_t p;
  asm volatile("{\n.reg .pred q;\nelect.sync _|q, 0xFFFFFFFF;\nselp.u32 %0, 1, 0, q;\n}" : "=r"(p));
  return p;
}
__device__ __forceinline__ void bulk_load_mc(uint32_t dst, const void* src, uint32_t bar, uint16_t mask) {
  if (EFO) asm volatile("cp.async.bulk.shared::cluster.global.mbarrier::complete_tx::bytes.multicast::cluster.L2::cache_hint [%0], [%1], 8192, [%2], %3, %4;"
               :: "r"(dst), "l"(src), "r"(bar), "h"(mask), "l"(l2_stream()) : "memory");
  else asm volatile("cp.async.bulk.shared::cluster.global.mbarrier::complete_tx::bytes.multicast::cluster [%0], [%1], 8192, [%2], %3;"
               :: "r"(dst), "l"(src), "r"(bar), "h"(mask) : "memory");
}
__device__ __forceinline__ void bulk_load(uint32_t dst, const void* src, uint32_t bytes, uint32_t bar) {
  asm volatile("cp.async.bulk.shared::cluster.global.mbarrier::complete_tx::bytes [%0], [%1], %2, [%3];" :: "r"(dst), "l"(src), "r"(bytes), "r"(bar) : "memory");
}
__device__ __forceinline__ void mbar_arrive_rem(uint32_t bar) { asm volatile("mbarrier.arrive.shared::cluster.b64 _, [%0];" :: "r"(bar) : "memory"); }
template <uint32_t O> __device__ __forceinline__ void ldsm4_o(uint32_t addr, uint32_t& a, uint32_t& b, uint32_t& c, uint32_t& d) {
  asm volatile("ldmatrix.sync.aligned.m8n8.x4.shared.b16 {%0,%1,%2,%3}, [%4+%5];" : "=r"(a), "=r"(b), "=r"(c), "=r"(d) : "r"(addr), "n"(O) : "memory");
}
template <uint32_t O> __device__ __forceinline__ void ldsm4t_o(uint32_t addr, uint32_t (&r)[4]) {
  asm volatile("ldmatrix.sync.aligned.m8n8.x4.trans.shared.b16 {%0,%1,%2,%3}, [%4+%5];" : "=r"(r[0]), "=r"(r[1]), "=r"(r[2]), "=r"(r[3]) : "r"(addr), "n"(O) : "memory");
}
__device__ __forceinline__ void mma16816(float (&c)[4], const uint32_t (&a)[4], uint32_t b0, uint32_t b1) {
  asm("mma.sync.aligned.m16n8k16.row.col.f32.bf16.bf16.f32 {%0,%1,%2,%3}, {%4,%5,%6,%7}, {%8,%9}, {%0,%1,%2,%3};"
      : "+f"(c[0]), "+f"(c[1]), "+f"(c[2]), "+f"(c[3]) : "r"(a[0]), "r"(a[1]), "r"(a[2]), "r"(a[3]), "r"(b0), "r"(b1));
}
__device__ __forceinline__ void l2_prefetch(const void* p) { asm volatile("prefetch.global.L2 [%0];" :: "l"(p) : "memory"); }
__device__ __forceinline__ uint32_t clk() { uint32_t t; asm volatile("mov.u32 %0, %%clock;" : "=r"(t) :: "memory"); return t; }
__device__ __forceinline__ void delay(uint32_t t0, uint32_t n) { while (clk() - t0 < n) {} }
template <int ID> __device__ __forceinline__ void cut(uint32_t zero) { asm volatile("{\n.reg .pred p;\nsetp.eq.u32 p, %0, %1;\nCUT:\n@p nanosleep.u32 1;\n@p bra.uni CUT;\n}" :: "r"(zero), "n"(ID) : "memory"); }
__device__ __forceinline__ void tmap_prefetch(const CUtensorMap* tm) { asm volatile("prefetch.tensormap [%0];" :: "l"(tm) : "memory"); }
__device__ __forceinline__ void wg_fence() { asm volatile("wgmma.fence.sync.aligned;" ::: "memory"); }
__device__ __forceinline__ void wg_commit() { asm volatile("wgmma.commit_group.sync.aligned;" ::: "memory"); }
template <int N> __device__ __forceinline__ void wg_wait() { asm volatile("wgmma.wait_group.sync.aligned %0;" :: "n"(N) : "memory"); }
template <int N> __device__ __forceinline__ void pin(float (&d)[N]) {
#pragma unroll
  for (int i = 0; i < N; i++) asm volatile("" : "+f"(d[i]) :: "memory");
}
__device__ __forceinline__ void pin4(uint4& v) { asm volatile("" : "+r"(v.x), "+r"(v.y), "+r"(v.z), "+r"(v.w) :: "memory"); }
template <uint32_t SBO, uint32_t SWZ> __device__ __forceinline__ uint64_t dsc(uint32_t lo) { return ((uint64_t)((SBO >> 4) | (SWZ << 30)) << 32) | lo; }
__host__ __device__ constexpr uint32_t dlo(uint32_t addr, uint32_t lbo) { return (addr >> 4) | ((lbo >> 4) << 16); }
__device__ __forceinline__ void bar_sync(int id, int n) { asm volatile("bar.sync %0, %1;" :: "r"(id), "r"(n) : "memory"); }
__device__ __forceinline__ void bar_arrive(int id, int n) { asm volatile("bar.arrive %0, %1;" :: "r"(id), "r"(n) : "memory"); }
__device__ __forceinline__ void fence_async_smem() { asm volatile("fence.proxy.async.shared::cta;" ::: "memory"); }
__device__ __forceinline__ void fence_gpu() { asm volatile("fence.acq_rel.gpu;" ::: "memory"); }
__device__ __forceinline__ uint4 ld_cg4(const void* p) { uint4 v; asm volatile("ld.global.cg.v4.u32 {%0,%1,%2,%3}, [%4];" : "=r"(v.x), "=r"(v.y), "=r"(v.z), "=r"(v.w) : "l"(p) : "memory"); return v; }
__device__ __forceinline__ uint4 ld_rlx4(const void* p) { uint4 v; asm volatile("ld.relaxed.gpu.global.v4.u32 {%0,%1,%2,%3}, [%4];" : "=r"(v.x), "=r"(v.y), "=r"(v.z), "=r"(v.w) : "l"(p) : "memory"); return v; }
__device__ __forceinline__ uint32_t ld_rlx(const void* p) { uint32_t v; asm volatile("ld.relaxed.gpu.global.u32 %0, [%1];" : "=r"(v) : "l"(p) : "memory"); return v; }
__device__ __forceinline__ void st_rlx4(void* p, uint4 v) { asm volatile("st.relaxed.gpu.global.v4.u32 [%0], {%1,%2,%3,%4};" :: "l"(p), "r"(v.x), "r"(v.y), "r"(v.z), "r"(v.w) : "memory"); }
__device__ __forceinline__ void st_rlx2(void* p, uint32_t a, uint32_t b) { asm volatile("st.relaxed.gpu.global.v2.u32 [%0], {%1,%2};" :: "l"(p), "r"(a), "r"(b) : "memory"); }
__device__ __forceinline__ void st_rlx(void* p, uint32_t a) { asm volatile("st.relaxed.gpu.global.u32 [%0], %1;" :: "l"(p), "r"(a) : "memory"); }
__device__ __forceinline__ void red4(bool on, void* p, float a, float b, float c, float d) {
  asm volatile("{\n.reg .pred q;\nsetp.ne.b32 q, %5, 0;\n@q red.relaxed.gpu.global.add.v4.f32 [%0], {%1,%2,%3,%4};\n}" :: "l"(p), "f"(a), "f"(b), "f"(c), "f"(d), "r"((int)on) : "memory");
}
__device__ __forceinline__ uint32_t pack2(float lo, float hi) { uint32_t r; asm("cvt.rn.bf16x2.f32 %0, %1, %2;" : "=r"(r) : "f"(hi), "f"(lo)); return r; }
__device__ __forceinline__ float bf_lo(uint32_t v) { return __uint_as_float(v << 16); }
__device__ __forceinline__ float bf_hi(uint32_t v) { return __uint_as_float(v & 0xFFFF0000u); }
__device__ __forceinline__ void stsm4(uint32_t addr, uint32_t a, uint32_t b, uint32_t c, uint32_t d) {
  asm volatile("stmatrix.sync.aligned.m8n8.x4.shared.b16 [%0], {%1,%2,%3,%4};" :: "r"(addr), "r"(a), "r"(b), "r"(c), "r"(d) : "memory");
}
template <uint32_t O> __device__ __forceinline__ void stsm4_o(uint32_t addr, uint32_t a, uint32_t b, uint32_t c, uint32_t d) {
  asm volatile("stmatrix.sync.aligned.m8n8.x4.shared.b16 [%0+%5], {%1,%2,%3,%4};" :: "r"(addr), "r"(a), "r"(b), "r"(c), "r"(d), "n"(O) : "memory");
}
__device__ __forceinline__ void sts4(uint32_t addr, uint32_t a, uint32_t b, uint32_t c, uint32_t d) { asm volatile("st.shared.v4.u32 [%0], {%1,%2,%3,%4};" :: "r"(addr), "r"(a), "r"(b), "r"(c), "r"(d) : "memory"); }
__device__ __forceinline__ void sts2f(uint32_t addr, float a, float b) { asm volatile("st.shared.v2.f32 [%0], {%1,%2};" :: "r"(addr), "f"(a), "f"(b) : "memory"); }
__device__ __forceinline__ void sts1(uint32_t addr, uint32_t a) { asm volatile("st.shared.u32 [%0], %1;" :: "r"(addr), "r"(a) : "memory"); }
__device__ __forceinline__ float2 lds2f(uint32_t addr) { float2 v; asm volatile("ld.shared.v2.f32 {%0,%1}, [%2];" : "=f"(v.x), "=f"(v.y) : "r"(addr) : "memory"); return v; }
template <uint32_t O> __device__ __forceinline__ float2 lds2f_o(uint32_t addr) { float2 v; asm volatile("ld.shared.v2.f32 {%0,%1}, [%2+%3];" : "=f"(v.x), "=f"(v.y) : "r"(addr), "n"(O) : "memory"); return v; }
template <int I, int N, class F> __device__ __forceinline__ void static_for(F&& f) { if constexpr (I < N) { f(std::integral_constant<int, I>{}); static_for<I + 1, N>(f); } }
__device__ __forceinline__ uint4 lds4(uint32_t addr) { uint4 v; asm volatile("ld.shared.v4.u32 {%0,%1,%2,%3}, [%4];" : "=r"(v.x), "=r"(v.y), "=r"(v.z), "=r"(v.w) : "r"(addr) : "memory"); return v; }
__device__ __forceinline__ uint32_t lds1(uint32_t addr) { uint32_t v; asm volatile("ld.shared.u32 %0, [%1];" : "=r"(v) : "r"(addr) : "memory"); return v; }
__device__ __forceinline__ float ex2(float x) { float y; asm("ex2.approx.ftz.f32 %0, %1;" : "=f"(y) : "f"(x)); return y; }
__device__ __forceinline__ uint32_t max4(uint32_t m, const uint4& v) { return __vimax3_u32(__vimax3_u32(m, v.x, v.y), v.z, v.w); }
__device__ __forceinline__ float rsq(float x) { float y; asm("rsqrt.approx.ftz.f32 %0, %1;" : "=f"(y) : "f"(x)); return y; }
__device__ __forceinline__ float rcp(float x) { float y; asm("rcp.approx.ftz.f32 %0, %1;" : "=f"(y) : "f"(x)); return y; }
__device__ __forceinline__ uint2 ld_rlx2(const void* p) { uint2 v; asm volatile("ld.relaxed.gpu.global.v2.u32 {%0,%1}, [%2];" : "=r"(v.x), "=r"(v.y) : "l"(p) : "memory"); return v; }
template <uint32_t O> __device__ __forceinline__ uint4 lds4_o(uint32_t addr) { uint4 v; asm volatile("ld.shared.v4.u32 {%0,%1,%2,%3}, [%4+%5];" : "=r"(v.x), "=r"(v.y), "=r"(v.z), "=r"(v.w) : "r"(addr), "n"(O) : "memory"); return v; }
__device__ __forceinline__ uint32_t hadd2(uint32_t a, uint32_t b) { uint32_t r; asm("add.rn.bf16x2 %0, %1, %2;" : "=r"(r) : "r"(a), "r"(b)); return r; }
__device__ __forceinline__ uint4 hadd8(const uint4& a, const uint4& b) { return make_uint4(hadd2(a.x, b.x), hadd2(a.y, b.y), hadd2(a.z, b.z), hadd2(a.w, b.w)); }
__device__ __forceinline__ bool hnan(uint32_t a) { return (a & 0x7FFF0000u) > 0x7F800000u; }
__device__ __forceinline__ uint32_t hfma2(uint32_t a, uint32_t b, uint32_t c) { uint32_t r; asm("fma.rn.bf16x2 %0, %1, %2, %3;" : "=r"(r) : "r"(a), "r"(b), "r"(c)); return r; }
__device__ __forceinline__ uint32_t ordered(float v) { const uint32_t u = __float_as_uint(v); return u ^ ((uint32_t)((int)u >> 31) | 0x80000000u); }
__device__ __forceinline__ uint32_t route(const uint4& v, float sw, int row, float2& pr) {
  const float mean = __uint_as_float(v.x) * (1.f / D_);
  pr.x = rsq(fmaxf(fmaf(-mean, mean, __uint_as_float(v.y) * (1.f / D_)), 0.f) + 1e-5f);
  pr.y = -mean * pr.x;
  return min(ordered(pr.x * fmaf(-mean, sw, __uint_as_float(v.z))) & ~2047u, 0xFFFFF000u) | (2047 - row);
}
__device__ __forceinline__ uint2 top2(uint32_t a, uint32_t b, uint32_t c, uint32_t d) {
  const uint32_t h0 = max(a, b), h1 = max(c, d), h = max(h0, h1), l = __vimax3_u32(min(h0, h1), min(a, b), min(c, d));
  const uint32_t m1 = __reduce_max_sync(~0u, h);
  return make_uint2(m1, __reduce_max_sync(~0u, h == m1 ? l : h));
}
__device__ __forceinline__ uint32_t hmul2(uint32_t a, uint32_t b) { uint32_t r; asm("mul.rn.bf16x2 %0, %1, %2;" : "=r"(r) : "r"(a), "r"(b)); return r; }
__device__ __forceinline__ uint32_t phi2(float u0, float u1, uint32_t r2, float rl) {
  uint32_t p, r;
  asm("cvt.rn.relu.bf16x2.f32 %0, %1, %2;" : "=r"(p) : "f"(u1), "f"(u0));
  asm("fma.rn.bf16x2 %0, %1, %2, %3;" : "=r"(r) : "r"(p), "r"(r2), "r"(pack2(__saturatef(ex2(u0 * rl) + 1e-6f), __saturatef(ex2(u1 * rl) + 1e-6f))));
  return r;
}

template<int TA, int TB, int OFF, int SZ> __device__ __forceinline__ void wgmma_n192_ss(float (&d)[SZ], uint64_t da, uint64_t db, int scale_d) {
  asm volatile("{\n.reg .pred p;\nsetp.ne.b32 p, %98, 0;\n"
    "wgmma.mma_async.sync.aligned.m64n192k16.f32.bf16.bf16 {%0,%1,%2,%3,%4,%5,%6,%7,%8,%9,%10,%11,%12,%13,%14,%15,%16,%17,%18,%19,%20,%21,%22,%23,%24,%25,%26,%27,%28,%29,%30,%31,%32,%33,%34,%35,%36,%37,%38,%39,%40,%41,%42,%43,%44,%45,%46,%47,%48,%49,%50,%51,%52,%53,%54,%55,%56,%57,%58,%59,%60,%61,%62,%63,%64,%65,%66,%67,%68,%69,%70,%71,%72,%73,%74,%75,%76,%77,%78,%79,%80,%81,%82,%83,%84,%85,%86,%87,%88,%89,%90,%91,%92,%93,%94,%95}, %96, %97, p, 1, 1, %99, %100;\n}\n"
    : "+f"(d[OFF+0]), "+f"(d[OFF+1]), "+f"(d[OFF+2]), "+f"(d[OFF+3]), "+f"(d[OFF+4]), "+f"(d[OFF+5]), "+f"(d[OFF+6]), "+f"(d[OFF+7]),
      "+f"(d[OFF+8]), "+f"(d[OFF+9]), "+f"(d[OFF+10]), "+f"(d[OFF+11]), "+f"(d[OFF+12]), "+f"(d[OFF+13]), "+f"(d[OFF+14]), "+f"(d[OFF+15]),
      "+f"(d[OFF+16]), "+f"(d[OFF+17]), "+f"(d[OFF+18]), "+f"(d[OFF+19]), "+f"(d[OFF+20]), "+f"(d[OFF+21]), "+f"(d[OFF+22]), "+f"(d[OFF+23]),
      "+f"(d[OFF+24]), "+f"(d[OFF+25]), "+f"(d[OFF+26]), "+f"(d[OFF+27]), "+f"(d[OFF+28]), "+f"(d[OFF+29]), "+f"(d[OFF+30]), "+f"(d[OFF+31]),
      "+f"(d[OFF+32]), "+f"(d[OFF+33]), "+f"(d[OFF+34]), "+f"(d[OFF+35]), "+f"(d[OFF+36]), "+f"(d[OFF+37]), "+f"(d[OFF+38]), "+f"(d[OFF+39]),
      "+f"(d[OFF+40]), "+f"(d[OFF+41]), "+f"(d[OFF+42]), "+f"(d[OFF+43]), "+f"(d[OFF+44]), "+f"(d[OFF+45]), "+f"(d[OFF+46]), "+f"(d[OFF+47]),
      "+f"(d[OFF+48]), "+f"(d[OFF+49]), "+f"(d[OFF+50]), "+f"(d[OFF+51]), "+f"(d[OFF+52]), "+f"(d[OFF+53]), "+f"(d[OFF+54]), "+f"(d[OFF+55]),
      "+f"(d[OFF+56]), "+f"(d[OFF+57]), "+f"(d[OFF+58]), "+f"(d[OFF+59]), "+f"(d[OFF+60]), "+f"(d[OFF+61]), "+f"(d[OFF+62]), "+f"(d[OFF+63]),
      "+f"(d[OFF+64]), "+f"(d[OFF+65]), "+f"(d[OFF+66]), "+f"(d[OFF+67]), "+f"(d[OFF+68]), "+f"(d[OFF+69]), "+f"(d[OFF+70]), "+f"(d[OFF+71]),
      "+f"(d[OFF+72]), "+f"(d[OFF+73]), "+f"(d[OFF+74]), "+f"(d[OFF+75]), "+f"(d[OFF+76]), "+f"(d[OFF+77]), "+f"(d[OFF+78]), "+f"(d[OFF+79]),
      "+f"(d[OFF+80]), "+f"(d[OFF+81]), "+f"(d[OFF+82]), "+f"(d[OFF+83]), "+f"(d[OFF+84]), "+f"(d[OFF+85]), "+f"(d[OFF+86]), "+f"(d[OFF+87]),
      "+f"(d[OFF+88]), "+f"(d[OFF+89]), "+f"(d[OFF+90]), "+f"(d[OFF+91]), "+f"(d[OFF+92]), "+f"(d[OFF+93]), "+f"(d[OFF+94]), "+f"(d[OFF+95])
    : "l"(da), "l"(db), "r"(scale_d), "n"(TA), "n"(TB));
}
template<int TA, int TB, int OFF, int SZ> __device__ __forceinline__ void wgmma_n128_ss(float (&d)[SZ], uint64_t da, uint64_t db, int scale_d) {
  asm volatile("{\n.reg .pred p;\nsetp.ne.b32 p, %66, 0;\n"
    "wgmma.mma_async.sync.aligned.m64n128k16.f32.bf16.bf16 {%0,%1,%2,%3,%4,%5,%6,%7,%8,%9,%10,%11,%12,%13,%14,%15,%16,%17,%18,%19,%20,%21,%22,%23,%24,%25,%26,%27,%28,%29,%30,%31,%32,%33,%34,%35,%36,%37,%38,%39,%40,%41,%42,%43,%44,%45,%46,%47,%48,%49,%50,%51,%52,%53,%54,%55,%56,%57,%58,%59,%60,%61,%62,%63}, %64, %65, p, 1, 1, %67, %68;\n}\n"
    : "+f"(d[OFF+0]), "+f"(d[OFF+1]), "+f"(d[OFF+2]), "+f"(d[OFF+3]), "+f"(d[OFF+4]), "+f"(d[OFF+5]), "+f"(d[OFF+6]), "+f"(d[OFF+7]),
      "+f"(d[OFF+8]), "+f"(d[OFF+9]), "+f"(d[OFF+10]), "+f"(d[OFF+11]), "+f"(d[OFF+12]), "+f"(d[OFF+13]), "+f"(d[OFF+14]), "+f"(d[OFF+15]),
      "+f"(d[OFF+16]), "+f"(d[OFF+17]), "+f"(d[OFF+18]), "+f"(d[OFF+19]), "+f"(d[OFF+20]), "+f"(d[OFF+21]), "+f"(d[OFF+22]), "+f"(d[OFF+23]),
      "+f"(d[OFF+24]), "+f"(d[OFF+25]), "+f"(d[OFF+26]), "+f"(d[OFF+27]), "+f"(d[OFF+28]), "+f"(d[OFF+29]), "+f"(d[OFF+30]), "+f"(d[OFF+31]),
      "+f"(d[OFF+32]), "+f"(d[OFF+33]), "+f"(d[OFF+34]), "+f"(d[OFF+35]), "+f"(d[OFF+36]), "+f"(d[OFF+37]), "+f"(d[OFF+38]), "+f"(d[OFF+39]),
      "+f"(d[OFF+40]), "+f"(d[OFF+41]), "+f"(d[OFF+42]), "+f"(d[OFF+43]), "+f"(d[OFF+44]), "+f"(d[OFF+45]), "+f"(d[OFF+46]), "+f"(d[OFF+47]),
      "+f"(d[OFF+48]), "+f"(d[OFF+49]), "+f"(d[OFF+50]), "+f"(d[OFF+51]), "+f"(d[OFF+52]), "+f"(d[OFF+53]), "+f"(d[OFF+54]), "+f"(d[OFF+55]),
      "+f"(d[OFF+56]), "+f"(d[OFF+57]), "+f"(d[OFF+58]), "+f"(d[OFF+59]), "+f"(d[OFF+60]), "+f"(d[OFF+61]), "+f"(d[OFF+62]), "+f"(d[OFF+63])
    : "l"(da), "l"(db), "r"(scale_d), "n"(TA), "n"(TB));
}
template<int TA, int TB, int OFF, int SZ> __device__ __forceinline__ void wgmma_n64_ss(float (&d)[SZ], uint64_t da, uint64_t db, int scale_d) {
  asm volatile("{\n.reg .pred p;\nsetp.ne.b32 p, %34, 0;\n"
    "wgmma.mma_async.sync.aligned.m64n64k16.f32.bf16.bf16 {%0,%1,%2,%3,%4,%5,%6,%7,%8,%9,%10,%11,%12,%13,%14,%15,%16,%17,%18,%19,%20,%21,%22,%23,%24,%25,%26,%27,%28,%29,%30,%31}, %32, %33, p, 1, 1, %35, %36;\n}\n"
    : "+f"(d[OFF+0]), "+f"(d[OFF+1]), "+f"(d[OFF+2]), "+f"(d[OFF+3]), "+f"(d[OFF+4]), "+f"(d[OFF+5]), "+f"(d[OFF+6]), "+f"(d[OFF+7]),
      "+f"(d[OFF+8]), "+f"(d[OFF+9]), "+f"(d[OFF+10]), "+f"(d[OFF+11]), "+f"(d[OFF+12]), "+f"(d[OFF+13]), "+f"(d[OFF+14]), "+f"(d[OFF+15]),
      "+f"(d[OFF+16]), "+f"(d[OFF+17]), "+f"(d[OFF+18]), "+f"(d[OFF+19]), "+f"(d[OFF+20]), "+f"(d[OFF+21]), "+f"(d[OFF+22]), "+f"(d[OFF+23]),
      "+f"(d[OFF+24]), "+f"(d[OFF+25]), "+f"(d[OFF+26]), "+f"(d[OFF+27]), "+f"(d[OFF+28]), "+f"(d[OFF+29]), "+f"(d[OFF+30]), "+f"(d[OFF+31])
    : "l"(da), "l"(db), "r"(scale_d), "n"(TA), "n"(TB));
}
template<int TB, int OFF, int SZ> __device__ __forceinline__ void wgmma_n64_rs(float (&d)[SZ], uint32_t a0, uint32_t a1, uint32_t a2, uint32_t a3, uint64_t db, int scale_d) {
  asm volatile("{\n.reg .pred p;\nsetp.ne.b32 p, %37, 0;\n"
    "wgmma.mma_async.sync.aligned.m64n64k16.f32.bf16.bf16 {%0,%1,%2,%3,%4,%5,%6,%7,%8,%9,%10,%11,%12,%13,%14,%15,%16,%17,%18,%19,%20,%21,%22,%23,%24,%25,%26,%27,%28,%29,%30,%31}, {%32,%33,%34,%35}, %36, p, 1, 1, %38;\n}\n"
    : "+f"(d[OFF+0]), "+f"(d[OFF+1]), "+f"(d[OFF+2]), "+f"(d[OFF+3]), "+f"(d[OFF+4]), "+f"(d[OFF+5]), "+f"(d[OFF+6]), "+f"(d[OFF+7]),
      "+f"(d[OFF+8]), "+f"(d[OFF+9]), "+f"(d[OFF+10]), "+f"(d[OFF+11]), "+f"(d[OFF+12]), "+f"(d[OFF+13]), "+f"(d[OFF+14]), "+f"(d[OFF+15]),
      "+f"(d[OFF+16]), "+f"(d[OFF+17]), "+f"(d[OFF+18]), "+f"(d[OFF+19]), "+f"(d[OFF+20]), "+f"(d[OFF+21]), "+f"(d[OFF+22]), "+f"(d[OFF+23]),
      "+f"(d[OFF+24]), "+f"(d[OFF+25]), "+f"(d[OFF+26]), "+f"(d[OFF+27]), "+f"(d[OFF+28]), "+f"(d[OFF+29]), "+f"(d[OFF+30]), "+f"(d[OFF+31])
    : "r"(a0), "r"(a1), "r"(a2), "r"(a3), "l"(db), "r"(scale_d), "n"(TB));
}
template<int TA, int TB, int OFF, int SZ> __device__ __forceinline__ void wgmma_n72_ss(float (&d)[SZ], uint64_t da, uint64_t db, int scale_d) {
  asm volatile("{\n.reg .pred p;\nsetp.ne.b32 p, %38, 0;\n"
    "wgmma.mma_async.sync.aligned.m64n72k16.f32.bf16.bf16 {%0,%1,%2,%3,%4,%5,%6,%7,%8,%9,%10,%11,%12,%13,%14,%15,%16,%17,%18,%19,%20,%21,%22,%23,%24,%25,%26,%27,%28,%29,%30,%31,%32,%33,%34,%35}, %36, %37, p, 1, 1, %39, %40;\n}\n"
    : "+f"(d[OFF+0]), "+f"(d[OFF+1]), "+f"(d[OFF+2]), "+f"(d[OFF+3]), "+f"(d[OFF+4]), "+f"(d[OFF+5]), "+f"(d[OFF+6]), "+f"(d[OFF+7]),
      "+f"(d[OFF+8]), "+f"(d[OFF+9]), "+f"(d[OFF+10]), "+f"(d[OFF+11]), "+f"(d[OFF+12]), "+f"(d[OFF+13]), "+f"(d[OFF+14]), "+f"(d[OFF+15]),
      "+f"(d[OFF+16]), "+f"(d[OFF+17]), "+f"(d[OFF+18]), "+f"(d[OFF+19]), "+f"(d[OFF+20]), "+f"(d[OFF+21]), "+f"(d[OFF+22]), "+f"(d[OFF+23]),
      "+f"(d[OFF+24]), "+f"(d[OFF+25]), "+f"(d[OFF+26]), "+f"(d[OFF+27]), "+f"(d[OFF+28]), "+f"(d[OFF+29]), "+f"(d[OFF+30]), "+f"(d[OFF+31]),
      "+f"(d[OFF+32]), "+f"(d[OFF+33]), "+f"(d[OFF+34]), "+f"(d[OFF+35])
    : "l"(da), "l"(db), "r"(scale_d), "n"(TA), "n"(TB));
}
template<int TB, int OFF, int SZ> __device__ __forceinline__ void wgmma_n40_rs(float (&d)[SZ], uint32_t a0, uint32_t a1, uint32_t a2, uint32_t a3, uint64_t db, int scale_d) {
  asm volatile("{\n.reg .pred p;\nsetp.ne.b32 p, %25, 0;\n"
    "wgmma.mma_async.sync.aligned.m64n40k16.f32.bf16.bf16 {%0,%1,%2,%3,%4,%5,%6,%7,%8,%9,%10,%11,%12,%13,%14,%15,%16,%17,%18,%19}, {%20,%21,%22,%23}, %24, p, 1, 1, %26;\n}\n"
    : "+f"(d[OFF+0]), "+f"(d[OFF+1]), "+f"(d[OFF+2]), "+f"(d[OFF+3]), "+f"(d[OFF+4]), "+f"(d[OFF+5]), "+f"(d[OFF+6]), "+f"(d[OFF+7]),
      "+f"(d[OFF+8]), "+f"(d[OFF+9]), "+f"(d[OFF+10]), "+f"(d[OFF+11]), "+f"(d[OFF+12]), "+f"(d[OFF+13]), "+f"(d[OFF+14]), "+f"(d[OFF+15]),
      "+f"(d[OFF+16]), "+f"(d[OFF+17]), "+f"(d[OFF+18]), "+f"(d[OFF+19])
    : "r"(a0), "r"(a1), "r"(a2), "r"(a3), "l"(db), "r"(scale_d), "n"(TB));
}
template<int TB, int OFF, int SZ> __device__ __forceinline__ void wgmma_n128_rs(float (&d)[SZ], uint32_t a0, uint32_t a1, uint32_t a2, uint32_t a3, uint64_t db, int scale_d) {
  asm volatile("{\n.reg .pred p;\nsetp.ne.b32 p, %69, 0;\n"
    "wgmma.mma_async.sync.aligned.m64n128k16.f32.bf16.bf16 {%0,%1,%2,%3,%4,%5,%6,%7,%8,%9,%10,%11,%12,%13,%14,%15,%16,%17,%18,%19,%20,%21,%22,%23,%24,%25,%26,%27,%28,%29,%30,%31,%32,%33,%34,%35,%36,%37,%38,%39,%40,%41,%42,%43,%44,%45,%46,%47,%48,%49,%50,%51,%52,%53,%54,%55,%56,%57,%58,%59,%60,%61,%62,%63}, {%64,%65,%66,%67}, %68, p, 1, 1, %70;\n}\n"
    : "+f"(d[OFF+0]), "+f"(d[OFF+1]), "+f"(d[OFF+2]), "+f"(d[OFF+3]), "+f"(d[OFF+4]), "+f"(d[OFF+5]), "+f"(d[OFF+6]), "+f"(d[OFF+7]),
      "+f"(d[OFF+8]), "+f"(d[OFF+9]), "+f"(d[OFF+10]), "+f"(d[OFF+11]), "+f"(d[OFF+12]), "+f"(d[OFF+13]), "+f"(d[OFF+14]), "+f"(d[OFF+15]),
      "+f"(d[OFF+16]), "+f"(d[OFF+17]), "+f"(d[OFF+18]), "+f"(d[OFF+19]), "+f"(d[OFF+20]), "+f"(d[OFF+21]), "+f"(d[OFF+22]), "+f"(d[OFF+23]),
      "+f"(d[OFF+24]), "+f"(d[OFF+25]), "+f"(d[OFF+26]), "+f"(d[OFF+27]), "+f"(d[OFF+28]), "+f"(d[OFF+29]), "+f"(d[OFF+30]), "+f"(d[OFF+31]),
      "+f"(d[OFF+32]), "+f"(d[OFF+33]), "+f"(d[OFF+34]), "+f"(d[OFF+35]), "+f"(d[OFF+36]), "+f"(d[OFF+37]), "+f"(d[OFF+38]), "+f"(d[OFF+39]),
      "+f"(d[OFF+40]), "+f"(d[OFF+41]), "+f"(d[OFF+42]), "+f"(d[OFF+43]), "+f"(d[OFF+44]), "+f"(d[OFF+45]), "+f"(d[OFF+46]), "+f"(d[OFF+47]),
      "+f"(d[OFF+48]), "+f"(d[OFF+49]), "+f"(d[OFF+50]), "+f"(d[OFF+51]), "+f"(d[OFF+52]), "+f"(d[OFF+53]), "+f"(d[OFF+54]), "+f"(d[OFF+55]),
      "+f"(d[OFF+56]), "+f"(d[OFF+57]), "+f"(d[OFF+58]), "+f"(d[OFF+59]), "+f"(d[OFF+60]), "+f"(d[OFF+61]), "+f"(d[OFF+62]), "+f"(d[OFF+63])
    : "r"(a0), "r"(a1), "r"(a2), "r"(a3), "l"(db), "r"(scale_d), "n"(TB));
}

struct Ptrs { const __nv_bfloat16 *x, *wqkv, *wo, *wr, *wg, *wu, *wd; __nv_bfloat16* out; };

__global__ void __cluster_dims__(2, 1, 1) __launch_bounds__(384, 1) fused_kernel(const __grid_constant__ CUtensorMap tmX, const __grid_constant__ CUtensorMap tmW,
                                                       const __grid_constant__ CUtensorMap tmO, const __grid_constant__ CUtensorMap tmG,
                                                       const __grid_constant__ CUtensorMap tmU, const __grid_constant__ CUtensorMap tmD,
                                                       const __grid_constant__ CUtensorMap tmM, const __grid_constant__ CUtensorMap tmPG,
                                                       const __grid_constant__ CUtensorMap tmPU, const __grid_constant__ CUtensorMap tmPD,
                                                       const Ptrs P) {
  extern __shared__ __align__(1024) uint8_t smem_raw[];
  if (TMPF && threadIdx.x == 0) { tmap_prefetch(&tmX); tmap_prefetch(&tmW); }
  const int tid = threadIdx.x, wid = __shfl_sync(~0u, tid >> 5, 0), wg = __shfl_sync(~0u, tid >> 7, 0), lane = tid & 31;
  const int pj = blockIdx.x >> 1, pi = pj - 36;
  const int b = (pj < 4 ? 32 + pj * 8 : pj < 36 ? pj - 4 : 33 + pi + ((pi * 37) >> 8)) * 2 + (blockIdx.x & 1);
  const int rb = b >> 4, cg = b & 15, hf = cg >> 3, c3 = cg & 7;
  const int jp = cg >> 1;
  const int fidx = jp == rb ? -1 : b - 2 * rb - (jp > rb ? 2 : 0);
  const uint32_t rank = b & 1, own = rank << 24;
  const uint32_t zero = gridDim.y - 1;
  const uint32_t sm = own + sb, mb = own + bars;
  auto chunk_of = [&](int p) { return (int)((0x1765432FEDCBA980ull >> (4 * p)) & 15) ^ (p == 0 || p == 15 ? cg : p < 9 ? cg & 8 : cg & 14); };
  const int kl = (jp & 3) * 256;
  auto k_of = [&](int kb) { return kb >= 12 ? kl + (kb - 12) * 64 : kb * 64 < kl ? kb * 64 : kb * 64 + 256; };
  auto load_w = [&](int kb) {
#pragma unroll
    for (int i = 0; i < 3; i++) tma_2d(sm + woff(kb & 3) + i * WSTR, &tmW, i * D_ + cg * 64, k_of(kb), mb + B_FULL + 8 * (kb & 3), EFW);
  };
  TS_DECL; TS(0); TSG(30);
  if (wid == 8) {
    if (elect_one()) {
      if (smem_u32(smem_raw) != sm) {
#pragma unroll
        for (int i = 0; i < PERT; i++) sts1(mb, lds1(mb));
        asm volatile("trap;");
      }
#pragma unroll
      for (int s = 0; s < 4; s++) mbar_init(mb + B_FULL + 8 * s, 1);
      asm volatile("fence.mbarrier_init.release.cluster;" ::: "memory");
      if (INIF) fence_async_smem();
    }
  } else if (wid == 9) {
    if (elect_one()) {
#pragma unroll
      for (int i = 4; i < 32; i++)
        if (i != 27) mbar_init(mb + 8 * i, i < 8 ? 8 : i == 8 ? 64 : i == 26 ? 2 : i == 29 ? 4 : 1);
      asm volatile("fence.mbarrier_init.release.cluster;" ::: "memory");
      if (INIF) fence_async_smem();
    }
  }
  __syncwarp();
  asm volatile("barrier.cluster.arrive.relaxed.aligned;" ::: "memory");
  if (wid == 8) {
    if (elect_one()) {
      mbar_expect_tx(mb + B_FULL, STAGE_B);
      tma_2d(sm + xoff(0, 0), &tmX, k_of(0), rb * 256, mb + B_FULL, EFX);
      tma_2d(sm + xoff(0, 1), &tmX, k_of(0), rb * 256 + 128, mb + B_FULL, EFX);
      load_w(0);
    }
    __syncwarp();
  }
  asm volatile("barrier.cluster.wait.aligned;" ::: "memory");

  if (wg == 2) {
    asm volatile("setmaxnreg.dec.sync.aligned.u32 56;");
    auto wait3 = [&](int i) { mbar_wait(sm + bar3(i), 0); };
    if (wid == 8) {
      if (elect_one()) {
        int np = fidx >= 0 ? 0 : 32;
        if (fidx >= 0) mbar_expect_tx(mb + B_FFN, 32 * 512);
#pragma unroll 1
        for (int kb = 1; kb < 16 - PEEL; kb++) {
          const uint32_t fb = mb + B_FULL + 8 * (kb & 3);
          mbar_wait(fb + B_EMPTY, ((kb >> 2) & 1) ^ 1);
          mbar_expect_tx(fb, STAGE_B);
          tma_2d_mc(sm + xoff(kb & 3, rank), &tmX, k_of(kb), rb * 256 + rank * 128, fb, EFX);
          load_w(kb);
          if (kb >= 12) asm volatile("mbarrier.arrive.shared::cta.b64 _, [%0], 7;" :: "r"(fb + B_EMPTY) : "memory");
#pragma unroll 1
          for (int n = ((NPK << 16) >> (4 * kb)) & 15; n > 0 && np < 32; n--, np++)
            tma_2d(sm + OFF_STATS + 512, (np & 1) ? &tmPU : &tmPG, (fidx >> 1) * 64, (np >> 1) * 64 + rank * 32, mb + B_FFN, false);
        }
        if (PEEL) {
          mbar_wait(mb + B_EMPTY + 24, 0);
          tma_2d_mc(sm + xoff(3, rank), &tmX, kl + 192, rb * 256 + rank * 128, mb + B_FULL + 24, EFX);
          load_w(15);
          mbar_expect_tx(mb + B_FULL + 24, STAGE_B);
        }
        if (fidx >= 0) { mbar_wait(mb + B_FFN, 0); mbar_expect_tx(mb + B_FFN, 65536 + 8 * 512); mbar_expect_tx(mb + B_FFN + 8, 65536); }
#pragma unroll
        for (int p = 4; p < 8; p++) sts4(sm + OFF_STATS + p * 144, 0x3F803F80u, 0x3F803F80u, 0x3F803F80u, 0x3F803F80u);
        fence_async_smem();
        mbar_arrive(mb + B_LATE);
        PTS(2);
        mbar_expect_tx(mb + B_KVL, 36864);
        mbar_wait(mb + B_LATE, 0);
        wait3(60);
        delay(clk(), KDELAY);
        bulk_load(sm + 11 * SLOT_B, &G.kvp[cg * 2304], SLOT_B, mb + B_KVL);
        bulk_load(sm + 13 * SLOT_B, &G.kvp[cg * 2304 + 1024], SLOT_B, mb + B_KVL);
        bulk_load(sm + 2 * SLOT_B, &G.kvp[cg * 2304 + 2048], 4096, mb + B_KVL);
        PTS(3);
        const uint4* src = &G.obuf[(rb * 4 + rank * 2 + hf) * 64 * 128];
        wait3(48);
        const uint32_t t1 = clk();
#pragma unroll
        for (int p = 1; p < 5; p++) {
          delay(t1, ADELAY + (p - 1) * ASTEP);
          bulk_load_mc(sm + (10 + (p & 3)) * SLOT_B + rank * 8192, src + ((hf ^ 1) * 8 + p - 1) * 512, sm + bar3(p) + rank * 256, 3);
        }
        PTS(7);
#pragma unroll 1
        for (int i = 5; i < 17; i++) {
          const int p = min(i, 15);
          const uint32_t d = sm + (10 + (p & 3)) * SLOT_B + rank * 8192, fb = sm + bar3(0) + o3(p) + rank * 256;
          const uint4* q = src + chunk_of(i & 15) * 512;
          mbar_wait(sm + bar3(48) + o3(p - 4 + ((LATEP >> p) & 1)), 0);
          bulk_load_mc(d, q, fb, i < 15 ? 3 : 1 << ((i ^ rank ^ 1) & 1));
        }
        PTS(15);
      }
    } else {
      const int r4 = lane >> 3, c8 = lane & 7;
      const uint32_t eb = (lane << 24) + bars + B_EMPTY;
      auto tagged = [](float v, uint32_t tag) { return ((__float_as_uint(v) + 128) & ~255u) | tag; };
      auto gather = [&](uint32_t tag) {
        const int q = (wid - 9) * 24 + lane;
        const uint4* cp = lane < 24 ? &G.csp[cg * 8 * 48 + q] : &G.st1[rb * 8 * 48 + (wid - 9) * 8 + lane - 24];
        uint4 v[8];
        delay(clk(), GDELAY);
#pragma unroll 1
        for (int it = 0;; it++) {
#pragma unroll
          for (int i = 0; i < 8; i++) v[i] = ld_rlx4(cp + i * 48);
          uint32_t x = 0;
#pragma unroll
          for (int i = 0; i < 8; i++) { v[i].x ^= tag; v[i].y ^= tag; v[i].z ^= tag; v[i].w ^= tag; x |= v[i].x | v[i].y | v[i].z | v[i].w; }
          if (!__any_sync(~0u, (x & 255) != 0)) break;
          SPINCHK(it, 3);
        }
        float c[4] = {0.f, 0.f, 0.f, 0.f};
#pragma unroll
        for (int i = 0; i < 8; i++) { c[0] += __uint_as_float(v[i].x); c[1] += __uint_as_float(v[i].y); c[2] += __uint_as_float(v[i].z); c[3] += __uint_as_float(v[i].w); }
        const uint32_t h0 = pack2(c[0], c[1]), h1 = pack2(c[2], c[3]), ca = sm + OFF_COLSUM + (q >> 1) * 32 + (q & 1) * 8;
        if (lane < 24) {
          sts2f(ca, __uint_as_float(h0), __uint_as_float(h1));
          sts2f(ca + 16, __uint_as_float(pack2(c[0] - bf_lo(h0), c[1] - bf_hi(h0))), __uint_as_float(pack2(c[2] - bf_lo(h1), c[3] - bf_hi(h1))));
        }
        fence_async_smem();
        mbar_arrive(mb + B_AUX);
      };
      const int r2 = lane >> 4, c16 = lane & 15;
      float a[12];
#pragma unroll
      for (int i = 0; i < 12; i++) a[i] = 0.f;
      auto kb_of = [](int it) { return (int)(KORD >> (4 * it)) & 15; };
      if (wid == 9) {
        const uint32_t a0 = sm + rb * 1024 + r2 * 128 + (((c16 >> 1) ^ r2) << 4) + (c16 & 1) * 8;
        const uint2* gw = (const uint2*)(P.wqkv + (kl + rb * 8 + r2) * 3072 + cg * 64) + c16;
#pragma unroll 1
        for (int it = 0; it < 16; it++) {
          uint2 w[12];
          const int kb = kb_of(it);
          if (kb >= 12) {
#pragma unroll
            for (int j = 0; j < 12; j++) w[j] = ld_rlx2(gw + (j >> 2) * 256 + (j & 3) * 1536);
            gw += 64 * 768;
          } else {
            const uint32_t so = a0 + woff(kb & 3);
            mbar_wait(mb + B_FULL + 8 * (kb & 3), (kb >> 2) & 1);
            static_for<0, 12>([&](auto ic) { constexpr int i = decltype(ic)::value;
              const float2 v = lds2f_o<(i >> 2) * WSTR + (i & 3) * 256>(so ^ ((i & 3) << 5)); w[i] = make_uint2(__float_as_uint(v.x), __float_as_uint(v.y)); });
            uint32_t done = 0;
#pragma unroll
            for (int i = 0; i < 12; i++) done |= w[i].y;
            if (lane < 2) mbar_arrive_rem(eb + 8 * (kb & 3) + (done & zero));
          }
#pragma unroll
          for (int i = 0; i < 12; i++) { float* q = a + (i >> 2) * 4; q[0] += bf_lo(w[i].x); q[1] += bf_hi(w[i].x); q[2] += bf_lo(w[i].y); q[3] += bf_hi(w[i].y); }
        }
        if (lane == 0) PTS(8);
        float c[6];
#pragma unroll
        for (int i = 0; i < 6; i++) {
          const int o = (i >> 1) * 4 + (i & 1);
          c[i] = (r2 ? a[o + 2] : a[o]) + __shfl_xor_sync(~0u, r2 ? a[o] : a[o + 2], 16);
        }
        bar_sync(5, 96);
        if (lane == 0) PTS(5);
        const uint32_t tag = lds1(mb + B_SW + 4) & 255;
#pragma unroll
        for (int sg = 0; sg < 3; sg++) st_rlx2((uint2*)&G.csp[(cg * 8 + rb) * 48] + sg * 32 + c16 * 2 + r2, tagged(c[sg * 2], tag), tagged(c[sg * 2 + 1], tag));
      } else {
       if (wid == 10) {
        if (lane < 24 && (lane & 28) != 4) sts4(sm + OFF_STATS + (lane < 16 ? lane * 128 + c8 * 16 : c8 * 16), 0x3F803F80u, 0x3F803F80u, 0x3F803F80u, 0x3F803F80u);
       } else {
        mbar_wait(mb + B_FULL + 8 * PFST, 0);
        const uint32_t ep = ld_rlx(&G.epoch);
        uint4 v[4];
#pragma unroll
        for (int i = 0; i < 4; i++) v[i] = ld_cg4((const uint4*)P.wr + lane + i * 32);
        if (elect_one()) { tmap_prefetch(&tmO); tmap_prefetch(&tmG); tmap_prefetch(&tmU); tmap_prefetch(&tmD); tmap_prefetch(&tmPD); tmap_prefetch(&tmM); }
        __syncwarp();
        const uint4 sv = make_uint4(SENT, SENT, SENT, SENT);
#pragma unroll 1
        for (int i = 0; i < 9; i++) {
          uint4* q = i < 8 ? &G.obuf[((rb * 4 + (i >> 1)) * 64 + cg * 4) * 128 + (i & 1) * 256 + lane] : &G.kvp[cg * 2304 + rb * 288 + lane];
#pragma unroll
          for (int j = 0; j < 8; j++) q[j * 32] = sv;
          if (i == 8) q[256] = sv;
          else if (lane < ((i & 1) ? 24 : 16)) l2_prefetch((i & 1) ? P.wqkv + (kl + (i >> 1) * 64 + rb * 8 + c8) * 3072 + r4 * 1024 + cg * 64 : P.x + (b * 16 + lane) * D_ + kl + i * 32);
        }
        float s = 0.f;
#pragma unroll 1
        for (int i = 0; i < 4; i++) {
          s += (bf_lo(v[0].x) + bf_hi(v[0].x)) + (bf_lo(v[0].y) + bf_hi(v[0].y)) + (bf_lo(v[0].z) + bf_hi(v[0].z)) + (bf_lo(v[0].w) + bf_hi(v[0].w));
          v[0] = v[1]; v[1] = v[2]; v[2] = v[3];
        }
#pragma unroll
        for (int o = 16; o; o >>= 1) s += __shfl_xor_sync(~0u, s, o);
        if (lane == 0) sts2f(mb + B_SW, s, __uint_as_float(ep + 1));
       }
        const uint32_t xa = sm + (c3 * 16 + r4) * 128 + ((c8 ^ r4) << 4);
        const uint4* gx = (const uint4*)(P.x + (b * 16 + r4) * D_ + kl) + c8;
        uint32_t e[4] = {0, 0, 0, 0};
        uint4 wq;
#pragma unroll 1
        for (int kb = wid == 10 ? 0 : 12; kb < (wid == 10 ? 12 : 16); kb++) {
          uint4 v[4];
          if (!(kb & 3)) wq = ld_cg4((const uint4*)(P.wr + k_of(kb + r4)) + c8);
          if (kb >= 12) {
#pragma unroll
            for (int j = 0; j < 4; j++) v[j] = ld_cg4(gx + j * 512);
            gx += 8;
          } else {
            const uint32_t so = xa + xoff(kb & 3, hf);
            mbar_wait(mb + B_FULL + 8 * (kb & 3), (kb >> 2) & 1);
            v[0] = lds4_o<0>(so); v[1] = lds4_o<512>(so ^ 64); v[2] = lds4_o<1024>(so); v[3] = lds4_o<1536>(so ^ 64);
            if (lane < 2) mbar_arrive_rem(eb + 8 * (kb & 3) + ((v[0].x | v[1].x | v[2].x | v[3].x) & zero));
          }
#pragma unroll
          for (int j = 0; j < 16; j++) {
            const uint32_t u = (j & 3) == 0 ? v[j >> 2].x : (j & 3) == 1 ? v[j >> 2].y : (j & 3) == 2 ? v[j >> 2].z : v[j >> 2].w;
            const float d0 = bf_lo(u), d1 = bf_hi(u);
            a[j >> 2] += d0 + d1; a[4 + (j >> 2)] = fmaf(d0, d0, fmaf(d1, d1, a[4 + (j >> 2)]));
          }
          cut<1>(zero);
          const int sl = (kb & 3) * 8 + c8;
          const uint4 wn = make_uint4(__shfl_sync(~0u, wq.x, sl), __shfl_sync(~0u, wq.y, sl), __shfl_sync(~0u, wq.z, sl), __shfl_sync(~0u, wq.w, sl));
#pragma unroll
          for (int j = 0; j < 4; j++) e[j] = hfma2(v[j].x, wn.x, hfma2(v[j].y, wn.y, hfma2(v[j].z, wn.z, hfma2(v[j].w, wn.w, e[j]))));
        }
        float mean, pd;
#pragma unroll 1
        for (int h = 0; h < 2; h++) {
          float u[4], v[2];
#pragma unroll
          for (int i = 0; i < 4; i++) u[i] = ((lane & 4) ? a[4 + i] : a[i]) + __shfl_xor_sync(~0u, (lane & 4) ? a[i] : a[4 + i], 4);
#pragma unroll
          for (int i = 0; i < 2; i++) v[i] = ((lane & 2) ? u[2 + i] : u[i]) + __shfl_xor_sync(~0u, (lane & 2) ? u[i] : u[2 + i], 2);
          mean = pd;
          pd = ((lane & 1) ? v[1] : v[0]) + __shfl_xor_sync(~0u, (lane & 1) ? v[0] : v[1], 1);
#pragma unroll
          for (int j = 0; j < 4; j++) { a[j] = bf_lo(e[j]); a[4 + j] = bf_hi(e[j]); }
        }
        if (wid == 11) {
          sts2f(sm + OFF_COLSUM + 512 + lane * 8, mean, pd);
          fence_gpu();
          bar_arrive(5, 96); PTS(0);
          if (elect_one()) {
#pragma unroll 1
            for (int p = 0; p < 16; p++) {
              const uint32_t ad = sm + bar3(0) + o3(p);
              mbar_init(ad, 1); mbar_init(ad + 256, 1); mbar_init(ad + 448, 8); mbar_init(ad + 704, p == 0 ? 2 : p == 12 ? 1 : p == 15 ? 7 : 8);
              mbar_expect_tx(ad, 8192); mbar_expect_tx(ad + 256, 8192); mbar_expect_tx(mb + B_FULL3 + 8 * p, SLOT_B);
            }
            asm volatile("fence.mbarrier_init.release.cluster;" ::: "memory");
            fence_async_smem();
            mbar_arrive_rem(bars + B_LATE); mbar_arrive_rem((1u << 24) + bars + B_LATE);
          }
          __syncwarp();
        } else {
          if (lane == 0) PTS(1);
          bar_sync(5, 96);
          const float2 u = lds2f(sm + OFF_COLSUM + 512 + lane * 8), sw = lds2f(mb + B_SW);
          mean = (mean + u.x) * (1.f / D_);
          pd += u.y;
          pd += __shfl_xor_sync(~0u, pd, 4);
          const float var = fmaxf(fmaf(-mean, mean, __shfl_xor_sync(~0u, mean, 4)), 0.f);
          const uint32_t tag = __float_as_uint(sw.y) & 255;
          if (c8 < 4) {
            st_rlx2((uint2*)G.st1 + (b >> 1) * 96 + rank * 16 + r4 + 4 * c8, tagged(-mean, tag), tagged(rsq(var + 1e-5f), tag));
            st_rlx(&G.pred[b * 16 + r4 + 4 * c8], (ordered(fmaf(-mean, sw.x, pd)) & ~255u) | tag);
          }
        }
      }
      if (wid < 11) gather(lds1(mb + B_SW + 4) & 255);
      if (wid == 9) {
        if (lane == 0) PTS(6);
        {
          const uint4 sv = make_uint4(SENT, SENT, SENT, SENT);
          uint4* y = &G.ybuf[b * NFFN * 4 + lane];
#pragma unroll
          for (int i = 0; i < 14; i++) y[i * 32] = sv;
          if (lane < 16) G.st2[b * 16 + lane] = make_uint4(0, 0, 0, 0);
          G.hsel[b * 64 + lane] = sv; G.hsel[b * 64 + 32 + lane] = sv;
          if (b < 8) { G.cand[b * 32 + lane] = SENT; G.cst[b * 32 + lane] = make_uint4(0, 0, 0, 0); }
          fence_gpu();
          __syncwarp();
          if (lane == 0) mbar_arrive(mb + B_LATE);
        }
      } else if (wid == 10) {
        {
          mbar_wait(mb + B_FULL + 24, 1);
#pragma unroll 1
          for (int r = -4; r < (fidx >= 0 ? 16 : 0); r++) {
            l2_prefetch((r < 0 ? (const char*)P.wo + (b + 1) * 16384 : (const char*)P.wd + fidx * 65536) + r * 4096 + lane * 128);
            delay(clk(), PDT);
          }
          PTS(4);
        }
      }
      mbar_wait(mb + B_LATE, 0);
      if (wid == 9) {
        if (elect_one()) {
          wait3(60);
#pragma unroll 1
          for (int p = 0; p < 16; p++) {
            const bool mix = (unsigned)(p - 1) < 8;
            const int c1 = mix ? ((p - 1) >> 1) * 16 : 0, c2 = mix ? (hf ^ 1) * 8 + ((p - 1) & 1) * 4 : chunk_of(p) * 4;
            const uint32_t d = sm + (uint32_t)((WO_SLOTS >> (4 * p)) & 15) * SLOT_B;
            if ((0xFFE2 >> p) & 1) mbar_wait(p == 1 ? mb + B_EMPTY + 8 : sm + bar3(32) + o3(p - 5), p == 1);
            if (EFWO) asm volatile("cp.async.bulk.tensor.4d.shared::cluster.global.mbarrier::complete_tx::bytes.L2::cache_hint [%0], [%1, {0, %3, %4, %5}], [%2], %6;"
                         :: "r"(d), "l"(mix ? &tmM : &tmO), "r"(mb + B_FULL3 + 8 * p), "r"(c1), "r"(c2), "r"(c3 * 2), "l"(l2_stream()) : "memory");
            else asm volatile("cp.async.bulk.tensor.4d.shared::cluster.global.mbarrier::complete_tx::bytes [%0], [%1, {0, %3, %4, %5}], [%2];"
                         :: "r"(d), "l"(mix ? &tmM : &tmO), "r"(mb + B_FULL3 + 8 * p), "r"(c1), "r"(c2), "r"(c3 * 2) : "memory");
            if (p >= 10) PTS(7 + p);
          }
          if (fidx >= 0) {
#pragma unroll
            for (int i = 0; i < 4; i++) {
              if (i == 0 || ((DEV >> (4 * i)) & 15) != ((DEV >> (4 * i - 4)) & 15)) wait3(32 + ((DEV >> (4 * i)) & 15));
              tma_3d(sm + ((D_SLOTS >> (4 * i)) & 15) * SLOT_B, &tmD, 0, fidx * 32, i * 4, mb + B_FFN + 8, EFF);
            }
          }
        }
      } else if (wid == 11) {
        const uint2 w = ld_rlx2((const uint2*)(P.wr + c3 * 128) + lane);
        wait3(36);
        sts1(sm + OFF_LNP + (lane & 1) * 128 + (lane >> 1) * 4, w.x); sts1(sm + OFF_LNP + (lane & 1) * 128 + 64 + (lane >> 1) * 4, w.y);
        if (lane < 16) sts1(sm + OFF_LNP + 256 + lane * 4, 0x3F803F80u);
        const uint32_t tag = lds1(mb + B_SW + 4) & 255;
        uint4 k;
        for (int it = 0;; it++) {
          k = ld_rlx4((const uint4*)&G.pred[rb * 256 + hf * 64 + r2 * 128] + c16);
          k.x ^= tag; k.y ^= tag; k.z ^= tag; k.w ^= tag;
          if (!__any_sync(~0u, (k.x | k.y | k.z | k.w) & 255)) break;
          SPINCHK(it, 13);
        }
        const uint2 ahead = top2(k.x | (lane * 4), k.y | (lane * 4 + 1), k.z | (lane * 4 + 2), k.w | (lane * 4 + 3));
        if (lane == 0) sts2f(sm + OFF_MSC + 8, __uint_as_float((ahead.x & 127) ^ NOSPEC), __uint_as_float((ahead.y & 127) ^ NOSPEC));
        __syncwarp();
        if (lane == 0) mbar_arrive(mb + B_FULL3 + 8 * 15);
      } else if (fidx >= 0 && elect_one()) {
        wait3(60);
        mbar_expect_tx(mb + B_FULL, 65536);
#pragma unroll 1
        for (int h = 0; h < 2; h++) {
          const int up = h ^ hf ^ 1;
          mbar_wait(mb + B_EMPTY + 16 - 16 * h, 1);
#pragma unroll
          for (int i = 0; i < 4; i++) {
            const int f = (0x5140 >> (4 * i)) & 15;
            tma_2d(sm + ((GU_SLOTS >> (4 * f)) & 15) * SLOT_B + up * 8192, up ? &tmU : &tmG, fidx * 32, f * 128, mb + B_FULL, EFF);
            if (FDT) delay(clk(), FDT);
          }
          PTS(23 + h);
        }
#pragma unroll 1
        for (int j = 0; j < 8; j++) { mbar_wait(sm + bar3(32) + o3(PD0 + j * PDS / 2), 0); tma_2d(sm + OFF_COLSUM, &tmPD, 0, fidx * 256 + j * 32, mb + B_FFN, false); }
#pragma unroll 1
        for (int i = 0; i < 4; i++) {
          const int f = (0x7362 >> (4 * i)) & 15;
          const uint32_t d = sm + ((GU_SLOTS >> (4 * f)) & 15) * SLOT_B;
          mbar_wait(sm + bar3(32) + o3((GEV >> (4 * i)) & 15), 0);
          tma_2d(d, &tmG, fidx * 32, f * 128, mb + B_FFN, EFF);
          tma_2d(d + 8192, &tmU, fidx * 32, f * 128, mb + B_FFN, EFF);
          PTS(27 + i);
        }
      }
    }
    __syncwarp();
    const float sw = __uint_as_float(lds1(mb + B_SW));
    const int rr = lane >> 4, row00 = rb * 256 + hf * 64;
    uint2 pick;
    if (wid == 8) {
      wait3(61);
      delay(clk(), SDELAY);
      uint4 v;
      int id;
      for (int it = 0;; it++) {
        v = ld_rlx4(&G.cst[jp * 32 + lane]);
        id = __float2int_rn(__uint_as_float(v.w));
        if (!__any_sync(~0u, (id & 15) != 8)) break;
        SPINCHK(it, 14);
      }
      float2 pr;
      const uint32_t k = route(v, sw, id >> 4, pr);
      pick.x = __reduce_max_sync(~0u, k); pick.y = __reduce_max_sync(~0u, k == pick.x ? 0 : k);
      if (k == pick.x || k == pick.y) sts4(sm + OFF_MSC + 16 + (k == pick.y) * 16, k, lane, __float_as_uint(pr.x), __float_as_uint(pr.y));
      __syncwarp();
      if (lane == 0) { mbar_arrive(mb + B_SEL); PTS(16); }
    } else if (wid == 9) {
      wait3(61);
      delay(clk(), LDELAY);
      uint4 v[4];
      for (int it = 0;; it++) {
#pragma unroll
        for (int i = 0; i < 4; i++) v[i] = ld_rlx4(&G.st2[row00 + (i >> 1) * 128 + (i & 1) * 32 + lane]);
        if (!__any_sync(~0u, (v[0].w & v[1].w & v[2].w & v[3].w) != 0x41000000u)) break;
        SPINCHK(it, 6);
      }
      uint32_t k[4];
#pragma unroll
      for (int i = 0; i < 4; i++) {
        float2 pr;
        k[i] = route(v[i], sw, row00 + (i >> 1) * 128 + (i & 1) * 32 + lane, pr);
        const float nm = __uint_as_float(v[i].x) * (-1.f / D_);
        sts2f(sm + OFF_LNP + (i * 32 + lane) * 8, __uint_as_float(pack2(pr.x, pr.x)), __uint_as_float(pack2(nm, nm)));
      }
      const uint2 m = top2(k[0], k[1], k[2], k[3]);
      if (lane == 0) { st_rlx2(&G.cand[c3 * 32 + (rb * 2 + hf) * 2], m.x, m.y); sts2f(sm + OFF_MSC + 0, __uint_as_float(m.x), __uint_as_float(m.y)); }
      wait3(62);
      __syncwarp();
      if (lane == 0) { mbar_arrive(mb + B_OUT); PTS(12); }
      const int ca = 2047 - (((lane & 4) ? m.y : m.x) & 2047), ta = ((ca >> 1) & 64) + (ca & 63);
      uint32_t h0, h1, h2, h3;
      ldsm4_o<0>(sm + HST + ta * 256 + ((((lane & 3) * 4 + (lane >> 3)) ^ (ta & 7)) << 4), h0, h1, h2, h3);
      st_rlx4(&G.hsel[(32 + (rb * 2 + hf) * 2 + rr) * 128 + c3 * 16 + (lane & 15)], make_uint4(h0, h1, h2, h3));
    }
    mbar_wait(mb + B_OUT, 0);
    const float2 cf = lds2f(sm + OFF_MSC + 0);
    const int ca0 = ~__float_as_int(cf.x), ca1 = ~__float_as_int(cf.y), cand0 = ((ca0 >> 1) & 64) + (ca0 & 63), cand1 = ((ca1 >> 1) & 64) + (ca1 & 63);
    auto norm = [](const uint4& v, const float2& pr) {
      const uint32_t r = __float_as_uint(pr.x), m = __float_as_uint(pr.y);
      return make_uint4(hfma2(hadd2(v.x, m), r, v.x), hfma2(hadd2(v.y, m), r, v.y), hfma2(hadd2(v.z, m), r, v.z), hfma2(hadd2(v.w, m), r, v.w));
    };
    uint4* const og = (uint4*)(P.out + row00 * D_ + c3 * 128) + (lane & 15);
    if (wid == 8) {
      delay(clk(), CDELAY);
      uint32_t k;
      for (int it = 0;; it++) { k = ld_rlx(&G.cand[c3 * 32 + lane]); if (!__any_sync(~0u, k == SENT)) break; SPINCHK(it, 12); }
      const uint32_t m1 = __reduce_max_sync(~0u, k), m2 = __reduce_max_sync(~0u, k == m1 ? 0 : k);
      const uint32_t miss = ((m1 ^ pick.x) | (m2 ^ pick.y)) & 2047;
      if (miss && (k == m1 || k == m2)) {
        float2 pr;
        route(ld_rlx4(&G.st2[2047 - (k & 2047)]), sw, 0, pr);
        sts4(sm + OFF_MSC + 48 + (k == m2) * 16, k, 32 + lane, __float_as_uint(pr.x), __float_as_uint(pr.y));
      }
      if (lane == 0) sts1(sm + OFF_MSC + 80, miss);
      __syncwarp();
      if (lane == 0) { mbar_arrive(mb + B_SEL2); PTS(13); }
      const uint32_t kc = __float_as_uint(rr ? cf.y : cf.x);
      const int c = rr ? cand1 : cand0;
      if (kc != m1 && kc != m2) og[(c + (c & 64)) * 128] = norm(lds4(sm + HST + c * 256 + (((lane & 15) ^ (c & 7)) << 4)), lds2f(sm + OFF_LNP + c * 8));
    }
#pragma unroll 1
    for (int t0 = wid == 8 ? 120 : (11 - wid) * 8; t0 < (wid == 8 ? 128 : 120) * !NOOUT; t0 += 24) {
      uint4 v[4];
      float2 pr[4];
      const uint32_t ad = sm + HST + t0 * 256 + lane * 16;
      static_for<0, 4>([&](auto ic) { constexpr int i = decltype(ic)::value; v[i] = lds4_o<i * 512>(ad ^ (rr << 4) ^ (i << 5)); pr[i] = lds2f_o<i * 16>(sm + OFF_LNP + (t0 + rr) * 8); });
#pragma unroll
      for (int i = 0; i < 4; i++) v[i] = norm(v[i], pr[i]);
      if (t0 >= OHOLD) wait3(63);
#pragma unroll
      for (int i = 0; i < 4; i++) {
        const int tr = t0 + rr + 2 * i;
        if (tr != cand0 && tr != cand1) {
          if (OUTEF) asm volatile("st.global.L2::cache_hint.v4.u32 [%0], {%1,%2,%3,%4}, %5;" :: "l"(og + (tr + (tr & 64)) * 128), "r"(v[i].x), "r"(v[i].y), "r"(v[i].z), "r"(v[i].w), "l"(l2_stream()) : "memory");
          else og[(tr + (tr & 64)) * 128] = v[i];
        }
      }
    }
    if (wid == 11 && lane == 0) PTS(31);
  } else {
    asm volatile("setmaxnreg.inc.sync.aligned.u32 224;");
    const int t128 = tid & 127, warp = wid & 3, g = lane >> 2, t = lane & 3;
    const int mb3 = rb * 4 + wg * 2 + hf;
    float acc[64];
    uint4 abuf[3][4];
    uint32_t to;
    int tid2;
    {
      float acc0[96], acc1[96];
#pragma unroll
      for (int i = 0; i < 96; i++) { asm volatile("" : "=f"(acc0[i])); asm volatile("" : "=f"(acc1[i])); }
      const uint32_t xo0 = dlo(sb, 16) + hf * 512, xo1 = dlo(sb, 16) + (hf ^ 1) * 512;
      const uint32_t eb0 = (t128 << 24) + bars + B_EMPTY;
#pragma unroll 1
      for (int kb = 0; kb < 12; kb++) {
        const int s = kb & 3;
        mbar_wait(mb + B_FULL + 8 * s, (kb >> 2) & 1);
        if (LOCK) bar_sync(13, 256);
        if (kb == 0) TS(1);
        const uint32_t xs = xoff(s, wg) >> 4, ws = dlo(sb + woff(s), WSTR);
        pin(acc0); pin(acc1);
        wg_fence();
#pragma unroll
        for (int k = 0; k < 4; k++) {
          const uint64_t db = dsc<1024, 1>(ws + k * 128);
          const int sd = k == 0 ? kb : 1;
          wgmma_n192_ss<0, 1, 0>(acc0, dsc<1024, 1>(xs + xo0 + k * 2), db, sd);
          wgmma_n192_ss<0, 1, 0>(acc1, dsc<1024, 1>(xs + xo1 + k * 2), db, sd);
          if (k == RELK || k == 3) wg_commit();
          if (k == RELK) {
            wg_wait<1>();
            if (kb > 0 && t128 < 2) mbar_arrive_rem(eb0 + 8 * ((kb - 1) & 3));
          }
        }
        pin(acc0); pin(acc1);
      }
      float qa0[32], qa1[32], kv0[64], kv1[64];
#pragma unroll
      for (int i = 0; i < 96; i++) { if (i < 32) { qa0[i] = acc0[i]; qa1[i] = acc1[i]; } else { kv0[i - 32] = acc0[i]; kv1[i - 32] = acc1[i]; } }
      uint2 st[2][2];
      uint4 am;
      auto center = [&](float (&q)[32], float (&kv)[64], const uint2 (&v)[2]) {
        const uint32_t n0 = v[0].x & (t == 0 ? ~255u : 0u), n1 = v[1].x & (t == 0 ? ~255u : 0u);
        am = make_uint4(__byte_perm(n0, 0, 0x3232), __byte_perm(n1, 0, 0x3232),
                        __byte_perm(__float_as_uint(__uint_as_float(n0) - bf_hi(n0)), 0, 0x3232), __byte_perm(__float_as_uint(__uint_as_float(n1) - bf_hi(n1)), 0, 0x3232));
        wg_fence();
        wgmma_n64_rs<1, 0>(q, am.x, am.y, am.z, am.w, dsc<32, 0>(dlo(sb + OFF_COLSUM, 0)), 1);
        wgmma_n128_rs<1, 0>(kv, am.x, am.y, am.z, am.w, dsc<32, 0>(dlo(sb + OFF_COLSUM + 256, 0)), 1);
      };
      auto load_st = [&]() {
        mbar_wait(mb + B_AUX, 0);
#pragma unroll
        for (int i = 0; i < 4; i++) st[i >> 1][i & 1] = ld_rlx2((const uint2*)G.st1 + ((rb * 4 + wg * 2 + ((i >> 1) ^ hf)) * 2 + (warp >> 1)) * 96 + (warp & 1) * 16 + (i & 1) * 8 + g);
      };
      if (!wg) {
        wg_wait<0>();
        if (t128 < 2) mbar_arrive_rem(eb0 + 24);
        load_st();
#pragma unroll 1
        for (int s = 0; s < (B6E < 3 ? 3 : 4); s++) mbar_wait(mb + B_FULL + 8 * s, 1);
        bar_sync(6, 256);
      }
      static_for<0, 4>([&](auto sc) {
        constexpr int s = decltype(sc)::value;
        if (wg || (B6E < 3 && s == 3)) mbar_wait(mb + B_FULL + 8 * s, 1);
        const uint32_t xs = (wg ? xoff(s, 1) : xoff(s, 0)) >> 4, ws = dlo(sb + woff(s) + WSTR, WSTR);
        pin(kv0); pin(kv1); pin(qa0); pin(qa1);
        wg_fence();
#pragma unroll
        for (int k = 0; k < 4; k++) {
          const uint64_t db = dsc<1024, 1>(ws + k * 128);
          wgmma_n128_ss<0, 1, 0>(kv0, dsc<1024, 1>(xs + xo0 + k * 2), db, 1);
          wgmma_n128_ss<0, 1, 0>(kv1, dsc<1024, 1>(xs + xo1 + k * 2), db, 1);
          if (s == 0 && k == B6H - 1) { if (!wg) bar_sync(14, 256); wg_fence(); }
          if (k == 3 || (k == 2 && s == 0)) wg_commit();
          if (k == (s ? 3 : 2) && s < 3) {
            wg_wait<1>();
            if (s == 0) { if (wg && t128 < 2) mbar_arrive_rem(eb0 + 24); }
            else if (!wg) bar_arrive(8 + s, 256);
          }
        }
        if (s == B6E && wg) bar_arrive(6, 256);
        if (s == 3 && B6H && wg) bar_arrive(14, 256);
        if (s == STLD && wg) load_st();
      });
      if (CUTS & 2) {
        cut<6>(zero);
#pragma unroll
        for (int i = 0; i < 4; i++) asm volatile("" : "+r"(st[i >> 1][i & 1].x), "+r"(st[i >> 1][i & 1].y) :: "memory");
      }
      center(qa0, kv0, st[0]);
      wg_commit();
      if (B6E > 3 && wg) bar_arrive(6, 256);
      float rs[2][2];
#pragma unroll
      for (int i = 0; i < 4; i++) rs[i >> 1][i & 1] = __uint_as_float(st[i >> 1][i & 1].y & ~255u);
      const uint32_t sad = sm + (wg ? 11 : 2) * SLOT_B + (warp * 16 + (lane & 15)) * 128 + (((lane >> 4) ^ (lane & 7)) << 4);
      wg_wait<0>();
      pin(kv0); pin(kv1); pin(qa0); pin(qa1); pin4(am);
      center(qa1, kv1, st[1]);
      wg_commit();
      if (wg) bar_arrive(11, 256);
      if (CUTS & 1) cut<2>(zero);
      TS(2);
      float rl[2];
      uint32_t r2[2];
      auto scales = [&](int m, uint32_t z) {
#pragma unroll
        for (int h = 0; h < 2; h++) { const float r = __uint_as_float(__float_as_uint(rs[m][h]) + z); r2[h] = pack2(r, r); rl[h] = r * 1.4426950408889634f; }
      };
      auto phi8 = [&](const float* a) {
        return make_uint4(phi2(a[0], a[1], r2[0], rl[0]), phi2(a[2], a[3], r2[1], rl[1]), phi2(a[4], a[5], r2[0], rl[0]), phi2(a[6], a[7], r2[1], rl[1]));
      };
      auto stage = [&](float (&a)[64], auto mc) {
        constexpr int m = decltype(mc)::value;
        uint4 r[4];
        scales(m, 0);
#pragma unroll
        for (int j = 0; j < 4; j++) r[j] = phi8(a + j * 8);
        if (m == 0 || wg) bar_sync(wg ? 9 + m : 11, 256 + (r[SBAR].x & zero));
#pragma unroll
        for (int j = 0; j < 4; j++) {
          const int v = 32 + j * 8;
          stsm4_o<WSTR + m * 8192>(sad ^ (j << 5), hmul2(pack2(a[v], a[v + 1]), r2[0]), hmul2(pack2(a[v + 2], a[v + 3]), r2[1]),
                                                   hmul2(pack2(a[v + 4], a[v + 5]), r2[0]), hmul2(pack2(a[v + 6], a[v + 7]), r2[1]));
        }
#pragma unroll
        for (int j = 0; j < 4; j++) stsm4_o<m * 8192>(sad ^ (j << 5), r[j].x, r[j].y, r[j].z, r[j].w);
      };
      stage(kv0, std::integral_constant<int, 0>{});
      wg_wait<0>();
      pin(kv1); pin(qa1); pin4(am);
      stage(kv1, std::integral_constant<int, 1>{});
      fence_async_smem();
      TS(3);
      uint32_t xr[8][4];
      auto load_xr = [&]() {
        const uint32_t xa = sm + hf * 8192 + (warp * 16 + (lane & 15)) * 128 + (((lane >> 4) ^ (lane & 7)) << 4);
#pragma unroll
        for (int q = 0; q < 8; q++) ldsm4_o<0>((xa ^ ((q & 3) << 5)) + xoff(rank * 2 + (q >> 2), wg), xr[q][0], xr[q][1], xr[q][2], xr[q][3]);
      };
      if (!wg) { bar_arrive(4, 256); load_xr(); }
      else {
        float ka[36];
#pragma unroll
        for (int i = 0; i < 36; i++) ka[i] = 0.f;
        auto kv_mma = [&](auto ic) {
          constexpr int i = decltype(ic)::value;
          constexpr uint32_t o = sb + (i < 8 ? 11 : 2) * SLOT_B + (i & 7) * 2048;
          wgmma_n72_ss<1, 1, 0>(ka, dsc<1024, 1>(dlo(o, 8192)), dsc<1024, 1>(dlo(o + WSTR, sb + OFF_STATS - o - WSTR)), i);
        };
        mbar_wait(mb + B_LATE, 0);
        bar_sync(3, 128);
        wg_fence();
        static_for<0, 8>(kv_mma);
        wg_commit();
        uint4* dst = &G.kvp[cg * 2304 + rb * 32];
        if (CUTS & 4) cut<3>(zero);
        load_xr();
        bar_sync(4, 256);
        static_for<8, 16>(kv_mma);
        wg_commit();
        if (QHOLD == 1) bar_arrive(8, 256);
        wg_wait<0>();
        pin(ka);
        if (QHOLD == 2) bar_arrive(8, 256);
        TS(4);
        if (warp < 2) {
          st_rlx4(dst + warp * 512 + lane, make_uint4(pack2(ka[0], ka[1]), pack2(ka[4], ka[5]), pack2(ka[8], ka[9]), pack2(ka[12], ka[13])));
          st_rlx4(dst + warp * 512 + 256 + lane, make_uint4(pack2(ka[2], ka[3]), pack2(ka[6], ka[7]), pack2(ka[10], ka[11]), pack2(ka[14], ka[15])));
        } else {
          st_rlx4(dst + warp * 512 + lane, make_uint4(pack2(ka[16], ka[17]), pack2(ka[20], ka[21]), pack2(ka[24], ka[25]), pack2(ka[28], ka[29])));
          st_rlx4(dst + warp * 512 + 256 + lane, make_uint4(pack2(ka[18], ka[19]), pack2(ka[22], ka[23]), pack2(ka[26], ka[27]), pack2(ka[30], ka[31])));
        }
        st_rlx((uint32_t*)(dst + 2048) + t128, pack2(ka[32], ka[34]));
        if (QHOLD == 3) bar_arrive(8, 256);
        if (t128 == 0) mbar_arrive(sm + bar3(60));
      }
      TS(5);
      uint32_t pq[16], pq0[16];
      auto q_mma = [&](float (&q)[32], uint32_t xo, int s0, int s1) {
#pragma unroll 1
        for (int s = s0; s < s1; s++) {
          const uint32_t xs = (xoff(s, wg) >> 4) + xo, ws = dlo(sb + woff(s), 8192);
          pin(q);
          wg_fence();
#pragma unroll
          for (int k = 0; k < 4; k++) wgmma_n64_ss<0, 1, 0>(q, dsc<1024, 1>(xs + k * 2), dsc<1024, 1>(ws + k * 128), 1);
          wg_commit();
        }
      };
      auto q_phi = [&](float (&q)[32], int m, uint32_t (&pq)[16], int lo, int hi) {
        scales(m, zero);
#pragma unroll
        for (int j = lo; j < hi; j++) { const uint4 r = phi8(q + j * 8); pq[j * 4] = r.x; pq[j * 4 + 1] = r.y; pq[j * 4 + 2] = r.z; pq[j * 4 + 3] = r.w; }
      };
      auto o_of = [&](uint32_t (&pq)[16], uint4 (&o)[4], uint4* first, bool pub) {
        float oa[2][20];
#pragma unroll
        for (int i = 0; i < 40; i++) oa[i / 20][i % 20] = 0.f;
        wg_fence();
#pragma unroll
        for (int ks = 0; ks < 4; ks++) {
          wgmma_n40_rs<1, 0>(oa[ks >> 1], pq[ks * 4], pq[ks * 4 + 1], pq[ks * 4 + 2], pq[ks * 4 + 3], dsc<1024, 1>(dlo(sb + OFF_KVB + ks * 2048, 8192)), ks & 1);
          if (ks & 1) wg_commit();
        }
#pragma unroll
        for (int h = 0; h < 2; h++) {
          if (h) wg_wait<0>(); else wg_wait<1>();
          pin(oa[h]);
          const float (&d)[20] = oa[h];
          const float i0 = rcp(d[16] + 1e-6f), i1 = rcp(d[18] + 1e-6f);
#pragma unroll
          for (int k2 = 0; k2 < 2; k2++) {
            o[h * 2 + k2] = make_uint4(pack2(d[k2 * 8] * i0, d[k2 * 8 + 1] * i0), pack2(d[k2 * 8 + 2] * i1, d[k2 * 8 + 3] * i1),
                                       pack2(d[k2 * 8 + 4] * i0, d[k2 * 8 + 5] * i0), pack2(d[k2 * 8 + 6] * i1, d[k2 * 8 + 7] * i1));
            if (pub && !h) st_rlx4(first + (h * 2 + k2) * 1024, o[h * 2 + k2]);
          }
        }
#pragma unroll
        for (int i = 0; i < 16; i++) asm volatile("" : "+r"(pq[i]) :: "memory");
      };
      bar_sync(wg ? 7 : 8, 256);
      TS(12);
      q_mma(qa1, xo1, 0, 4);
      if (wg) {
        if (QX) {
          pin(qa0);
          wg_fence();
#pragma unroll
          for (int k = 0; k < 4 * QX; k++) wgmma_n64_ss<0, 1, 0>(qa0, dsc<1024, 1>((xoff(k >> 2, 1) >> 4) + xo0 + (k & 3) * 2), dsc<1024, 1>(dlo(sb + woff(k >> 2), 8192) + (k & 3) * 128), 1);
          wg_commit();
        }
        bar_arrive(8, 256);
        wg_wait<QX ? 1 : 0>();
      }
      else { bar_arrive(7, 256); wg_wait<0>(); }
      TS(13);
      if (tid == 0) mbar_arrive(mb + B_EMPTY + 16);
      cut<5>(zero);
      pin(qa1);
      q_phi(qa1, 1, pq, 0, 4);
      tid2 = __shfl_sync(~0u, tid, lane);
      uint32_t done = 0;
#pragma unroll
      for (int j = 0; j < 8; j++) done |= pq[2 * j] | pq[2 * j + 1] | xr[j][3];
      bar_sync(wg ? 7 : 8, 256 + (done & zero));
      TS(9);
      q_mma(qa0, xo0, wg * QX, 4);
      if (!wg) bar_arrive(7, 256);
      wg_wait<0>();
      pin(qa0);
      if (t128 == 0) mbar_arrive(mb + B_EMPTY + 8 * wg);
      TS(6);
#pragma unroll
      for (int i = 0; i < 16; i++) pq0[i] = 0;
#pragma unroll 1
      for (int r = 0;; r++) {
      if (ASYM && r == wg) { pin(qa0); q_phi(qa0, 0, pq0, 0, ASYM); }
      if (r) break;
      {
        uint4 a, v[8];
        uint32_t z[8], zs;
        const int blk = warp * 2 + wg;
        mbar_wait(mb + B_KVL, 0);
        static_for<0, 8>([&](auto ic) { constexpr int i = decltype(ic)::value; v[i] = lds4_o<sb + 11 * SLOT_B + i * 512>(own + (blk + (blk & 4)) * 4096 + lane * 16); });
#pragma unroll
        for (int i = 0; i < 8; i++) z[i] = lds1(sm + 2 * SLOT_B + i * 512 + t128 * 4);
#pragma unroll 1
        for (int it = 0;; it++) {
          zs = hadd2(hadd2(hadd2(z[0], z[1]), hadd2(z[2], z[3])), hadd2(hadd2(z[4], z[5]), hadd2(z[6], z[7])));
          a = hadd8(hadd8(hadd8(v[0], v[1]), hadd8(v[2], v[3])), hadd8(hadd8(v[4], v[5]), hadd8(v[6], v[7])));
          TSV(20, it + 1);
          if (!__any_sync(~0u, hnan(hadd2(hadd2(hadd2(a.x, a.y), hadd2(a.z, a.w)), zs)))) break;
          uint32_t mm = 0;
#pragma unroll
          for (int i = 0; i < 8; i++) mm = max4(max(mm, z[i]), v[i]);
          if (!__any_sync(~0u, mm == SENT)) break;
#pragma unroll
          for (int i = 0; i < 8; i++) { v[i] = ld_rlx4(&G.kvp[cg * 2304 + blk * 256 + i * 32 + lane]); z[i] = ld_rlx((const uint32_t*)&G.kvp[cg * 2304 + 2048 + i * 32] + t128); }
          SPINCHK(it, 4);
        }
        TS(23);
        const uint32_t kb0 = sm + OFF_KVB + blk * 1024 + (lane & 7) * 128;
        stsm4(kb0 + (((lane >> 3) ^ (lane & 7)) << 4), a.x, a.y, a.z, a.w);
        asm volatile("stmatrix.sync.aligned.m8n8.x1.shared.b16 [%0], {%1};" :: "r"(kb0 + ((4 ^ (lane & 7)) << 4)), "r"(zs >> (16 * wg)) : "memory");
        fence_async_smem();
        bar_sync(12, 256);
      }
      TS(7);
      if (t128 == 0) mbar_arrive_rem((wg << 24) + sb + bar3(48));
      to = clk();
      o_of(pq, abuf[1], &G.obuf[((mb3 ^ 1) * 64 + hf * 32 + c3) * 128 + (tid2 & 127)], true);
      TS(29);
      }
      if (!ASYM) cut<4>(zero);
      pin(qa0);
      q_phi(qa0, 0, pq0, ASYM, 4);
      o_of(pq0, abuf[0], nullptr, false);
#pragma unroll
      for (int q = 0; q < 32; q++) { asm volatile("" : "+r"(xr[q >> 2][q & 3])); acc[q * 2] = bf_lo(xr[q >> 2][q & 3]); acc[q * 2 + 1] = bf_hi(xr[q >> 2][q & 3]); }
      pin(acc);
    }
    {
    const int t128 = tid2 & 127, lane = tid2 & 31, g = lane >> 2, t = lane & 3;
    TS(8);
    uint32_t wa[32][4];
    auto load_gu = [&](int f, int lo = 0, int hi = 8) {
      const uint32_t ad = own + ((lane >> 3) & 1) * 8192 + ((lane >> 4) * 8 + (lane & 7)) * 64 + ((warp ^ ((lane >> 1) & 3)) << 4) + ((GU_SLOTS >> (16 * wg + 4 * f)) & 15) * SLOT_B;
      static_for<0, 8>([&](auto ic) { constexpr int i = decltype(ic)::value; if (i >= lo && i < hi) ldsm4t_o<sb + i * 1024>(ad, wa[f * 8 + i]); });
    };
    {
      const uint32_t la = own + wg * 8192 + t128 * 16, fa = sm + wg * 256;
      int pv = tid2 & zero;
      auto step = [&](const int p, auto jc) {
        constexpr int j = decltype(jc)::value;
        uint4 (&a)[4] = abuf[j == 3 ? 0 : (j + 1) % 3];
        uint4 (&n)[4] = abuf[j == 3 ? 1 : (j + 2) % 3];
        auto fetch = [&]() {
          const uint32_t ra = la + ((p + 1) & 3) * SLOT_B;
          mbar_wait(fa + bar3(0) + o3(p + 1), 0);
          n[0] = lds4_o<sb + 10 * SLOT_B>(ra); n[1] = lds4_o<sb + 10 * SLOT_B + 2048>(ra); n[2] = lds4_o<sb + 10 * SLOT_B + 4096>(ra); n[3] = lds4_o<sb + 10 * SLOT_B + 6144>(ra);
        };
        const bool early = j == 0 ? p > 1 : j == 1 ? true : j == 2 ? p < 15 : false;
        const uint32_t bs = dlo(sb, 8192) + (uint32_t)((WO_SLOTS >> (4 * p)) & 15) * (SLOT_B >> 4);
        if (early) fetch();
        if (p == 1) TS(28);
        pin(acc);
        wg_fence();
#pragma unroll
        for (int k = 0; k < 4; k++) {
          wgmma_n128_rs<1, 0>(acc, a[k].x, a[k].y, a[k].z, a[k].w, dsc<1024, 1>(bs + k * 128), 1);
          if (k == 0) { if (j != 2 || p < 15) mbar_wait(mb + B_FULL3 + 8 * p + 8, 0); wg_fence(); }
        }
        wg_commit();
        if (j == 3) {
#pragma unroll
          for (int i = 0; i < 4; i++) { abuf[2][i] = make_uint4(zero, zero, zero, zero); pin4(abuf[2][i]); }
          if (GUP == 0) { if (fidx >= 0) mbar_wait(mb + B_FULL, 0); load_gu(0); }
          if (GUP < 2) load_gu(1);
          delay(to, BDELAY);
#pragma unroll
          for (int k = 2; k < 4; k++) st_rlx4(&G.obuf[((mb3 ^ 1) * 64 + hf * 32 + c3) * 128 + t128 + k * 1024], n[k]);
          TS(24);
          fetch();
          TS(27);
        } else if (j == 0 && p == 1) fetch();
        pv++;
        if (__any_sync(~0u, max(max4(max4(0, n[0]), n[1]), max4(max4(0, n[2]), n[3])) == SENT)) {
          const uint4* q = &G.obuf[(mb3 * 64 + chunk_of(pv) * 4) * 128 + t128];
#pragma unroll 1
          for (int it = 0;; it++) {
#pragma unroll
            for (int i = 0; i < 4; i++) n[i] = ld_rlx4(q + i * 128);
            TSV(21, _ts | 1 << pv);
            if (!__any_sync(~0u, max(max4(max4(0, n[0]), n[1]), max4(max4(0, n[2]), n[3])) == SENT)) break;
            SPINCHK(it, 5);
          }
        }
        if (lane == 0 && p < 11) mbar_arrive_rem((wg << 24) + sb + bar3(48) + o3(p + 1));
        wg_wait<1>();
        pin(acc);
        if (j < 3) {
#pragma unroll
          for (int i = 0; i < 4; i++) pin4(abuf[j][i]);
        }
        if (j == 3 || (j == 0 && p == 1)) {
#pragma unroll
          for (int k = 0; k < 4; k++) if ((k < W0N) == (j == 3)) st_rlx4(&G.obuf[(mb3 * 64 + cg * 4 + k) * 128 + t128], abuf[0][k]);
        }
        if (lane == 0) mbar_arrive(sm + bar3(32) + o3(p));
      };
      if (GUP > 0) { if (fidx >= 0) mbar_wait(mb + B_FULL, 0); load_gu(0); }
      if (GUP == 2) load_gu(1);
      mbar_wait(mb + B_FULL3, 0);
      step(0, std::integral_constant<int, 3>{});
#pragma unroll 1
      for (int pp = 1; pp < 16; pp += 3) static_for<0, 3>([&](auto jc) { step(pp + decltype(jc)::value, jc); });
    }
    uint4 wb[4];
#pragma unroll
    for (int i = 0; i < 4; i++) wb[i] = lds4(sm + OFF_LNP + ((g & 1) ? t * 64 : 256) + i * 16);
    const float2 ah = lds2f(sm + OFF_MSC + 8);
    const int ta = __float_as_int((lane & 8) ? ah.y : ah.x);
    int sl = (ta & 7) * 4 + ((ta >> 3) & 1), son = lane < 16 && (ta >> 4) == wid;
    float sid = c3 ? 1.f : (float)((mb3 * 64 + (ta & 63)) * 16 + 1);
    uint4 *sp = &G.cst[(lane & 7) * 32 + (rb * 2 + hf) * 2 + ((lane >> 3) & 1)], *sq = &G.st2[mb3 * 64 + warp * 16 + (t & 1) * 8 + g];
    asm volatile("" : "+r"(sl), "+r"(son), "+f"(sid), "+l"(sp), "+l"(sq) :: "memory");
    if (T4) cut<7>(zero);
    wg_wait<0>();
    pin(acc);
#pragma unroll
    for (int i = 0; i < 4; i++) pin4(abuf[0][i]);
    TS(10);
    const uint32_t msc = sm + OFF_MSC;
    uint32_t hp[8][4];
    {
      float se[2][4], q[4] = {0.f, 0.f, 0.f, 0.f};
#pragma unroll
      for (int i = 0; i < 8; i++) se[i >> 2][i & 3] = 0.f;
#pragma unroll
      for (int j = 0; j < 8; j++) {
#pragma unroll
        for (int i = 0; i < 4; i++) { const float a = acc[j * 8 + i * 2], c = acc[j * 8 + i * 2 + 1]; hp[j][i] = pack2(a, c); q[i] = fmaf(a, a, fmaf(c, c, q[i])); }
        mma16816(se[j & 1], hp[j], (j & 1) ? wb[j >> 1].z : wb[j >> 1].x, (j & 1) ? wb[j >> 1].w : wb[j >> 1].y);
      }
      const bool od = t & 1;
      const float q0 = q[0] + q[2], q1 = q[1] + q[3];
      float qq = (od ? q1 : q0) + __shfl_xor_sync(~0u, od ? q0 : q1, 1);
      qq += __shfl_xor_sync(~0u, qq, 2);
      const float ss = od ? se[0][2] + se[1][2] : se[0][0] + se[1][0], ee = od ? se[0][3] + se[1][3] : se[0][1] + se[1][1];
      red4(son, sp, __shfl_sync(~0u, ss, sl), __shfl_sync(~0u, qq, sl), __shfl_sync(~0u, ee, sl), sid);
      red4(t < 2, sq, ss, qq, ee, 1.f);
#pragma unroll 1
      for (int c = 0; c < 2; c++) {
        const int tr = __float_as_int(c ? ah.y : ah.x);
        if ((tr >> 4) == wid && g == (tr & 7)) {
#pragma unroll
          for (int i = 0; i < 4; i++)
            st_rlx4(&G.hsel[((rb * 2 + hf) * 2 + c) * 128 + c3 * 16 + i * 4 + t], (tr & 8) ? make_uint4(hp[2 * i][1], hp[2 * i][3], hp[2 * i + 1][1], hp[2 * i + 1][3])
                                                                                           : make_uint4(hp[2 * i][0], hp[2 * i][2], hp[2 * i + 1][0], hp[2 * i + 1][2]));
        }
      }
      if (lane == 0) mbar_arrive(sm + bar3(61));
      TS(11);
    }
    uint32_t wd[8][2][4];
    const uint32_t dw = sm + ((D_SLOTS >> (2 * (wid & 6))) & 15) * SLOT_B + (wid & 1) * 8192;
    const uint32_t da = dw + ((lane >> 4) * 8 + (lane & 7)) * 128 + ((((lane >> 3) & 1) ^ (lane & 7)) << 4);
    const uint32_t xl = own + ((D_SLOTS >> (8 * wg + ((lane & 16) >> 2))) & 15) * SLOT_B + (lane & 8) * 1024 + (lane & 7) * 16;
    int pass = 0;
    if (!GUPOS) { if (fidx >= 0) mbar_wait(mb + B_FFN, 1); load_gu(2); load_gu(3); }
    {
      bar_sync(1, 256);
      const uint32_t ha = sm + HST + wid * 4096 + (lane & 15) * 256 + (((lane >> 4) ^ (lane & 7)) << 4);
      static_for<0, 8>([&](auto jc) { constexpr int j = decltype(jc)::value; stsm4_o<(j >> 2) * 128>(ha ^ ((j & 3) << 5), hp[j][0], hp[j][1], hp[j][2], hp[j][3]); });
      asm volatile("fence.acq_rel.cta;" ::: "memory");
      __syncwarp();
      if (lane == 0) mbar_arrive(sm + bar3(62));
    }
    auto load_d1 = [&]() {
      if (fidx >= 0) mbar_wait(mb + B_FFN + 8, 0);
      static_for<0, 8>([&](auto ic) { constexpr int i = decltype(ic)::value; ldsm4t_o<(i & 1) * 2048>(da ^ ((i >> 1) << 5), wd[i >> 1][i & 1]); });
    };
    if (GUPOS) { if (fidx >= 0) mbar_wait(mb + B_FFN, 1); load_gu(2); load_gu(3); }
    if (!D1POS) load_d1();
#pragma unroll 1
    for (;; pass++) {
      TS(15);
      mbar_wait(mb + B_SEL, 0);
      const uint4 sx = lds4(msc + 16 + pass * 32 + (lane & 16));
      TS(26);
      const uint4* xp = &G.hsel[sx.y * 128 + wid * 16 + (lane & 15)];
      uint4 xv = ld_rlx4(xp);
      if (D1POS && !pass) load_d1();
#pragma unroll 1
      for (int it = 0; __any_sync(~0u, max4(0, xv) == SENT); it++) { xv = ld_rlx4(xp); SPINCHK(it, 7); }
      const float f = __uint_as_float(sx.z), n = __uint_as_float(sx.w);
      sts4(dw + ((lane & 12) * 2 + (lane >> 4) * 4 + t) * 16, pack2(fmaf(bf_lo(xv.x), f, n), fmaf(bf_hi(xv.x), f, n)), pack2(fmaf(bf_lo(xv.y), f, n), fmaf(bf_hi(xv.y), f, n)),
           pack2(fmaf(bf_lo(xv.z), f, n), fmaf(bf_hi(xv.z), f, n)), pack2(fmaf(bf_lo(xv.w), f, n), fmaf(bf_hi(xv.w), f, n)));
      if (wid == rb && (g & 3) == (cg >> 2)) sts4(msc + 96 + (lane >> 4) * 16 + t * 32, xv.x, xv.y, xv.z, xv.w);
      bar_sync(2 + wg, 128);
      TS(14);
      float gu[4][4];
#pragma unroll
      for (int i = 0; i < 16; i++) gu[i >> 2][i & 3] = 0.f;
      uint4 xb[4];
      static_for<0, 4>([&](auto ic) { constexpr int i = decltype(ic)::value; xb[i] = lds4_o<sb + i * 128>(xl); });
#pragma unroll
      for (int i = 0; i < 16; i++) {
        const int ks = i & 7;
#pragma unroll
        for (int j = i < 8 ? 2 : 0; j < (i < 8 ? 4 : 2); j++) mma16816(gu[j], wa[j * 8 + ks], (ks & 1) ? xb[ks >> 1].z : xb[ks >> 1].x, (ks & 1) ? xb[ks >> 1].w : xb[ks >> 1].y);
        if (i == D2I) {
          const uint32_t dd = da | ((__float_as_uint(gu[2][0]) | __float_as_uint(gu[3][0])) & zero);
          static_for<0, 8>([&](auto jc) { constexpr int j = decltype(jc)::value; ldsm4t_o<4096 + (j & 1) * 2048>(dd ^ ((j >> 1) << 5), wd[4 + (j >> 1)][j & 1]); });
          if (T1) cut<8>(zero);
#pragma unroll
          for (int j = 0; j < 4; j++) { pin(gu[j]); pin4(xb[j]); }
        }
      }
      {
        float o[4];
#pragma unroll
        for (int j = 0; j < 4; j++) o[j] = t == 0 ? gu[0][j] : t == 1 ? gu[1][j] : t == 2 ? gu[2][j] : gu[3][j];
        const float e0 = ((t & 2) ? o[2] : o[0]) + __shfl_xor_sync(~0u, (t & 2) ? o[0] : o[2], 2), e1 = ((t & 2) ? o[3] : o[1]) + __shfl_xor_sync(~0u, (t & 2) ? o[1] : o[3], 2);
        sts1(sm + (wg ? DS1 : DS0) * SLOT_B + 1024 + t128 * 4, __float_as_uint(((t & 1) ? e1 : e0) + __shfl_xor_sync(~0u, (t & 1) ? e0 : e1, 1)));
      }
      TS(25);
      mbar_wait(mb + B_SEL2, 0);
      const uint32_t miss = lds1(msc + 80);
      bar_sync(1, 256);
      if (pass || !miss) break;
      load_gu(2); load_gu(3);
    }
    {
      const uint4 p0 = lds4_o<sb + DS0 * SLOT_B + 1024>(own + lane * 16), p1 = lds4_o<sb + DS1 * SLOT_B + 1024>(own + lane * 16);
      const float g0 = __uint_as_float(p0.x) + __uint_as_float(p1.x), g1 = __uint_as_float(p0.y) + __uint_as_float(p1.y);
      const float u0 = __uint_as_float(p0.z) + __uint_as_float(p1.z), u1 = __uint_as_float(p0.w) + __uint_as_float(p1.w);
      const uint32_t act = pack2(g0 * rcp(1.f + ex2(-1.4426950408889634f * g0)) * u0, g1 * rcp(1.f + ex2(-1.4426950408889634f * g1)) * u1);
      uint32_t bq[4];
#pragma unroll
      for (int i = 0; i < 4; i++) {
        const uint32_t lo = __shfl_sync(~0u, act, i * 8 + 2 * t), hi = __shfl_sync(~0u, act, i * 8 + 2 * t + 1);
        bq[i] = __byte_perm(lo, hi, (g & 1) ? 0x7632 : 0x5410);
      }
      TS(16);
      float ya[8][4];
#pragma unroll
      for (int i = 0; i < 8; i++) { ya[i][0] = 0.f; ya[i][1] = 0.f; ya[i][2] = 0.f; ya[i][3] = 0.f; }
#pragma unroll
      for (int ks = 0; ks < 2; ks++)
#pragma unroll
        for (int i = 0; i < 8; i++) mma16816(ya[i], wd[i][ks], bq[ks * 2], bq[ks * 2 + 1]);
    if (fidx >= 0) {
      uint2* const yp = (uint2*)&G.ybuf[((wid * 16 + t * 2) * NFFN + fidx) * 4] + g;
#pragma unroll
      for (int h = 0; h < 2; h++) {
        float o[4];
#pragma unroll
        for (int j = 0; j < 4; j++) o[j] = t == 0 ? ya[h * 4][j] : t == 1 ? ya[h * 4 + 1][j] : t == 2 ? ya[h * 4 + 2][j] : ya[h * 4 + 3][j];
        st_rlx2(yp + h * (8 * NFFN * 8), __float_as_uint(o[0]), __float_as_uint(o[1]));
        st_rlx2(yp + h * (8 * NFFN * 8) + NFFN * 8, __float_as_uint(o[2]), __float_as_uint(o[3]));
      }
    }
    }
    const uint32_t ty = clk();
    TS(17);
    if (wid < 7) {
      const uint4* const yq = &G.ybuf[b * NFFN * 4 + wid * 64 + lane];
      const uint4 sel = lds4(msc + 16 + pass * 32 + (lane & 1) * 16);
      const uint32_t fh = lds1(msc + 96 + (lane & 1) * 16 + (g & 3) * 32 + (cg & 3) * 4);
      const float r = __uint_as_float(sel.x ^ (~(uint32_t)((int)sel.x >> 31) | 0x80000000u));
      float sg = rcp(1.f + ex2(-1.4426950408889634f * r)), base = fmaf((lane & 2) ? bf_hi(fh) : bf_lo(fh), 1.f + __uint_as_float(sel.z), __uint_as_float(sel.w));
      __nv_bfloat16* op = P.out + (size_t)(2047 - (sel.x & 2047)) * D_ + b * 8 + ((lane >> 1) & 7);
      asm volatile("" : "+f"(sg), "+f"(base), "+l"(op) :: "memory");
      delay(ty | (__float_as_uint(sg) & zero), YDELAY);
      uint4 v0, v1;
#pragma unroll 1
      for (int it = 0;; it++) {
        v0 = ld_rlx4(yq); v1 = ld_rlx4(yq + 32);
        TSV(22, it + 1);
        if (!__any_sync(~0u, max(max4(0, v0), max4(0, v1)) == SENT)) break;
        SPINCHK(it, 8);
      }
      if (lane == 0) mbar_arrive(sm + bar3(63));
      TS(18);
      float y0 = __uint_as_float(v0.x) + __uint_as_float(v1.x), y1 = __uint_as_float(v0.y) + __uint_as_float(v1.y);
      float y2 = __uint_as_float(v0.z) + __uint_as_float(v1.z), y3 = __uint_as_float(v0.w) + __uint_as_float(v1.w);
      float z0 = ((lane & 16) ? y2 : y0) + __shfl_xor_sync(~0u, (lane & 16) ? y0 : y2, 16), z1 = ((lane & 16) ? y3 : y1) + __shfl_xor_sync(~0u, (lane & 16) ? y1 : y3, 16);
      z0 = ((lane & 8) ? z1 : z0) + __shfl_xor_sync(~0u, (lane & 8) ? z0 : z1, 8);
      z0 += __shfl_xor_sync(~0u, z0, 4);
      const uint32_t yx = sm + OFF_COLSUM;
      if (!(lane & 4)) sts1(yx + (t * 4 + (lane >> 3)) * 32 + wid * 4, __float_as_uint(z0));
      if (wid) bar_arrive(1, 224);
      else {
        bar_sync(1, 224);
        const uint4 a = lds4(yx + (lane & 15) * 32), c = lds4(yx + (lane & 15) * 32 + 16);
        const float y = ((__uint_as_float(a.x) + __uint_as_float(a.y)) + (__uint_as_float(a.z) + __uint_as_float(a.w))) + ((__uint_as_float(c.x) + __uint_as_float(c.y)) + __uint_as_float(c.z));
        if (lane < 16) *op = __float2bfloat16(fmaf(y, sg, base));
        if (b == 0 && lane == 16) G.epoch = lds1(mb + B_SW + 4);
      }
    }
    }
    TS(19); TSG(31);
    if (warp == 0) TS_DUMP(wg);
  }
}

typedef CUresult (*EncodeFn)(CUtensorMap*, CUtensorMapDataType, cuuint32_t, void*, const cuuint64_t*, const cuuint64_t*, const cuuint32_t*,
                             const cuuint32_t*, CUtensorMapInterleave, CUtensorMapSwizzle, CUtensorMapL2promotion, CUtensorMapFloatOOBfill);
void make_map(EncodeFn enc, CUtensorMap* m, const void* p, uint64_t cols, uint64_t rows, uint64_t d0, uint32_t b0, uint32_t b1, uint32_t b2, CUtensorMapSwizzle sw,
              CUtensorMapL2promotion promo = CU_TENSOR_MAP_L2_PROMOTION_L2_128B) {
  cuuint64_t dims[3] = {d0, rows, cols / d0}, str[2] = {cols * 2, d0 * 2};
  cuuint32_t box[3] = {b0, b1, b2}, es[3] = {1, 1, 1};
  enc(m, CU_TENSOR_MAP_DATA_TYPE_BFLOAT16, b2 ? 3 : 2, const_cast<void*>(p), dims, str, box, es, CU_TENSOR_MAP_INTERLEAVE_NONE, sw,
      promo, CU_TENSOR_MAP_FLOAT_OOB_FILL_NONE);
}

}

extern "C" void kernel_launch(void* const* d_in, const int* in_sizes, int n_in, void* d_out, int out_size) {
  (void)in_sizes; (void)n_in; (void)out_size;
  Ptrs P;
  P.x = (const __nv_bfloat16*)d_in[0]; P.wqkv = (const __nv_bfloat16*)d_in[1]; P.wo = (const __nv_bfloat16*)d_in[2];
  P.wr = (const __nv_bfloat16*)d_in[4]; P.wg = (const __nv_bfloat16*)d_in[5]; P.wu = (const __nv_bfloat16*)d_in[6];
  P.wd = (const __nv_bfloat16*)d_in[7]; P.out = (__nv_bfloat16*)d_out;
  void* fn = nullptr;
  cudaDriverEntryPointQueryResult q;
  cudaGetDriverEntryPoint("cuTensorMapEncodeTiled", &fn, cudaEnableDefault, &q);
  EncodeFn enc = (EncodeFn)fn;
  CUtensorMap tmX, tmW, tmO, tmG, tmU, tmD, tmM, tmPG, tmPU, tmPD;
  make_map(enc, &tmX, P.x, D_, S_, D_, 64, 128, 0, CU_TENSOR_MAP_SWIZZLE_128B);
  make_map(enc, &tmW, P.wqkv, 3 * D_, D_, 3 * D_, 64, 64, 0, CU_TENSOR_MAP_SWIZZLE_128B);
  make_map(enc, &tmG, P.wg, F_, D_, F_, 32, 128, 0, CU_TENSOR_MAP_SWIZZLE_64B);
  make_map(enc, &tmU, P.wu, F_, D_, F_, 32, 128, 0, CU_TENSOR_MAP_SWIZZLE_64B);
  make_map(enc, &tmD, P.wd, D_, F_, 64, 64, 32, 4, CU_TENSOR_MAP_SWIZZLE_128B);
  make_map(enc, &tmPG, P.wg, F_, D_, F_, 8, 32, 0, CU_TENSOR_MAP_SWIZZLE_NONE);
  make_map(enc, &tmPU, P.wu, F_, D_, F_, 8, 32, 0, CU_TENSOR_MAP_SWIZZLE_NONE);
  make_map(enc, &tmPD, P.wd, 128, F_ * 8, 128, 8, 32, 0, CU_TENSOR_MAP_SWIZZLE_NONE, CU_TENSOR_MAP_L2_PROMOTION_L2_256B);
  for (int m = 0; m < 2; m++) {
    cuuint64_t dims[4] = {64, m ? 64u : 16u, m ? 16u : 64u, 16}, str[3] = {2 * D_, (m ? 128u : 32u) * D_, 128};
    cuuint32_t box[4] = {64, 16, 4, 2}, es[4] = {1, 1, 1, 1};
    enc(m ? &tmM : &tmO, CU_TENSOR_MAP_DATA_TYPE_BFLOAT16, 4, const_cast<__nv_bfloat16*>(P.wo), dims, str, box, es, CU_TENSOR_MAP_INTERLEAVE_NONE,
        CU_TENSOR_MAP_SWIZZLE_128B, CU_TENSOR_MAP_L2_PROMOTION_L2_128B, CU_TENSOR_MAP_FLOAT_OOB_FILL_NONE);
  }
  cudaFuncSetAttribute(fused_kernel, cudaFuncAttributeMaxDynamicSharedMemorySize, SMEM_BYTES);
  fused_kernel<<<NCTA, 384, SMEM_BYTES>>>(tmX, tmW, tmO, tmG, tmU, tmD, tmM, tmPG, tmPU, tmPD, P);
}
```

```cpp
#include <cuda_runtime.h>
#include <cuda.h>
#include <cuda_bf16.h>
#include <stdint.h>
#include <type_traits>

namespace {

constexpr int S_ = 2048, D_ = 1024, F_ = 3584;
constexpr int NCTA = 128, NFFN = 112;
constexpr uint32_t SENT = 0xFFFFFFFFu;
constexpr int SPIN_LIMIT = 1 << 20;

#define ADELAY 900
#define NPK 0x233333333333ull
#define KDELAY 700
#define SBAR 2
#define NOOUT 0
#define OHOLD 72
#define OUTEF 0
#define CUTS 2
#define EFO 0
#define EFWO 0
#define TMPF 1
#define INIF 0
#define DEV 0xFFEE
#define FDT 100
#define ASTEP 300
#define BDELAY 1500
#define LATEP 0x20
#define GEV 0xDCCB
#define PDS 2
#define D1POS 1
#define GUPOS 1
#define ASYM 2
#define GUP 2
#define PEEL 1
#define B6E 2
#define D2I 5
#define T1 1
#define T4 1
#define QX 0
#define B6H 2
#define XWPF 1
#define PD0 2
#define PDT 60
#define KORD 0xBA9F87E6D54C3210ull
#define SDELAY 450
#define LDELAY 500
#define NOSPEC 0
#define LOCK 1
#define STLD 2
#define RELK 1
#define PERT 1
#define QHOLD 3
#define CDELAY 0
#define YDELAY 500
#define EFX 0
#define EFW 1
#define EFF 1
#define GDELAY 800
#define PFST 1
#define W0N 2
constexpr uint32_t STAGE_B = 57344;
__host__ __device__ constexpr uint32_t xoff(int s, int w) { return ((0x87CA3651u >> (4 * (s + 4 * w))) & 15) * 16384; }
__host__ __device__ constexpr uint32_t woff(int s) { return (s < 2 ? 9 * 16384 : 0) + (s & 1) * 8192; }
constexpr uint32_t WSTR = 32768;
constexpr uint32_t OFF_BARS = 229376;
constexpr uint32_t OFF_COLSUM = 229632;
constexpr uint32_t OFF_STATS = 230400;
constexpr uint32_t SMEM_BYTES = 232448;
constexpr uint32_t B_FULL = 0, B_EMPTY = 32, B_AUX = 64, B_SEL2 = 72, B_KVL = 80, B_FULL3 = 88, B_SW = 216, B_OUT = 224, B_LATE = 232, B_SEL = B_FULL + 8, B_FFN = 240;
__host__ __device__ constexpr uint32_t o3(int p) { return p * 8 + (p & 8) * 8; }
__host__ __device__ constexpr uint32_t bar3(int i) { return OFF_STATS + 1024 + (i >> 3) * 128 + ((i & 32) ? 0 : 64) + (i & 7) * 8; }
constexpr uint32_t SLOT_B = 16384;
constexpr uint32_t sb = 1024;
constexpr uint32_t bars = sb + OFF_BARS;
constexpr uint64_t WO_SLOTS = 0x8794208794208794ull;
constexpr uint32_t GU_SLOTS = 0x35356161u, D_SLOTS = 0x9420, DS0 = D_SLOTS & 15, DS1 = (D_SLOTS >> 8) & 15;
constexpr uint32_t HST = 7 * SLOT_B;
constexpr uint32_t OFF_LNP = OFF_STATS;
constexpr uint32_t OFF_MSC = OFF_COLSUM + 512;
constexpr uint32_t OFF_KVB = 2 * SLOT_B + 8192;

struct Scratch {
  uint4 st1[64 * 48];
  uint4 csp[16 * 8 * 48];
  uint4 kvp[16 * 2304];
  uint4 obuf[32 * 64 * 128];
  uint4 st2[S_];
  uint32_t pred[S_];
  uint4 cst[8 * 32];
  uint4 hsel[64 * 128];
  uint32_t cand[8 * 32];
  uint4 ybuf[NCTA * NFFN * 4];
  unsigned epoch;
};
__device__ __align__(1024) Scratch G;
#define TS_DECL
#define TS(i)
#define TSG(i)
#define TSV(i, v)
#define TS_DUMP(slot)
#define PTS(i)

__device__ __forceinline__ uint32_t smem_u32(const void* p) { return (uint32_t)__cvta_generic_to_shared(p); }
__device__ __forceinline__ void mbar_init(uint32_t bar, uint32_t cnt) { asm volatile("mbarrier.init.shared::cta.b64 [%0], %1;" :: "r"(bar), "r"(cnt) : "memory"); }
__device__ __forceinline__ void mbar_expect_tx(uint32_t bar, uint32_t bytes) { asm volatile("mbarrier.arrive.expect_tx.shared::cta.b64 _, [%0], %1;" :: "r"(bar), "r"(bytes) : "memory"); }
__device__ __forceinline__ void mbar_arrive(uint32_t bar) { asm volatile("mbarrier.arrive.shared::cta.b64 _, [%0];" :: "r"(bar) : "memory"); }
#define SPINCHK(it, code) if ((it) > SPIN_LIMIT) break
__device__ __forceinline__ void mbar_wait(uint32_t bar, uint32_t parity) {
  asm volatile("{\n.reg .pred p;\n.reg .u32 c;\nmov.u32 c, 0;\n"
               "WL:\nmbarrier.try_wait.parity.shared::cta.b64 p, [%0], %1;\n@p bra WD;\n"
               "add.u32 c, c, 1;\nsetp.lt.u32 p, c, 1048576;\n@p bra WL;\nWD:\n}" :: "r"(bar), "r"(parity) : "memory");
}
__device__ __forceinline__ uint64_t l2_stream() { uint64_t p; asm("createpolicy.fractional.L2::evict_first.b64 %0, 1.0;" : "=l"(p)); return p; }
__device__ __forceinline__ void tma_2d(uint32_t dst, const CUtensorMap* tm, int c0, int c1, uint32_t bar, bool stream) {
  if (stream) asm volatile("cp.async.bulk.tensor.2d.shared::cluster.global.mbarrier::complete_tx::bytes.L2::cache_hint [%0], [%1, {%3, %4}], [%2], %5;"
                           :: "r"(dst), "l"(tm), "r"(bar), "r"(c0), "r"(c1), "l"(l2_stream()) : "memory");
  else asm volatile("cp.async.bulk.tensor.2d.shared::cluster.global.mbarrier::complete_tx::bytes [%0], [%1, {%3, %4}], [%2];"
                    :: "r"(dst), "l"(tm), "r"(bar), "r"(c0), "r"(c1) : "memory");
}
__device__ __forceinline__ void tma_3d(uint32_t dst, const CUtensorMap* tm, int c0, int c1, int c2, uint32_t bar, bool stream) {
  if (stream) asm volatile("cp.async.bulk.tensor.3d.shared::cluster.global.mbarrier::complete_tx::bytes.L2::cache_hint [%0], [%1, {%3, %4, %5}], [%2], %6;"
                           :: "r"(dst), "l"(tm), "r"(bar), "r"(c0), "r"(c1), "r"(c2), "l"(l2_stream()) : "memory");
  else asm volatile("cp.async.bulk.tensor.3d.shared::cluster.global.mbarrier::complete_tx::bytes [%0], [%1, {%3, %4, %5}], [%2];"
                    :: "r"(dst), "l"(tm), "r"(bar), "r"(c0), "r"(c1), "r"(c2) : "memory");
}
__device__ __forceinline__ void tma_2d_mc(uint32_t dst, const CUtensorMap* tm, int c0, int c1, uint32_t bar, bool stream) {
  if (stream) asm volatile("cp.async.bulk.tensor.2d.shared::cluster.global.mbarrier::complete_tx::bytes.multicast::cluster.L2::cache_hint [%0], [%1, {%3, %4}], [%2], %5, %6;"
                           :: "r"(dst), "l"(tm), "r"(bar), "r"(c0), "r"(c1), "h"((uint16_t)3), "l"(l2_stream()) : "memory");
  else asm volatile("cp.async.bulk.tensor.2d.shared::cluster.global.mbarrier::complete_tx::bytes.multicast::cluster [%0], [%1, {%3, %4}], [%2], %5;"
                    :: "r"(dst), "l"(tm), "r"(bar), "r"(c0), "r"(c1), "h"((uint16_t)3) : "memory");
}
__device__ __forceinline__ bool elect_one() {
  uint32_t p;
  asm volatile("{\n.reg .pred q;\nelect.sync _|q, 0xFFFFFFFF;\nselp.u32 %0, 1, 0, q;\n}" : "=r"(p));
  return p;
}
__device__ __forceinline__ void bulk_load_mc(uint32_t dst, const void* src, uint32_t bar, uint16_t mask) {
  if (EFO) asm volatile("cp.async.bulk.shared::cluster.global.mbarrier::complete_tx::bytes.multicast::cluster.L2::cache_hint [%0], [%1], 8192, [%2], %3, %4;"
               :: "r"(dst), "l"(src), "r"(bar), "h"(mask), "l"(l2_stream()) : "memory");
  else asm volatile("cp.async.bulk.shared::cluster.global.mbarrier::complete_tx::bytes.multicast::cluster [%0], [%1], 8192, [%2], %3;"
               :: "r"(dst), "l"(src), "r"(bar), "h"(mask) : "memory");
}
__device__ __forceinline__ void bulk_load(uint32_t dst, const void* src, uint32_t bytes, uint32_t bar) {
  asm volatile("cp.async.bulk.shared::cluster.global.mbarrier::complete_tx::bytes [%0], [%1], %2, [%3];" :: "r"(dst), "l"(src), "r"(bytes), "r"(bar) : "memory");
}
__device__ __forceinline__ void mbar_arrive_rem(uint32_t bar) { asm volatile("mbarrier.arrive.shared::cluster.b64 _, [%0];" :: "r"(bar) : "memory"); }
template <uint32_t O> __device__ __forceinline__ void ldsm4_o(uint32_t addr, uint32_t& a, uint32_t& b, uint32_t& c, uint32_t& d) {
  asm volatile("ldmatrix.sync.aligned.m8n8.x4.shared.b16 {%0,%1,%2,%3}, [%4+%5];" : "=r"(a), "=r"(b), "=r"(c), "=r"(d) : "r"(addr), "n"(O) : "memory");
}
template <uint32_t O> __device__ __forceinline__ void ldsm4t_o(uint32_t addr, uint32_t (&r)[4]) {
  asm volatile("ldmatrix.sync.aligned.m8n8.x4.trans.shared.b16 {%0,%1,%2,%3}, [%4+%5];" : "=r"(r[0]), "=r"(r[1]), "=r"(r[2]), "=r"(r[3]) : "r"(addr), "n"(O) : "memory");
}
__device__ __forceinline__ void mma16816(float (&c)[4], const uint32_t (&a)[4], uint32_t b0, uint32_t b1) {
  asm("mma.sync.aligned.m16n8k16.row.col.f32.bf16.bf16.f32 {%0,%1,%2,%3}, {%4,%5,%6,%7}, {%8,%9}, {%0,%1,%2,%3};"
      : "+f"(c[0]), "+f"(c[1]), "+f"(c[2]), "+f"(c[3]) : "r"(a[0]), "r"(a[1]), "r"(a[2]), "r"(a[3]), "r"(b0), "r"(b1));
}
__device__ __forceinline__ void l2_prefetch(const void* p) { asm volatile("prefetch.global.L2 [%0];" :: "l"(p) : "memory"); }
__device__ __forceinline__ uint32_t clk() { uint32_t t; asm volatile("mov.u32 %0, %%clock;" : "=r"(t) :: "memory"); return t; }
__device__ __forceinline__ void delay(uint32_t t0, uint32_t n) { while (clk() - t0 < n) {} }
template <int ID> __device__ __forceinline__ void cut(uint32_t zero) { asm volatile("{\n.reg .pred p;\nsetp.eq.u32 p, %0, %1;\nCUT:\n@p nanosleep.u32 1;\n@p bra.uni CUT;\n}" :: "r"(zero), "n"(ID) : "memory"); }
__device__ __forceinline__ void tmap_prefetch(const CUtensorMap* tm) { asm volatile("prefetch.tensormap [%0];" :: "l"(tm) : "memory"); }
__device__ __forceinline__ void wg_fence() { asm volatile("wgmma.fence.sync.aligned;" ::: "memory"); }
__device__ __forceinline__ void wg_commit() { asm volatile("wgmma.commit_group.sync.aligned;" ::: "memory"); }
template <int N> __device__ __forceinline__ void wg_wait() { asm volatile("wgmma.wait_group.sync.aligned %0;" :: "n"(N) : "memory"); }
template <int N> __device__ __forceinline__ void pin(float (&d)[N]) {
#pragma unroll
  for (int i = 0; i < N; i++) asm volatile("" : "+f"(d[i]) :: "memory");
}
__device__ __forceinline__ void pin4(uint4& v) { asm volatile("" : "+r"(v.x), "+r"(v.y), "+r"(v.z), "+r"(v.w) :: "memory"); }
template <uint32_t SBO, uint32_t SWZ> __device__ __forceinline__ uint64_t dsc(uint32_t lo) { return ((uint64_t)((SBO >> 4) | (SWZ << 30)) << 32) | lo; }
__host__ __device__ constexpr uint32_t dlo(uint32_t addr, uint32_t lbo) { return (addr >> 4) | ((lbo >> 4) << 16); }
__device__ __forceinline__ void bar_sync(int id, int n) { asm volatile("bar.sync %0, %1;" :: "r"(id), "r"(n) : "memory"); }
__device__ __forceinline__ void bar_arrive(int id, int n) { asm volatile("bar.arrive %0, %1;" :: "r"(id), "r"(n) : "memory"); }
__device__ __forceinline__ void fence_async_smem() { asm volatile("fence.proxy.async.shared::cta;" ::: "memory"); }
__device__ __forceinline__ void fence_gpu() { asm volatile("fence.acq_rel.gpu;" ::: "memory"); }
__device__ __forceinline__ uint4 ld_cg4(const void* p) { uint4 v; asm volatile("ld.global.cg.v4.u32 {%0,%1,%2,%3}, [%4];" : "=r"(v.x), "=r"(v.y), "=r"(v.z), "=r"(v.w) : "l"(p) : "memory"); return v; }
__device__ __forceinline__ uint4 ld_rlx4(const void* p) { uint4 v; asm volatile("ld.relaxed.gpu.global.v4.u32 {%0,%1,%2,%3}, [%4];" : "=r"(v.x), "=r"(v.y), "=r"(v.z), "=r"(v.w) : "l"(p) : "memory"); return v; }
__device__ __forceinline__ uint32_t ld_rlx(const void* p) { uint32_t v; asm volatile("ld.relaxed.gpu.global.u32 %0, [%1];" : "=r"(v) : "l"(p) : "memory"); return v; }
__device__ __forceinline__ void st_rlx4(void* p, uint4 v) { asm volatile("st.relaxed.gpu.global.v4.u32 [%0], {%1,%2,%3,%4};" :: "l"(p), "r"(v.x), "r"(v.y), "r"(v.z), "r"(v.w) : "memory"); }
__device__ __forceinline__ void st_rlx2(void* p, uint32_t a, uint32_t b) { asm volatile("st.relaxed.gpu.global.v2.u32 [%0], {%1,%2};" :: "l"(p), "r"(a), "r"(b) : "memory"); }
__device__ __forceinline__ void st_rlx(void* p, uint32_t a) { asm volatile("st.relaxed.gpu.global.u32 [%0], %1;" :: "l"(p), "r"(a) : "memory"); }
__device__ __forceinline__ void red4(bool on, void* p, float a, float b, float c, float d) {
  asm volatile("{\n.reg .pred q;\nsetp.ne.b32 q, %5, 0;\n@q red.relaxed.gpu.global.add.v4.f32 [%0], {%1,%2,%3,%4};\n}" :: "l"(p), "f"(a), "f"(b), "f"(c), "f"(d), "r"((int)on) : "memory");
}
__device__ __forceinline__ uint32_t pack2(float lo, float hi) { uint32_t r; asm("cvt.rn.bf16x2.f32 %0, %1, %2;" : "=r"(r) : "f"(hi), "f"(lo)); return r; }
__device__ __forceinline__ float bf_lo(uint32_t v) { return __uint_as_float(v << 16); }
__device__ __forceinline__ float bf_hi(uint32_t v) { return __uint_as_float(v & 0xFFFF0000u); }
__device__ __forceinline__ void stsm4(uint32_t addr, uint32_t a, uint32_t b, uint32_t c, uint32_t d) {
  asm volatile("stmatrix.sync.aligned.m8n8.x4.shared.b16 [%0], {%1,%2,%3,%4};" :: "r"(addr), "r"(a), "r"(b), "r"(c), "r"(d) : "memory");
}
template <uint32_t O> __device__ __forceinline__ void stsm4_o(uint32_t addr, uint32_t a, uint32_t b, uint32_t c, uint32_t d) {
  asm volatile("stmatrix.sync.aligned.m8n8.x4.shared.b16 [%0+%5], {%1,%2,%3,%4};" :: "r"(addr), "r"(a), "r"(b), "r"(c), "r"(d), "n"(O) : "memory");
}
__device__ __forceinline__ void sts4(uint32_t addr, uint32_t a, uint32_t b, uint32_t c, uint32_t d) { asm volatile("st.shared.v4.u32 [%0], {%1,%2,%3,%4};" :: "r"(addr), "r"(a), "r"(b), "r"(c), "r"(d) : "memory"); }
__device__ __forceinline__ void sts2f(uint32_t addr, float a, float b) { asm volatile("st.shared.v2.f32 [%0], {%1,%2};" :: "r"(addr), "f"(a), "f"(b) : "memory"); }
__device__ __forceinline__ void sts1(uint32_t addr, uint32_t a) { asm volatile("st.shared.u32 [%0], %1;" :: "r"(addr), "r"(a) : "memory"); }
__device__ __forceinline__ float2 lds2f(uint32_t addr) { float2 v; asm volatile("ld.shared.v2.f32 {%0,%1}, [%2];" : "=f"(v.x), "=f"(v.y) : "r"(addr) : "memory"); return v; }
template <uint32_t O> __device__ __forceinline__ float2 lds2f_o(uint32_t addr) { float2 v; asm volatile("ld.shared.v2.f32 {%0,%1}, [%2+%3];" : "=f"(v.x), "=f"(v.y) : "r"(addr), "n"(O) : "memory"); return v; }
template <int I, int N, class F> __device__ __forceinline__ void static_for(F&& f) { if constexpr (I < N) { f(std::integral_constant<int, I>{}); static_for<I + 1, N>(f); } }
__device__ __forceinline__ uint4 lds4(uint32_t addr) { uint4 v; asm volatile("ld.shared.v4.u32 {%0,%1,%2,%3}, [%4];" : "=r"(v.x), "=r"(v.y), "=r"(v.z), "=r"(v.w) : "r"(addr) : "memory"); return v; }
__device__ __forceinline__ uint32_t lds1(uint32_t addr) { uint32_t v; asm volatile("ld.shared.u32 %0, [%1];" : "=r"(v) : "r"(addr) : "memory"); return v; }
__device__ __forceinline__ float ex2(float x) { float y; asm("ex2.approx.ftz.f32 %0, %1;" : "=f"(y) : "f"(x)); return y; }
__device__ __forceinline__ uint32_t max4(uint32_t m, const uint4& v) { return __vimax3_u32(__vimax3_u32(m, v.x, v.y), v.z, v.w); }
__device__ __forceinline__ float rsq(float x) { float y; asm("rsqrt.approx.ftz.f32 %0, %1;" : "=f"(y) : "f"(x)); return y; }
__device__ __forceinline__ float rcp(float x) { float y; asm("rcp.approx.ftz.f32 %0, %1;" : "=f"(y) : "f"(x)); return y; }
__device__ __forceinline__ uint2 ld_rlx2(const void* p) { uint2 v; asm volatile("ld.relaxed.gpu.global.v2.u32 {%0,%1}, [%2];" : "=r"(v.x), "=r"(v.y) : "l"(p) : "memory"); return v; }
template <uint32_t O> __device__ __forceinline__ uint4 lds4_o(uint32_t addr) { uint4 v; asm volatile("ld.shared.v4.u32 {%0,%1,%2,%3}, [%4+%5];" : "=r"(v.x), "=r"(v.y), "=r"(v.z), "=r"(v.w) : "r"(addr), "n"(O) : "memory"); return v; }
__device__ __forceinline__ uint32_t hadd2(uint32_t a, uint32_t b) { uint32_t r; asm("add.rn.bf16x2 %0, %1, %2;" : "=r"(r) : "r"(a), "r"(b)); return r; }
__device__ __forceinline__ uint4 hadd8(const uint4& a, const uint4& b) { return make_uint4(hadd2(a.x, b.x), hadd2(a.y, b.y), hadd2(a.z, b.z), hadd2(a.w, b.w)); }
__device__ __forceinline__ bool hnan(uint32_t a) { return (a & 0x7FFF0000u) > 0x7F800000u; }
__device__ __forceinline__ uint32_t hfma2(uint32_t a, uint32_t b, uint32_t c) { uint32_t r; asm("fma.rn.bf16x2 %0, %1, %2, %3;" : "=r"(r) : "r"(a), "r"(b), "r"(c)); return r; }
__device__ __forceinline__ uint32_t ordered(float v) { const uint32_t u = __float_as_uint(v); return u ^ ((uint32_t)((int)u >> 31) | 0x80000000u); }
__device__ __forceinline__ uint32_t route(const uint4& v, float sw, int row, float2& pr) {
  const float mean = __uint_as_float(v.x) * (1.f / D_);
  pr.x = rsq(fmaxf(fmaf(-mean, mean, __uint_as_float(v.y) * (1.f / D_)), 0.f) + 1e-5f);
  pr.y = -mean * pr.x;
  return min(ordered(pr.x * fmaf(-mean, sw, __uint_as_float(v.z))) & ~2047u, 0xFFFFF000u) | (2047 - row);
}
__device__ __forceinline__ uint2 top2(uint32_t a, uint32_t b, uint32_t c, uint32_t d) {
  const uint32_t h0 = max(a, b), h1 = max(c, d), h = max(h0, h1), l = __vimax3_u32(min(h0, h1), min(a, b), min(c, d));
  const uint32_t m1 = __reduce_max_sync(~0u, h);
  return make_uint2(m1, __reduce_max_sync(~0u, h == m1 ? l : h));
}
__device__ __forceinline__ uint32_t hmul2(uint32_t a, uint32_t b) { uint32_t r; asm("mul.rn.bf16x2 %0, %1, %2;" : "=r"(r) : "r"(a), "r"(b)); return r; }
__device__ __forceinline__ uint32_t phi2(float u0, float u1, uint32_t r2, float rl) {
  uint32_t p, r;
  asm("cvt.rn.relu.bf16x2.f32 %0, %1, %2;" : "=r"(p) : "f"(u1), "f"(u0));
  asm("fma.rn.bf16x2 %0, %1, %2, %3;" : "=r"(r) : "r"(p), "r"(r2), "r"(pack2(__saturatef(ex2(u0 * rl) + 1e-6f), __saturatef(ex2(u1 * rl) + 1e-6f))));
  return r;
}

template<int TA, int TB, int OFF, int SZ> __device__ __forceinline__ void wgmma_n192_ss(float (&d)[SZ], uint64_t da, uint64_t db, int scale_d) {
  asm volatile("{\n.reg .pred p;\nsetp.ne.b32 p, %98, 0;\n"
    "wgmma.mma_async.sync.aligned.m64n192k16.f32.bf16.bf16 {%0,%1,%2,%3,%4,%5,%6,%7,%8,%9,%10,%11,%12,%13,%14,%15,%16,%17,%18,%19,%20,%21,%22,%23,%24,%25,%26,%27,%28,%29,%30,%31,%32,%33,%34,%35,%36,%37,%38,%39,%40,%41,%42,%43,%44,%45,%46,%47,%48,%49,%50,%51,%52,%53,%54,%55,%56,%57,%58,%59,%60,%61,%62,%63,%64,%65,%66,%67,%68,%69,%70,%71,%72,%73,%74,%75,%76,%77,%78,%79,%80,%81,%82,%83,%84,%85,%86,%87,%88,%89,%90,%91,%92,%93,%94,%95}, %96, %97, p, 1, 1, %99, %100;\n}\n"
    : "+f"(d[OFF+0]), "+f"(d[OFF+1]), "+f"(d[OFF+2]), "+f"(d[OFF+3]), "+f"(d[OFF+4]), "+f"(d[OFF+5]), "+f"(d[OFF+6]), "+f"(d[OFF+7]),
      "+f"(d[OFF+8]), "+f"(d[OFF+9]), "+f"(d[OFF+10]), "+f"(d[OFF+11]), "+f"(d[OFF+12]), "+f"(d[OFF+13]), "+f"(d[OFF+14]), "+f"(d[OFF+15]),
      "+f"(d[OFF+16]), "+f"(d[OFF+17]), "+f"(d[OFF+18]), "+f"(d[OFF+19]), "+f"(d[OFF+20]), "+f"(d[OFF+21]), "+f"(d[OFF+22]), "+f"(d[OFF+23]),
      "+f"(d[OFF+24]), "+f"(d[OFF+25]), "+f"(d[OFF+26]), "+f"(d[OFF+27]), "+f"(d[OFF+28]), "+f"(d[OFF+29]), "+f"(d[OFF+30]), "+f"(d[OFF+31]),
      "+f"(d[OFF+32]), "+f"(d[OFF+33]), "+f"(d[OFF+34]), "+f"(d[OFF+35]), "+f"(d[OFF+36]), "+f"(d[OFF+37]), "+f"(d[OFF+38]), "+f"(d[OFF+39]),
      "+f"(d[OFF+40]), "+f"(d[OFF+41]), "+f"(d[OFF+42]), "+f"(d[OFF+43]), "+f"(d[OFF+44]), "+f"(d[OFF+45]), "+f"(d[OFF+46]), "+f"(d[OFF+47]),
      "+f"(d[OFF+48]), "+f"(d[OFF+49]), "+f"(d[OFF+50]), "+f"(d[OFF+51]), "+f"(d[OFF+52]), "+f"(d[OFF+53]), "+f"(d[OFF+54]), "+f"(d[OFF+55]),
      "+f"(d[OFF+56]), "+f"(d[OFF+57]), "+f"(d[OFF+58]), "+f"(d[OFF+59]), "+f"(d[OFF+60]), "+f"(d[OFF+61]), "+f"(d[OFF+62]), "+f"(d[OFF+63]),
      "+f"(d[OFF+64]), "+f"(d[OFF+65]), "+f"(d[OFF+66]), "+f"(d[OFF+67]), "+f"(d[OFF+68]), "+f"(d[OFF+69]), "+f"(d[OFF+70]), "+f"(d[OFF+71]),
      "+f"(d[OFF+72]), "+f"(d[OFF+73]), "+f"(d[OFF+74]), "+f"(d[OFF+75]), "+f"(d[OFF+76]), "+f"(d[OFF+77]), "+f"(d[OFF+78]), "+f"(d[OFF+79]),
      "+f"(d[OFF+80]), "+f"(d[OFF+81]), "+f"(d[OFF+82]), "+f"(d[OFF+83]), "+f"(d[OFF+84]), "+f"(d[OFF+85]), "+f"(d[OFF+86]), "+f"(d[OFF+87]),
      "+f"(d[OFF+88]), "+f"(d[OFF+89]), "+f"(d[OFF+90]), "+f"(d[OFF+91]), "+f"(d[OFF+92]), "+f"(d[OFF+93]), "+f"(d[OFF+94]), "+f"(d[OFF+95])
    : "l"(da), "l"(db), "r"(scale_d), "n"(TA), "n"(TB));
}
template<int TA, int TB, int OFF, int SZ> __device__ __forceinline__ void wgmma_n128_ss(float (&d)[SZ], uint64_t da, uint64_t db, int scale_d) {
  asm volatile("{\n.reg .pred p;\nsetp.ne.b32 p, %66, 0;\n"
    "wgmma.mma_async.sync.aligned.m64n128k16.f32.bf16.bf16 {%0,%1,%2,%3,%4,%5,%6,%7,%8,%9,%10,%11,%12,%13,%14,%15,%16,%17,%18,%19,%20,%21,%22,%23,%24,%25,%26,%27,%28,%29,%30,%31,%32,%33,%34,%35,%36,%37,%38,%39,%40,%41,%42,%43,%44,%45,%46,%47,%48,%49,%50,%51,%52,%53,%54,%55,%56,%57,%58,%59,%60,%61,%62,%63}, %64, %65, p, 1, 1, %67, %68;\n}\n"
    : "+f"(d[OFF+0]), "+f"(d[OFF+1]), "+f"(d[OFF+2]), "+f"(d[OFF+3]), "+f"(d[OFF+4]), "+f"(d[OFF+5]), "+f"(d[OFF+6]), "+f"(d[OFF+7]),
      "+f"(d[OFF+8]), "+f"(d[OFF+9]), "+f"(d[OFF+10]), "+f"(d[OFF+11]), "+f"(d[OFF+12]), "+f"(d[OFF+13]), "+f"(d[OFF+14]), "+f"(d[OFF+15]),
      "+f"(d[OFF+16]), "+f"(d[OFF+17]), "+f"(d[OFF+18]), "+f"(d[OFF+19]), "+f"(d[OFF+20]), "+f"(d[OFF+21]), "+f"(d[OFF+22]), "+f"(d[OFF+23]),
      "+f"(d[OFF+24]), "+f"(d[OFF+25]), "+f"(d[OFF+26]), "+f"(d[OFF+27]), "+f"(d[OFF+28]), "+f"(d[OFF+29]), "+f"(d[OFF+30]), "+f"(d[OFF+31]),
      "+f"(d[OFF+32]), "+f"(d[OFF+33]), "+f"(d[OFF+34]), "+f"(d[OFF+35]), "+f"(d[OFF+36]), "+f"(d[OFF+37]), "+f"(d[OFF+38]), "+f"(d[OFF+39]),
      "+f"(d[OFF+40]), "+f"(d[OFF+41]), "+f"(d[OFF+42]), "+f"(d[OFF+43]), "+f"(d[OFF+44]), "+f"(d[OFF+45]), "+f"(d[OFF+46]), "+f"(d[OFF+47]),
      "+f"(d[OFF+48]), "+f"(d[OFF+49]), "+f"(d[OFF+50]), "+f"(d[OFF+51]), "+f"(d[OFF+52]), "+f"(d[OFF+53]), "+f"(d[OFF+54]), "+f"(d[OFF+55]),
      "+f"(d[OFF+56]), "+f"(d[OFF+57]), "+f"(d[OFF+58]), "+f"(d[OFF+59]), "+f"(d[OFF+60]), "+f"(d[OFF+61]), "+f"(d[OFF+62]), "+f"(d[OFF+63])
    : "l"(da), "l"(db), "r"(scale_d), "n"(TA), "n"(TB));
}
template<int TA, int TB, int OFF, int SZ> __device__ __forceinline__ void wgmma_n64_ss(float (&d)[SZ], uint64_t da, uint64_t db, int scale_d) {
  asm volatile("{\n.reg .pred p;\nsetp.ne.b32 p, %34, 0;\n"
    "wgmma.mma_async.sync.aligned.m64n64k16.f32.bf16.bf16 {%0,%1,%2,%3,%4,%5,%6,%7,%8,%9,%10,%11,%12,%13,%14,%15,%16,%17,%18,%19,%20,%21,%22,%23,%24,%25,%26,%27,%28,%29,%30,%31}, %32, %33, p, 1, 1, %35, %36;\n}\n"
    : "+f"(d[OFF+0]), "+f"(d[OFF+1]), "+f"(d[OFF+2]), "+f"(d[OFF+3]), "+f"(d[OFF+4]), "+f"(d[OFF+5]), "+f"(d[OFF+6]), "+f"(d[OFF+7]),
      "+f"(d[OFF+8]), "+f"(d[OFF+9]), "+f"(d[OFF+10]), "+f"(d[OFF+11]), "+f"(d[OFF+12]), "+f"(d[OFF+13]), "+f"(d[OFF+14]), "+f"(d[OFF+15]),
      "+f"(d[OFF+16]), "+f"(d[OFF+17]), "+f"(d[OFF+18]), "+f"(d[OFF+19]), "+f"(d[OFF+20]), "+f"(d[OFF+21]), "+f"(d[OFF+22]), "+f"(d[OFF+23]),
      "+f"(d[OFF+24]), "+f"(d[OFF+25]), "+f"(d[OFF+26]), "+f"(d[OFF+27]), "+f"(d[OFF+28]), "+f"(d[OFF+29]), "+f"(d[OFF+30]), "+f"(d[OFF+31])
    : "l"(da), "l"(db), "r"(scale_d), "n"(TA), "n"(TB));
}
template<int TB, int OFF, int SZ> __device__ __forceinline__ void wgmma_n64_rs(float (&d)[SZ], uint32_t a0, uint32_t a1, uint32_t a2, uint32_t a3, uint64_t db, int scale_d) {
  asm volatile("{\n.reg .pred p;\nsetp.ne.b32 p, %37, 0;\n"
    "wgmma.mma_async.sync.aligned.m64n64k16.f32.bf16.bf16 {%0,%1,%2,%3,%4,%5,%6,%7,%8,%9,%10,%11,%12,%13,%14,%15,%16,%17,%18,%19,%20,%21,%22,%23,%24,%25,%26,%27,%28,%29,%30,%31}, {%32,%33,%34,%35}, %36, p, 1, 1, %38;\n}\n"
    : "+f"(d[OFF+0]), "+f"(d[OFF+1]), "+f"(d[OFF+2]), "+f"(d[OFF+3]), "+f"(d[OFF+4]), "+f"(d[OFF+5]), "+f"(d[OFF+6]), "+f"(d[OFF+7]),
      "+f"(d[OFF+8]), "+f"(d[OFF+9]), "+f"(d[OFF+10]), "+f"(d[OFF+11]), "+f"(d[OFF+12]), "+f"(d[OFF+13]), "+f"(d[OFF+14]), "+f"(d[OFF+15]),
      "+f"(d[OFF+16]), "+f"(d[OFF+17]), "+f"(d[OFF+18]), "+f"(d[OFF+19]), "+f"(d[OFF+20]), "+f"(d[OFF+21]), "+f"(d[OFF+22]), "+f"(d[OFF+23]),
      "+f"(d[OFF+24]), "+f"(d[OFF+25]), "+f"(d[OFF+26]), "+f"(d[OFF+27]), "+f"(d[OFF+28]), "+f"(d[OFF+29]), "+f"(d[OFF+30]), "+f"(d[OFF+31])
    : "r"(a0), "r"(a1), "r"(a2), "r"(a3), "l"(db), "r"(scale_d), "n"(TB));
}
template<int TA, int TB, int OFF, int SZ> __device__ __forceinline__ void wgmma_n72_ss(float (&d)[SZ], uint64_t da, uint64_t db, int scale_d) {
  asm volatile("{\n.reg .pred p;\nsetp.ne.b32 p, %38, 0;\n"
    "wgmma.mma_async.sync.aligned.m64n72k16.f32.bf16.bf16 {%0,%1,%2,%3,%4,%5,%6,%7,%8,%9,%10,%11,%12,%13,%14,%15,%16,%17,%18,%19,%20,%21,%22,%23,%24,%25,%26,%27,%28,%29,%30,%31,%32,%33,%34,%35}, %36, %37, p, 1, 1, %39, %40;\n}\n"
    : "+f"(d[OFF+0]), "+f"(d[OFF+1]), "+f"(d[OFF+2]), "+f"(d[OFF+3]), "+f"(d[OFF+4]), "+f"(d[OFF+5]), "+f"(d[OFF+6]), "+f"(d[OFF+7]),
      "+f"(d[OFF+8]), "+f"(d[OFF+9]), "+f"(d[OFF+10]), "+f"(d[OFF+11]), "+f"(d[OFF+12]), "+f"(d[OFF+13]), "+f"(d[OFF+14]), "+f"(d[OFF+15]),
      "+f"(d[OFF+16]), "+f"(d[OFF+17]), "+f"(d[OFF+18]), "+f"(d[OFF+19]), "+f"(d[OFF+20]), "+f"(d[OFF+21]), "+f"(d[OFF+22]), "+f"(d[OFF+23]),
      "+f"(d[OFF+24]), "+f"(d[OFF+25]), "+f"(d[OFF+26]), "+f"(d[OFF+27]), "+f"(d[OFF+28]), "+f"(d[OFF+29]), "+f"(d[OFF+30]), "+f"(d[OFF+31]),
      "+f"(d[OFF+32]), "+f"(d[OFF+33]), "+f"(d[OFF+34]), "+f"(d[OFF+35])
    : "l"(da), "l"(db), "r"(scale_d), "n"(TA), "n"(TB));
}
template<int TB, int OFF, int SZ> __device__ __forceinline__ void wgmma_n40_rs(float (&d)[SZ], uint32_t a0, uint32_t a1, uint32_t a2, uint32_t a3, uint64_t db, int scale_d) {
  asm volatile("{\n.reg .pred p;\nsetp.ne.b32 p, %25, 0;\n"
    "wgmma.mma_async.sync.aligned.m64n40k16.f32.bf16.bf16 {%0,%1,%2,%3,%4,%5,%6,%7,%8,%9,%10,%11,%12,%13,%14,%15,%16,%17,%18,%19}, {%20,%21,%22,%23}, %24, p, 1, 1, %26;\n}\n"
    : "+f"(d[OFF+0]), "+f"(d[OFF+1]), "+f"(d[OFF+2]), "+f"(d[OFF+3]), "+f"(d[OFF+4]), "+f"(d[OFF+5]), "+f"(d[OFF+6]), "+f"(d[OFF+7]),
      "+f"(d[OFF+8]), "+f"(d[OFF+9]), "+f"(d[OFF+10]), "+f"(d[OFF+11]), "+f"(d[OFF+12]), "+f"(d[OFF+13]), "+f"(d[OFF+14]), "+f"(d[OFF+15]),
      "+f"(d[OFF+16]), "+f"(d[OFF+17]), "+f"(d[OFF+18]), "+f"(d[OFF+19])
    : "r"(a0), "r"(a1), "r"(a2), "r"(a3), "l"(db), "r"(scale_d), "n"(TB));
}
template<int TB, int OFF, int SZ> __device__ __forceinline__ void wgmma_n128_rs(float (&d)[SZ], uint32_t a0, uint32_t a1, uint32_t a2, uint32_t a3, uint64_t db, int scale_d) {
  asm volatile("{\n.reg .pred p;\nsetp.ne.b32 p, %69, 0;\n"
    "wgmma.mma_async.sync.aligned.m64n128k16.f32.bf16.bf16 {%0,%1,%2,%3,%4,%5,%6,%7,%8,%9,%10,%11,%12,%13,%14,%15,%16,%17,%18,%19,%20,%21,%22,%23,%24,%25,%26,%27,%28,%29,%30,%31,%32,%33,%34,%35,%36,%37,%38,%39,%40,%41,%42,%43,%44,%45,%46,%47,%48,%49,%50,%51,%52,%53,%54,%55,%56,%57,%58,%59,%60,%61,%62,%63}, {%64,%65,%66,%67}, %68, p, 1, 1, %70;\n}\n"
    : "+f"(d[OFF+0]), "+f"(d[OFF+1]), "+f"(d[OFF+2]), "+f"(d[OFF+3]), "+f"(d[OFF+4]), "+f"(d[OFF+5]), "+f"(d[OFF+6]), "+f"(d[OFF+7]),
      "+f"(d[OFF+8]), "+f"(d[OFF+9]), "+f"(d[OFF+10]), "+f"(d[OFF+11]), "+f"(d[OFF+12]), "+f"(d[OFF+13]), "+f"(d[OFF+14]), "+f"(d[OFF+15]),
      "+f"(d[OFF+16]), "+f"(d[OFF+17]), "+f"(d[OFF+18]), "+f"(d[OFF+19]), "+f"(d[OFF+20]), "+f"(d[OFF+21]), "+f"(d[OFF+22]), "+f"(d[OFF+23]),
      "+f"(d[OFF+24]), "+f"(d[OFF+25]), "+f"(d[OFF+26]), "+f"(d[OFF+27]), "+f"(d[OFF+28]), "+f"(d[OFF+29]), "+f"(d[OFF+30]), "+f"(d[OFF+31]),
      "+f"(d[OFF+32]), "+f"(d[OFF+33]), "+f"(d[OFF+34]), "+f"(d[OFF+35]), "+f"(d[OFF+36]), "+f"(d[OFF+37]), "+f"(d[OFF+38]), "+f"(d[OFF+39]),
      "+f"(d[OFF+40]), "+f"(d[OFF+41]), "+f"(d[OFF+42]), "+f"(d[OFF+43]), "+f"(d[OFF+44]), "+f"(d[OFF+45]), "+f"(d[OFF+46]), "+f"(d[OFF+47]),
      "+f"(d[OFF+48]), "+f"(d[OFF+49]), "+f"(d[OFF+50]), "+f"(d[OFF+51]), "+f"(d[OFF+52]), "+f"(d[OFF+53]), "+f"(d[OFF+54]), "+f"(d[OFF+55]),
      "+f"(d[OFF+56]), "+f"(d[OFF+57]), "+f"(d[OFF+58]), "+f"(d[OFF+59]), "+f"(d[OFF+60]), "+f"(d[OFF+61]), "+f"(d[OFF+62]), "+f"(d[OFF+63])
    : "r"(a0), "r"(a1), "r"(a2), "r"(a3), "l"(db), "r"(scale_d), "n"(TB));
}

struct Ptrs { const __nv_bfloat16 *x, *wqkv, *wo, *wr, *wg, *wu, *wd; __nv_bfloat16* out; };

__global__ void __cluster_dims__(2, 1, 1) __launch_bounds__(384, 1) fused_kernel(const Ptrs P, const __grid_constant__ CUtensorMap tmX, const __grid_constant__ CUtensorMap tmW,
                                                       const __grid_constant__ CUtensorMap tmO, const __grid_constant__ CUtensorMap tmG,
                                                       const __grid_constant__ CUtensorMap tmU, const __grid_constant__ CUtensorMap tmD,
                                                       const __grid_constant__ CUtensorMap tmM, const __grid_constant__ CUtensorMap tmPG,
                                                       const __grid_constant__ CUtensorMap tmPU, const __grid_constant__ CUtensorMap tmPD) {
  extern __shared__ __align__(1024) uint8_t smem_raw[];
  if (TMPF && threadIdx.x == 0) { tmap_prefetch(&tmX); tmap_prefetch(&tmW); }
  const int tid = threadIdx.x, wid = __shfl_sync(~0u, tid >> 5, 0), wg = __shfl_sync(~0u, tid >> 7, 0), lane = tid & 31;
  const int pj = blockIdx.x >> 1, pi = pj - 36;
  const int b = (pj < 4 ? 32 + pj * 8 : pj < 36 ? pj - 4 : 33 + pi + ((pi * 37) >> 8)) * 2 + (blockIdx.x & 1);
  const int rb = b >> 4, cg = b & 15, hf = cg >> 3, c3 = cg & 7;
  const int jp = cg >> 1;
  const int fidx = jp == rb ? -1 : b - 2 * rb - (jp > rb ? 2 : 0);
  const uint32_t rank = b & 1, own = rank << 24;
  const uint32_t zero = gridDim.y - 1;
  const uint32_t sm = own + sb, mb = own + bars;
  auto chunk_of = [&](int p) { return (int)((0x1765432FEDCBA980ull >> (4 * p)) & 15) ^ (p == 0 || p == 15 ? cg : p < 9 ? cg & 8 : cg & 14); };
  const int kl = (jp & 3) * 256;
  auto k_of = [&](int kb) { return kb >= 12 ? kl + (kb - 12) * 64 : kb * 64 < kl ? kb * 64 : kb * 64 + 256; };
  auto load_w = [&](int kb) {
#pragma unroll
    for (int i = 0; i < 3; i++) tma_2d(sm + woff(kb & 3) + i * WSTR, &tmW, i * D_ + cg * 64, k_of(kb), mb + B_FULL + 8 * (kb & 3), EFW);
  };
  if (XWPF && tid >= 32 && tid < 128) {
    const int k0 = kl ? 0 : 256;
    if (tid < 56) l2_prefetch(P.wqkv + (k0 + rb * 8 + (lane & 7)) * 3072 + (lane >> 3) * 1024 + cg * 64);
    else if (tid >= 64 && (!kl || tid < 86)) l2_prefetch(P.x + (rb * 256 + (kl ? min((cg - 2 - 2 * hf) * 22 + lane, 255) : (hf * 2 + rank) * 64 + tid - 64)) * D_ + k0);
  }
  TS_DECL; TS(0); TSG(30);
  if (wid == 8) {
    if (elect_one()) {
      if (smem_u32(smem_raw) != sm) {
#pragma unroll
        for (int i = 0; i < PERT; i++) sts1(mb, lds1(mb));
        asm volatile("trap;");
      }
#pragma unroll
      for (int s = 0; s < 4; s++) mbar_init(mb + B_FULL + 8 * s, 1);
      asm volatile("fence.mbarrier_init.release.cluster;" ::: "memory");
      if (INIF) fence_async_smem();
    }
  } else if (wid == 9) {
    if (elect_one()) {
#pragma unroll
      for (int i = 4; i < 32; i++)
        if (i != 27) mbar_init(mb + 8 * i, i < 8 ? 8 : i == 8 ? 64 : i == 26 ? 2 : i == 29 ? 4 : 1);
      asm volatile("fence.mbarrier_init.release.cluster;" ::: "memory");
      if (INIF) fence_async_smem();
    }
  }
  __syncwarp();
  asm volatile("barrier.cluster.arrive.relaxed.aligned;" ::: "memory");
  if (wid == 8) {
    if (elect_one()) {
      mbar_expect_tx(mb + B_FULL, STAGE_B);
      tma_2d(sm + xoff(0, 0), &tmX, k_of(0), rb * 256, mb + B_FULL, EFX);
      tma_2d(sm + xoff(0, 1), &tmX, k_of(0), rb * 256 + 128, mb + B_FULL, EFX);
      load_w(0);
    }
    __syncwarp();
  }
  asm volatile("barrier.cluster.wait.aligned;" ::: "memory");

  if (wg == 2) {
    asm volatile("setmaxnreg.dec.sync.aligned.u32 56;");
    auto wait3 = [&](int i) { mbar_wait(sm + bar3(i), 0); };
    if (wid == 8) {
      if (elect_one()) {
        int np = fidx >= 0 ? 0 : 32;
        if (fidx >= 0) mbar_expect_tx(mb + B_FFN, 32 * 512);
#pragma unroll 1
        for (int kb = 1; kb < 16 - PEEL; kb++) {
          const uint32_t fb = mb + B_FULL + 8 * (kb & 3);
          mbar_wait(fb + B_EMPTY, ((kb >> 2) & 1) ^ 1);
          mbar_expect_tx(fb, STAGE_B);
          tma_2d_mc(sm + xoff(kb & 3, rank), &tmX, k_of(kb), rb * 256 + rank * 128, fb, EFX);
          load_w(kb);
          if (kb >= 12) asm volatile("mbarrier.arrive.shared::cta.b64 _, [%0], 7;" :: "r"(fb + B_EMPTY) : "memory");
#pragma unroll 1
          for (int n = ((NPK << 16) >> (4 * kb)) & 15; n > 0 && np < 32; n--, np++)
            tma_2d(sm + OFF_STATS + 512, (np & 1) ? &tmPU : &tmPG, (fidx >> 1) * 64, (np >> 1) * 64 + rank * 32, mb + B_FFN, false);
        }
        if (PEEL) {
          mbar_wait(mb + B_EMPTY + 24, 0);
          tma_2d_mc(sm + xoff(3, rank), &tmX, kl + 192, rb * 256 + rank * 128, mb + B_FULL + 24, EFX);
          load_w(15);
          mbar_expect_tx(mb + B_FULL + 24, STAGE_B);
        }
        if (fidx >= 0) { mbar_wait(mb + B_FFN, 0); mbar_expect_tx(mb + B_FFN, 65536 + 8 * 512); mbar_expect_tx(mb + B_FFN + 8, 65536); }
#pragma unroll
        for (int p = 4; p < 8; p++) sts4(sm + OFF_STATS + p * 144, 0x3F803F80u, 0x3F803F80u, 0x3F803F80u, 0x3F803F80u);
        fence_async_smem();
        mbar_arrive(mb + B_LATE);
        PTS(2);
        mbar_expect_tx(mb + B_KVL, 36864);
        mbar_wait(mb + B_LATE, 0);
        wait3(60);
        delay(clk(), KDELAY);
        bulk_load(sm + 11 * SLOT_B, &G.kvp[cg * 2304], SLOT_B, mb + B_KVL);
        bulk_load(sm + 13 * SLOT_B, &G.kvp[cg * 2304 + 1024], SLOT_B, mb + B_KVL);
        bulk_load(sm + 2 * SLOT_B, &G.kvp[cg * 2304 + 2048], 4096, mb + B_KVL);
        PTS(3);
        const uint4* src = &G.obuf[(rb * 4 + rank * 2 + hf) * 64 * 128];
        wait3(48);
        const uint32_t t1 = clk();
#pragma unroll
        for (int p = 1; p < 5; p++) {
          delay(t1, ADELAY + (p - 1) * ASTEP);
          bulk_load_mc(sm + (10 + (p & 3)) * SLOT_B + rank * 8192, src + ((hf ^ 1) * 8 + p - 1) * 512, sm + bar3(p) + rank * 256, 3);
        }
        PTS(7);
#pragma unroll 1
        for (int i = 5; i < 17; i++) {
          const int p = min(i, 15);
          const uint32_t d = sm + (10 + (p & 3)) * SLOT_B + rank * 8192, fb = sm + bar3(0) + o3(p) + rank * 256;
          const uint4* q = src + chunk_of(i & 15) * 512;
          mbar_wait(sm + bar3(48) + o3(p - 4 + ((LATEP >> p) & 1)), 0);
          bulk_load_mc(d, q, fb, i < 15 ? 3 : 1 << ((i ^ rank ^ 1) & 1));
        }
        PTS(15);
      }
    } else {
      const int r4 = lane >> 3, c8 = lane & 7;
      const uint32_t eb = (lane << 24) + bars + B_EMPTY;
      auto tagged = [](float v, uint32_t tag) { return ((__float_as_uint(v) + 128) & ~255u) | tag; };
      auto gather = [&](uint32_t tag) {
        const int q = (wid - 9) * 24 + lane;
        const uint4* cp = lane < 24 ? &G.csp[cg * 8 * 48 + q] : &G.st1[rb * 8 * 48 + (wid - 9) * 8 + lane - 24];
        uint4 v[8];
        delay(clk(), GDELAY);
#pragma unroll 1
        for (int it = 0;; it++) {
#pragma unroll
          for (int i = 0; i < 8; i++) v[i] = ld_rlx4(cp + i * 48);
          uint32_t x = 0;
#pragma unroll
          for (int i = 0; i < 8; i++) { v[i].x ^= tag; v[i].y ^= tag; v[i].z ^= tag; v[i].w ^= tag; x |= v[i].x | v[i].y | v[i].z | v[i].w; }
          if (!__any_sync(~0u, (x & 255) != 0)) break;
          SPINCHK(it, 3);
        }
        float c[4] = {0.f, 0.f, 0.f, 0.f};
#pragma unroll
        for (int i = 0; i < 8; i++) { c[0] += __uint_as_float(v[i].x); c[1] += __uint_as_float(v[i].y); c[2] += __uint_as_float(v[i].z); c[3] += __uint_as_float(v[i].w); }
        const uint32_t h0 = pack2(c[0], c[1]), h1 = pack2(c[2], c[3]), ca = sm + OFF_COLSUM + (q >> 1) * 32 + (q & 1) * 8;
        if (lane < 24) {
          sts2f(ca, __uint_as_float(h0), __uint_as_float(h1));
          sts2f(ca + 16, __uint_as_float(pack2(c[0] - bf_lo(h0), c[1] - bf_hi(h0))), __uint_as_float(pack2(c[2] - bf_lo(h1), c[3] - bf_hi(h1))));
        }
        fence_async_smem();
        mbar_arrive(mb + B_AUX);
      };
      const int r2 = lane >> 4, c16 = lane & 15;
      float a[12];
#pragma unroll
      for (int i = 0; i < 12; i++) a[i] = 0.f;
      auto kb_of = [](int it) { return (int)(KORD >> (4 * it)) & 15; };
      if (wid == 9) {
        const uint32_t a0 = sm + rb * 1024 + r2 * 128 + (((c16 >> 1) ^ r2) << 4) + (c16 & 1) * 8;
        const uint2* gw = (const uint2*)(P.wqkv + (kl + rb * 8 + r2) * 3072 + cg * 64) + c16;
#pragma unroll 1
        for (int it = 0; it < 16; it++) {
          uint2 w[12];
          const int kb = kb_of(it);
          if (kb >= 12) {
#pragma unroll
            for (int j = 0; j < 12; j++) w[j] = ld_rlx2(gw + (j >> 2) * 256 + (j & 3) * 1536);
            gw += 64 * 768;
          } else {
            const uint32_t so = a0 + woff(kb & 3);
            mbar_wait(mb + B_FULL + 8 * (kb & 3), (kb >> 2) & 1);
            static_for<0, 12>([&](auto ic) { constexpr int i = decltype(ic)::value;
              const float2 v = lds2f_o<(i >> 2) * WSTR + (i & 3) * 256>(so ^ ((i & 3) << 5)); w[i] = make_uint2(__float_as_uint(v.x), __float_as_uint(v.y)); });
            uint32_t done = 0;
#pragma unroll
            for (int i = 0; i < 12; i++) done |= w[i].y;
            if (lane < 2) mbar_arrive_rem(eb + 8 * (kb & 3) + (done & zero));
          }
#pragma unroll
          for (int i = 0; i < 12; i++) { float* q = a + (i >> 2) * 4; q[0] += bf_lo(w[i].x); q[1] += bf_hi(w[i].x); q[2] += bf_lo(w[i].y); q[3] += bf_hi(w[i].y); }
        }
        if (lane == 0) PTS(8);
        float c[6];
#pragma unroll
        for (int i = 0; i < 6; i++) {
          const int o = (i >> 1) * 4 + (i & 1);
          c[i] = (r2 ? a[o + 2] : a[o]) + __shfl_xor_sync(~0u, r2 ? a[o] : a[o + 2], 16);
        }
        bar_sync(5, 96);
        if (lane == 0) PTS(5);
        const uint32_t tag = lds1(mb + B_SW + 4) & 255;
#pragma unroll
        for (int sg = 0; sg < 3; sg++) st_rlx2((uint2*)&G.csp[(cg * 8 + rb) * 48] + sg * 32 + c16 * 2 + r2, tagged(c[sg * 2], tag), tagged(c[sg * 2 + 1], tag));
      } else {
       if (wid == 10) {
        if (lane < 24 && (lane & 28) != 4) sts4(sm + OFF_STATS + (lane < 16 ? lane * 128 + c8 * 16 : c8 * 16), 0x3F803F80u, 0x3F803F80u, 0x3F803F80u, 0x3F803F80u);
       } else {
        mbar_wait(mb + B_FULL + 8 * PFST, 0);
        const uint32_t ep = ld_rlx(&G.epoch);
        uint4 v[4];
#pragma unroll
        for (int i = 0; i < 4; i++) v[i] = ld_cg4((const uint4*)P.wr + lane + i * 32);
        if (elect_one()) { tmap_prefetch(&tmO); tmap_prefetch(&tmG); tmap_prefetch(&tmU); tmap_prefetch(&tmD); tmap_prefetch(&tmPD); tmap_prefetch(&tmM); }
        __syncwarp();
        const uint4 sv = make_uint4(SENT, SENT, SENT, SENT);
#pragma unroll 1
        for (int i = 0; i < 9; i++) {
          uint4* q = i < 8 ? &G.obuf[((rb * 4 + (i >> 1)) * 64 + cg * 4) * 128 + (i & 1) * 256 + lane] : &G.kvp[cg * 2304 + rb * 288 + lane];
#pragma unroll
          for (int j = 0; j < 8; j++) q[j * 32] = sv;
          if (i == 8) q[256] = sv;
          else if (lane < ((i & 1) ? 24 : 16)) l2_prefetch((i & 1) ? P.wqkv + (kl + (i >> 1) * 64 + rb * 8 + c8) * 3072 + r4 * 1024 + cg * 64 : P.x + (b * 16 + lane) * D_ + kl + i * 32);
        }
        float s = 0.f;
#pragma unroll 1
        for (int i = 0; i < 4; i++) {
          s += (bf_lo(v[0].x) + bf_hi(v[0].x)) + (bf_lo(v[0].y) + bf_hi(v[0].y)) + (bf_lo(v[0].z) + bf_hi(v[0].z)) + (bf_lo(v[0].w) + bf_hi(v[0].w));
          v[0] = v[1]; v[1] = v[2]; v[2] = v[3];
        }
#pragma unroll
        for (int o = 16; o; o >>= 1) s += __shfl_xor_sync(~0u, s, o);
        if (lane == 0) sts2f(mb + B_SW, s, __uint_as_float(ep + 1));
       }
        const uint32_t xa = sm + (c3 * 16 + r4) * 128 + ((c8 ^ r4) << 4);
        const uint4* gx = (const uint4*)(P.x + (b * 16 + r4) * D_ + kl) + c8;
        uint32_t e[4] = {0, 0, 0, 0};
        uint4 wq;
#pragma unroll 1
        for (int kb = wid == 10 ? 0 : 12; kb < (wid == 10 ? 12 : 16); kb++) {
          uint4 v[4];
          if (!(kb & 3)) wq = ld_cg4((const uint4*)(P.wr + k_of(kb + r4)) + c8);
          if (kb >= 12) {
#pragma unroll
            for (int j = 0; j < 4; j++) v[j] = ld_cg4(gx + j * 512);
            gx += 8;
          } else {
            const uint32_t so = xa + xoff(kb & 3, hf);
            mbar_wait(mb + B_FULL + 8 * (kb & 3), (kb >> 2) & 1);
            v[0] = lds4_o<0>(so); v[1] = lds4_o<512>(so ^ 64); v[2] = lds4_o<1024>(so); v[3] = lds4_o<1536>(so ^ 64);
            if (lane < 2) mbar_arrive_rem(eb + 8 * (kb & 3) + ((v[0].x | v[1].x | v[2].x | v[3].x) & zero));
          }
#pragma unroll
          for (int j = 0; j < 16; j++) {
            const uint32_t u = (j & 3) == 0 ? v[j >> 2].x : (j & 3) == 1 ? v[j >> 2].y : (j & 3) == 2 ? v[j >> 2].z : v[j >> 2].w;
            const float d0 = bf_lo(u), d1 = bf_hi(u);
            a[j >> 2] += d0 + d1; a[4 + (j >> 2)] = fmaf(d0, d0, fmaf(d1, d1, a[4 + (j >> 2)]));
          }
          cut<1>(zero);
          const int sl = (kb & 3) * 8 + c8;
          const uint4 wn = make_uint4(__shfl_sync(~0u, wq.x, sl), __shfl_sync(~0u, wq.y, sl), __shfl_sync(~0u, wq.z, sl), __shfl_sync(~0u, wq.w, sl));
#pragma unroll
          for (int j = 0; j < 4; j++) e[j] = hfma2(v[j].x, wn.x, hfma2(v[j].y, wn.y, hfma2(v[j].z, wn.z, hfma2(v[j].w, wn.w, e[j]))));
        }
        float mean, pd;
#pragma unroll 1
        for (int h = 0; h < 2; h++) {
          float u[4], v[2];
#pragma unroll
          for (int i = 0; i < 4; i++) u[i] = ((lane & 4) ? a[4 + i] : a[i]) + __shfl_xor_sync(~0u, (lane & 4) ? a[i] : a[4 + i], 4);
#pragma unroll
          for (int i = 0; i < 2; i++) v[i] = ((lane & 2) ? u[2 + i] : u[i]) + __shfl_xor_sync(~0u, (lane & 2) ? u[i] : u[2 + i], 2);
          mean = pd;
          pd = ((lane & 1) ? v[1] : v[0]) + __shfl_xor_sync(~0u, (lane & 1) ? v[0] : v[1], 1);
#pragma unroll
          for (int j = 0; j < 4; j++) { a[j] = bf_lo(e[j]); a[4 + j] = bf_hi(e[j]); }
        }
        if (wid == 11) {
          sts2f(sm + OFF_COLSUM + 512 + lane * 8, mean, pd);
          fence_gpu();
          bar_arrive(5, 96); PTS(0);
          if (elect_one()) {
#pragma unroll 1
            for (int p = 0; p < 16; p++) {
              const uint32_t ad = sm + bar3(0) + o3(p);
              mbar_init(ad, 1); mbar_init(ad + 256, 1); mbar_init(ad + 448, 8); mbar_init(ad + 704, p == 0 ? 2 : p == 12 ? 1 : p == 15 ? 7 : 8);
              mbar_expect_tx(ad, 8192); mbar_expect_tx(ad + 256, 8192); mbar_expect_tx(mb + B_FULL3 + 8 * p, SLOT_B);
            }
            asm volatile("fence.mbarrier_init.release.cluster;" ::: "memory");
            fence_async_smem();
            mbar_arrive_rem(bars + B_LATE); mbar_arrive_rem((1u << 24) + bars + B_LATE);
          }
          __syncwarp();
        } else {
          if (lane == 0) PTS(1);
          bar_sync(5, 96);
          const float2 u = lds2f(sm + OFF_COLSUM + 512 + lane * 8), sw = lds2f(mb + B_SW);
          mean = (mean + u.x) * (1.f / D_);
          pd += u.y;
          pd += __shfl_xor_sync(~0u, pd, 4);
          const float var = fmaxf(fmaf(-mean, mean, __shfl_xor_sync(~0u, mean, 4)), 0.f);
          const uint32_t tag = __float_as_uint(sw.y) & 255;
          if (c8 < 4) {
            st_rlx2((uint2*)G.st1 + (b >> 1) * 96 + rank * 16 + r4 + 4 * c8, tagged(-mean, tag), tagged(rsq(var + 1e-5f), tag));
            st_rlx(&G.pred[b * 16 + r4 + 4 * c8], (ordered(fmaf(-mean, sw.x, pd)) & ~255u) | tag);
          }
        }
      }
      if (wid < 11) gather(lds1(mb + B_SW + 4) & 255);
      if (wid == 9) {
        if (lane == 0) PTS(6);
        {
          const uint4 sv = make_uint4(SENT, SENT, SENT, SENT);
          uint4* y = &G.ybuf[b * NFFN * 4 + lane];
#pragma unroll
          for (int i = 0; i < 14; i++) y[i * 32] = sv;
          if (lane < 16) G.st2[b * 16 + lane] = make_uint4(0, 0, 0, 0);
          G.hsel[b * 64 + lane] = sv; G.hsel[b * 64 + 32 + lane] = sv;
          if (b < 8) { G.cand[b * 32 + lane] = SENT; G.cst[b * 32 + lane] = make_uint4(0, 0, 0, 0); }
          fence_gpu();
          __syncwarp();
          if (lane == 0) mbar_arrive(mb + B_LATE);
        }
      } else if (wid == 10) {
        {
          mbar_wait(mb + B_FULL + 24, 1);
#pragma unroll 1
          for (int r = -4; r < (fidx >= 0 ? 16 : 0); r++) {
            l2_prefetch((r < 0 ? (const char*)P.wo + (b + 1) * 16384 : (const char*)P.wd + fidx * 65536) + r * 4096 + lane * 128);
            delay(clk(), PDT);
          }
          PTS(4);
        }
      }
      mbar_wait(mb + B_LATE, 0);
      if (wid == 9) {
        if (elect_one()) {
          wait3(60);
#pragma unroll 1
          for (int p = 0; p < 16; p++) {
            const bool mix = (unsigned)(p - 1) < 8;
            const int c1 = mix ? ((p - 1) >> 1) * 16 : 0, c2 = mix ? (hf ^ 1) * 8 + ((p - 1) & 1) * 4 : chunk_of(p) * 4;
            const uint32_t d = sm + (uint32_t)((WO_SLOTS >> (4 * p)) & 15) * SLOT_B;
            if ((0xFFE2 >> p) & 1) mbar_wait(p == 1 ? mb + B_EMPTY + 8 : sm + bar3(32) + o3(p - 5), p == 1);
            if (EFWO) asm volatile("cp.async.bulk.tensor.4d.shared::cluster.global.mbarrier::complete_tx::bytes.L2::cache_hint [%0], [%1, {0, %3, %4, %5}], [%2], %6;"
                         :: "r"(d), "l"(mix ? &tmM : &tmO), "r"(mb + B_FULL3 + 8 * p), "r"(c1), "r"(c2), "r"(c3 * 2), "l"(l2_stream()) : "memory");
            else asm volatile("cp.async.bulk.tensor.4d.shared::cluster.global.mbarrier::complete_tx::bytes [%0], [%1, {0, %3, %4, %5}], [%2];"
                         :: "r"(d), "l"(mix ? &tmM : &tmO), "r"(mb + B_FULL3 + 8 * p), "r"(c1), "r"(c2), "r"(c3 * 2) : "memory");
            if (p >= 10) PTS(7 + p);
          }
          if (fidx >= 0) {
#pragma unroll
            for (int i = 0; i < 4; i++) {
              if (i == 0 || ((DEV >> (4 * i)) & 15) != ((DEV >> (4 * i - 4)) & 15)) wait3(32 + ((DEV >> (4 * i)) & 15));
              tma_3d(sm + ((D_SLOTS >> (4 * i)) & 15) * SLOT_B, &tmD, 0, fidx * 32, i * 4, mb + B_FFN + 8, EFF);
            }
          }
        }
      } else if (wid == 11) {
        const uint2 w = ld_rlx2((const uint2*)(P.wr + c3 * 128) + lane);
        wait3(36);
        sts1(sm + OFF_LNP + (lane & 1) * 128 + (lane >> 1) * 4, w.x); sts1(sm + OFF_LNP + (lane & 1) * 128 + 64 + (lane >> 1) * 4, w.y);
        if (lane < 16) sts1(sm + OFF_LNP + 256 + lane * 4, 0x3F803F80u);
        const uint32_t tag = lds1(mb + B_SW + 4) & 255;
        uint4 k;
        for (int it = 0;; it++) {
          k = ld_rlx4((const uint4*)&G.pred[rb * 256 + hf * 64 + r2 * 128] + c16);
          k.x ^= tag; k.y ^= tag; k.z ^= tag; k.w ^= tag;
          if (!__any_sync(~0u, (k.x | k.y | k.z | k.w) & 255)) break;
          SPINCHK(it, 13);
        }
        const uint2 ahead = top2(k.x | (lane * 4), k.y | (lane * 4 + 1), k.z | (lane * 4 + 2), k.w | (lane * 4 + 3));
        if (lane == 0) sts2f(sm + OFF_MSC + 8, __uint_as_float((ahead.x & 127) ^ NOSPEC), __uint_as_float((ahead.y & 127) ^ NOSPEC));
        __syncwarp();
        if (lane == 0) mbar_arrive(mb + B_FULL3 + 8 * 15);
      } else if (fidx >= 0 && elect_one()) {
        wait3(60);
        mbar_expect_tx(mb + B_FULL, 65536);
#pragma unroll 1
        for (int h = 0; h < 2; h++) {
          const int up = h ^ hf ^ 1;
          mbar_wait(mb + B_EMPTY + 16 - 16 * h, 1);
#pragma unroll
          for (int i = 0; i < 4; i++) {
            const int f = (0x5140 >> (4 * i)) & 15;
            tma_2d(sm + ((GU_SLOTS >> (4 * f)) & 15) * SLOT_B + up * 8192, up ? &tmU : &tmG, fidx * 32, f * 128, mb + B_FULL, EFF);
            if (FDT) delay(clk(), FDT);
          }
          PTS(23 + h);
        }
#pragma unroll 1
        for (int j = 0; j < 8; j++) { mbar_wait(sm + bar3(32) + o3(PD0 + j * PDS / 2), 0); tma_2d(sm + OFF_COLSUM, &tmPD, 0, fidx * 256 + j * 32, mb + B_FFN, false); }
#pragma unroll 1
        for (int i = 0; i < 4; i++) {
          const int f = (0x7362 >> (4 * i)) & 15;
          const uint32_t d = sm + ((GU_SLOTS >> (4 * f)) & 15) * SLOT_B;
          mbar_wait(sm + bar3(32) + o3((GEV >> (4 * i)) & 15), 0);
          tma_2d(d, &tmG, fidx * 32, f * 128, mb + B_FFN, EFF);
          tma_2d(d + 8192, &tmU, fidx * 32, f * 128, mb + B_FFN, EFF);
          PTS(27 + i);
        }
      }
    }
    __syncwarp();
    const float sw = __uint_as_float(lds1(mb + B_SW));
    const int rr = lane >> 4, row00 = rb * 256 + hf * 64;
    uint2 pick;
    if (wid == 8) {
      wait3(61);
      delay(clk(), SDELAY);
      uint4 v;
      int id;
      for (int it = 0;; it++) {
        v = ld_rlx4(&G.cst[jp * 32 + lane]);
        id = __float2int_rn(__uint_as_float(v.w));
        if (!__any_sync(~0u, (id & 15) != 8)) break;
        SPINCHK(it, 14);
      }
      float2 pr;
      const uint32_t k = route(v, sw, id >> 4, pr);
      pick.x = __reduce_max_sync(~0u, k); pick.y = __reduce_max_sync(~0u, k == pick.x ? 0 : k);
      if (k == pick.x || k == pick.y) sts4(sm + OFF_MSC + 16 + (k == pick.y) * 16, k, lane, __float_as_uint(pr.x), __float_as_uint(pr.y));
      __syncwarp();
      if (lane == 0) { mbar_arrive(mb + B_SEL); PTS(16); }
    } else if (wid == 9) {
      wait3(61);
      delay(clk(), LDELAY);
      uint4 v[4];
      for (int it = 0;; it++) {
#pragma unroll
        for (int i = 0; i < 4; i++) v[i] = ld_rlx4(&G.st2[row00 + (i >> 1) * 128 + (i & 1) * 32 + lane]);
        if (!__any_sync(~0u, (v[0].w & v[1].w & v[2].w & v[3].w) != 0x41000000u)) break;
        SPINCHK(it, 6);
      }
      uint32_t k[4];
#pragma unroll
      for (int i = 0; i < 4; i++) {
        float2 pr;
        k[i] = route(v[i], sw, row00 + (i >> 1) * 128 + (i & 1) * 32 + lane, pr);
        const float nm = __uint_as_float(v[i].x) * (-1.f / D_);
        sts2f(sm + OFF_LNP + (i * 32 + lane) * 8, __uint_as_float(pack2(pr.x, pr.x)), __uint_as_float(pack2(nm, nm)));
      }
      const uint2 m = top2(k[0], k[1], k[2], k[3]);
      if (lane == 0) { st_rlx2(&G.cand[c3 * 32 + (rb * 2 + hf) * 2], m.x, m.y); sts2f(sm + OFF_MSC + 0, __uint_as_float(m.x), __uint_as_float(m.y)); }
      wait3(62);
      __syncwarp();
      if (lane == 0) { mbar_arrive(mb + B_OUT); PTS(12); }
      const int ca = 2047 - (((lane & 4) ? m.y : m.x) & 2047), ta = ((ca >> 1) & 64) + (ca & 63);
      uint32_t h0, h1, h2, h3;
      ldsm4_o<0>(sm + HST + ta * 256 + ((((lane & 3) * 4 + (lane >> 3)) ^ (ta & 7)) << 4), h0, h1, h2, h3);
      st_rlx4(&G.hsel[(32 + (rb * 2 + hf) * 2 + rr) * 128 + c3 * 16 + (lane & 15)], make_uint4(h0, h1, h2, h3));
    }
    mbar_wait(mb + B_OUT, 0);
    const float2 cf = lds2f(sm + OFF_MSC + 0);
    const int ca0 = ~__float_as_int(cf.x), ca1 = ~__float_as_int(cf.y), cand0 = ((ca0 >> 1) & 64) + (ca0 & 63), cand1 = ((ca1 >> 1) & 64) + (ca1 & 63);
    auto norm = [](const uint4& v, const float2& pr) {
      const uint32_t r = __float_as_uint(pr.x), m = __float_as_uint(pr.y);
      return make_uint4(hfma2(hadd2(v.x, m), r, v.x), hfma2(hadd2(v.y, m), r, v.y), hfma2(hadd2(v.z, m), r, v.z), hfma2(hadd2(v.w, m), r, v.w));
    };
    uint4* const og = (uint4*)(P.out + row00 * D_ + c3 * 128) + (lane & 15);
    if (wid == 8) {
      delay(clk(), CDELAY);
      uint32_t k;
      for (int it = 0;; it++) { k = ld_rlx(&G.cand[c3 * 32 + lane]); if (!__any_sync(~0u, k == SENT)) break; SPINCHK(it, 12); }
      const uint32_t m1 = __reduce_max_sync(~0u, k), m2 = __reduce_max_sync(~0u, k == m1 ? 0 : k);
      const uint32_t miss = ((m1 ^ pick.x) | (m2 ^ pick.y)) & 2047;
      if (miss && (k == m1 || k == m2)) {
        float2 pr;
        route(ld_rlx4(&G.st2[2047 - (k & 2047)]), sw, 0, pr);
        sts4(sm + OFF_MSC + 48 + (k == m2) * 16, k, 32 + lane, __float_as_uint(pr.x), __float_as_uint(pr.y));
      }
      if (lane == 0) sts1(sm + OFF_MSC + 80, miss);
      __syncwarp();
      if (lane == 0) { mbar_arrive(mb + B_SEL2); PTS(13); }
      const uint32_t kc = __float_as_uint(rr ? cf.y : cf.x);
      const int c = rr ? cand1 : cand0;
      if (kc != m1 && kc != m2) og[(c + (c & 64)) * 128] = norm(lds4(sm + HST + c * 256 + (((lane & 15) ^ (c & 7)) << 4)), lds2f(sm + OFF_LNP + c * 8));
    }
#pragma unroll 1
    for (int t0 = wid == 8 ? 120 : (11 - wid) * 8; t0 < (wid == 8 ? 128 : 120) * !NOOUT; t0 += 24) {
      uint4 v[4];
      float2 pr[4];
      const uint32_t ad = sm + HST + t0 * 256 + lane * 16;
      static_for<0, 4>([&](auto ic) { constexpr int i = decltype(ic)::value; v[i] = lds4_o<i * 512>(ad ^ (rr << 4) ^ (i << 5)); pr[i] = lds2f_o<i * 16>(sm + OFF_LNP + (t0 + rr) * 8); });
#pragma unroll
      for (int i = 0; i < 4; i++) v[i] = norm(v[i], pr[i]);
      if (t0 >= OHOLD) wait3(63);
#pragma unroll
      for (int i = 0; i < 4; i++) {
        const int tr = t0 + rr + 2 * i;
        if (tr != cand0 && tr != cand1) {
          if (OUTEF) asm volatile("st.global.L2::cache_hint.v4.u32 [%0], {%1,%2,%3,%4}, %5;" :: "l"(og + (tr + (tr & 64)) * 128), "r"(v[i].x), "r"(v[i].y), "r"(v[i].z), "r"(v[i].w), "l"(l2_stream()) : "memory");
          else og[(tr + (tr & 64)) * 128] = v[i];
        }
      }
    }
    if (wid == 11 && lane == 0) PTS(31);
  } else {
    asm volatile("setmaxnreg.inc.sync.aligned.u32 224;");
    const int t128 = tid & 127, warp = wid & 3, g = lane >> 2, t = lane & 3;
    const int mb3 = rb * 4 + wg * 2 + hf;
    float acc[64];
    uint4 abuf[3][4];
    uint32_t to;
    int tid2;
    {
      float acc0[96], acc1[96];
#pragma unroll
      for (int i = 0; i < 96; i++) { asm volatile("" : "=f"(acc0[i])); asm volatile("" : "=f"(acc1[i])); }
      const uint32_t xo0 = dlo(sb, 16) + hf * 512, xo1 = dlo(sb, 16) + (hf ^ 1) * 512;
      const uint32_t eb0 = (t128 << 24) + bars + B_EMPTY;
#pragma unroll 1
      for (int kb = 0; kb < 12; kb++) {
        const int s = kb & 3;
        mbar_wait(mb + B_FULL + 8 * s, (kb >> 2) & 1);
        if (LOCK) bar_sync(13, 256);
        if (kb == 0) TS(1);
        const uint32_t xs = xoff(s, wg) >> 4, ws = dlo(sb + woff(s), WSTR);
        pin(acc0); pin(acc1);
        wg_fence();
#pragma unroll
        for (int k = 0; k < 4; k++) {
          const uint64_t db = dsc<1024, 1>(ws + k * 128);
          const int sd = k == 0 ? kb : 1;
          wgmma_n192_ss<0, 1, 0>(acc0, dsc<1024, 1>(xs + xo0 + k * 2), db, sd);
          wgmma_n192_ss<0, 1, 0>(acc1, dsc<1024, 1>(xs + xo1 + k * 2), db, sd);
          if (k == RELK || k == 3) wg_commit();
          if (k == RELK) {
            wg_wait<1>();
            if (kb > 0 && t128 < 2) mbar_arrive_rem(eb0 + 8 * ((kb - 1) & 3));
          }
        }
        pin(acc0); pin(acc1);
      }
      float qa0[32], qa1[32], kv0[64], kv1[64];
#pragma unroll
      for (int i = 0; i < 96; i++) { if (i < 32) { qa0[i] = acc0[i]; qa1[i] = acc1[i]; } else { kv0[i - 32] = acc0[i]; kv1[i - 32] = acc1[i]; } }
      uint2 st[2][2];
      uint4 am;
      auto center = [&](float (&q)[32], float (&kv)[64], const uint2 (&v)[2]) {
        const uint32_t n0 = v[0].x & (t == 0 ? ~255u : 0u), n1 = v[1].x & (t == 0 ? ~255u : 0u);
        am = make_uint4(__byte_perm(n0, 0, 0x3232), __byte_perm(n1, 0, 0x3232),
                        __byte_perm(__float_as_uint(__uint_as_float(n0) - bf_hi(n0)), 0, 0x3232), __byte_perm(__float_as_uint(__uint_as_float(n1) - bf_hi(n1)), 0, 0x3232));
        wg_fence();
        wgmma_n64_rs<1, 0>(q, am.x, am.y, am.z, am.w, dsc<32, 0>(dlo(sb + OFF_COLSUM, 0)), 1);
        wgmma_n128_rs<1, 0>(kv, am.x, am.y, am.z, am.w, dsc<32, 0>(dlo(sb + OFF_COLSUM + 256, 0)), 1);
      };
      auto load_st = [&]() {
        mbar_wait(mb + B_AUX, 0);
#pragma unroll
        for (int i = 0; i < 4; i++) st[i >> 1][i & 1] = ld_rlx2((const uint2*)G.st1 + ((rb * 4 + wg * 2 + ((i >> 1) ^ hf)) * 2 + (warp >> 1)) * 96 + (warp & 1) * 16 + (i & 1) * 8 + g);
      };
      if (!wg) {
        wg_wait<0>();
        if (t128 < 2) mbar_arrive_rem(eb0 + 24);
        load_st();
#pragma unroll 1
        for (int s = 0; s < (B6E < 3 ? 3 : 4); s++) mbar_wait(mb + B_FULL + 8 * s, 1);
        bar_sync(6, 256);
      }
      static_for<0, 4>([&](auto sc) {
        constexpr int s = decltype(sc)::value;
        if (wg || (B6E < 3 && s == 3)) mbar_wait(mb + B_FULL + 8 * s, 1);
        const uint32_t xs = (wg ? xoff(s, 1) : xoff(s, 0)) >> 4, ws = dlo(sb + woff(s) + WSTR, WSTR);
        pin(kv0); pin(kv1); pin(qa0); pin(qa1);
        wg_fence();
#pragma unroll
        for (int k = 0; k < 4; k++) {
          const uint64_t db = dsc<1024, 1>(ws + k * 128);
          wgmma_n128_ss<0, 1, 0>(kv0, dsc<1024, 1>(xs + xo0 + k * 2), db, 1);
          wgmma_n128_ss<0, 1, 0>(kv1, dsc<1024, 1>(xs + xo1 + k * 2), db, 1);
          if (s == 0 && k == B6H - 1) { if (!wg) bar_sync(14, 256); wg_fence(); }
          if (k == 3 || (k == 2 && s == 0)) wg_commit();
          if (k == (s ? 3 : 2) && s < 3) {
            wg_wait<1>();
            if (s == 0) { if (wg && t128 < 2) mbar_arrive_rem(eb0 + 24); }
            else if (!wg) bar_arrive(8 + s, 256);
          }
        }
        if (s == B6E && wg) bar_arrive(6, 256);
        if (s == 3 && B6H && wg) bar_arrive(14, 256);
        if (s == STLD && wg) load_st();
      });
      if (CUTS & 2) {
        cut<6>(zero);
#pragma unroll
        for (int i = 0; i < 4; i++) asm volatile("" : "+r"(st[i >> 1][i & 1].x), "+r"(st[i >> 1][i & 1].y) :: "memory");
      }
      center(qa0, kv0, st[0]);
      wg_commit();
      if (B6E > 3 && wg) bar_arrive(6, 256);
      float rs[2][2];
#pragma unroll
      for (int i = 0; i < 4; i++) rs[i >> 1][i & 1] = __uint_as_float(st[i >> 1][i & 1].y & ~255u);
      const uint32_t sad = sm + (wg ? 11 : 2) * SLOT_B + (warp * 16 + (lane & 15)) * 128 + (((lane >> 4) ^ (lane & 7)) << 4);
      wg_wait<0>();
      pin(kv0); pin(kv1); pin(qa0); pin(qa1); pin4(am);
      center(qa1, kv1, st[1]);
      wg_commit();
      if (wg) bar_arrive(11, 256);
      if (CUTS & 1) cut<2>(zero);
      TS(2);
      float rl[2];
      uint32_t r2[2];
      auto scales = [&](int m, uint32_t z) {
#pragma unroll
        for (int h = 0; h < 2; h++) { const float r = __uint_as_float(__float_as_uint(rs[m][h]) + z); r2[h] = pack2(r, r); rl[h] = r * 1.4426950408889634f; }
      };
      auto phi8 = [&](const float* a) {
        return make_uint4(phi2(a[0], a[1], r2[0], rl[0]), phi2(a[2], a[3], r2[1], rl[1]), phi2(a[4], a[5], r2[0], rl[0]), phi2(a[6], a[7], r2[1], rl[1]));
      };
      auto stage = [&](float (&a)[64], auto mc) {
        constexpr int m = decltype(mc)::value;
        uint4 r[4];
        scales(m, 0);
#pragma unroll
        for (int j = 0; j < 4; j++) r[j] = phi8(a + j * 8);
        if (m == 0 || wg) bar_sync(wg ? 9 + m : 11, 256 + (r[SBAR].x & zero));
#pragma unroll
        for (int j = 0; j < 4; j++) {
          const int v = 32 + j * 8;
          stsm4_o<WSTR + m * 8192>(sad ^ (j << 5), hmul2(pack2(a[v], a[v + 1]), r2[0]), hmul2(pack2(a[v + 2], a[v + 3]), r2[1]),
                                                   hmul2(pack2(a[v + 4], a[v + 5]), r2[0]), hmul2(pack2(a[v + 6], a[v + 7]), r2[1]));
        }
#pragma unroll
        for (int j = 0; j < 4; j++) stsm4_o<m * 8192>(sad ^ (j << 5), r[j].x, r[j].y, r[j].z, r[j].w);
      };
      stage(kv0, std::integral_constant<int, 0>{});
      wg_wait<0>();
      pin(kv1); pin(qa1); pin4(am);
      stage(kv1, std::integral_constant<int, 1>{});
      fence_async_smem();
      TS(3);
      uint32_t xr[8][4];
      auto load_xr = [&]() {
        const uint32_t xa = sm + hf * 8192 + (warp * 16 + (lane & 15)) * 128 + (((lane >> 4) ^ (lane & 7)) << 4);
#pragma unroll
        for (int q = 0; q < 8; q++) ldsm4_o<0>((xa ^ ((q & 3) << 5)) + xoff(rank * 2 + (q >> 2), wg), xr[q][0], xr[q][1], xr[q][2], xr[q][3]);
      };
      if (!wg) { bar_arrive(4, 256); load_xr(); }
      else {
        float ka[36];
#pragma unroll
        for (int i = 0; i < 36; i++) ka[i] = 0.f;
        auto kv_mma = [&](auto ic) {
          constexpr int i = decltype(ic)::value;
          constexpr uint32_t o = sb + (i < 8 ? 11 : 2) * SLOT_B + (i & 7) * 2048;
          wgmma_n72_ss<1, 1, 0>(ka, dsc<1024, 1>(dlo(o, 8192)), dsc<1024, 1>(dlo(o + WSTR, sb + OFF_STATS - o - WSTR)), i);
        };
        mbar_wait(mb + B_LATE, 0);
        bar_sync(3, 128);
        wg_fence();
        static_for<0, 8>(kv_mma);
        wg_commit();
        uint4* dst = &G.kvp[cg * 2304 + rb * 32];
        if (CUTS & 4) cut<3>(zero);
        load_xr();
        bar_sync(4, 256);
        static_for<8, 16>(kv_mma);
        wg_commit();
        if (QHOLD == 1) bar_arrive(8, 256);
        wg_wait<0>();
        pin(ka);
        if (QHOLD == 2) bar_arrive(8, 256);
        TS(4);
        if (warp < 2) {
          st_rlx4(dst + warp * 512 + lane, make_uint4(pack2(ka[0], ka[1]), pack2(ka[4], ka[5]), pack2(ka[8], ka[9]), pack2(ka[12], ka[13])));
          st_rlx4(dst + warp * 512 + 256 + lane, make_uint4(pack2(ka[2], ka[3]), pack2(ka[6], ka[7]), pack2(ka[10], ka[11]), pack2(ka[14], ka[15])));
        } else {
          st_rlx4(dst + warp * 512 + lane, make_uint4(pack2(ka[16], ka[17]), pack2(ka[20], ka[21]), pack2(ka[24], ka[25]), pack2(ka[28], ka[29])));
          st_rlx4(dst + warp * 512 + 256 + lane, make_uint4(pack2(ka[18], ka[19]), pack2(ka[22], ka[23]), pack2(ka[26], ka[27]), pack2(ka[30], ka[31])));
        }
        st_rlx((uint32_t*)(dst + 2048) + t128, pack2(ka[32], ka[34]));
        if (QHOLD == 3) bar_arrive(8, 256);
        if (t128 == 0) mbar_arrive(sm + bar3(60));
      }
      TS(5);
      uint32_t pq[16], pq0[16];
      auto q_mma = [&](float (&q)[32], uint32_t xo, int s0, int s1) {
#pragma unroll 1
        for (int s = s0; s < s1; s++) {
          const uint32_t xs = (xoff(s, wg) >> 4) + xo, ws = dlo(sb + woff(s), 8192);
          pin(q);
          wg_fence();
#pragma unroll
          for (int k = 0; k < 4; k++) wgmma_n64_ss<0, 1, 0>(q, dsc<1024, 1>(xs + k * 2), dsc<1024, 1>(ws + k * 128), 1);
          wg_commit();
        }
      };
      auto q_phi = [&](float (&q)[32], int m, uint32_t (&pq)[16], int lo, int hi) {
        scales(m, zero);
#pragma unroll
        for (int j = lo; j < hi; j++) { const uint4 r = phi8(q + j * 8); pq[j * 4] = r.x; pq[j * 4 + 1] = r.y; pq[j * 4 + 2] = r.z; pq[j * 4 + 3] = r.w; }
      };
      auto o_of = [&](uint32_t (&pq)[16], uint4 (&o)[4], uint4* first, bool pub) {
        float oa[2][20];
#pragma unroll
        for (int i = 0; i < 40; i++) oa[i / 20][i % 20] = 0.f;
        wg_fence();
#pragma unroll
        for (int ks = 0; ks < 4; ks++) {
          wgmma_n40_rs<1, 0>(oa[ks >> 1], pq[ks * 4], pq[ks * 4 + 1], pq[ks * 4 + 2], pq[ks * 4 + 3], dsc<1024, 1>(dlo(sb + OFF_KVB + ks * 2048, 8192)), ks & 1);
          if (ks & 1) wg_commit();
        }
#pragma unroll
        for (int h = 0; h < 2; h++) {
          if (h) wg_wait<0>(); else wg_wait<1>();
          pin(oa[h]);
          const float (&d)[20] = oa[h];
          const float i0 = rcp(d[16] + 1e-6f), i1 = rcp(d[18] + 1e-6f);
#pragma unroll
          for (int k2 = 0; k2 < 2; k2++) {
            o[h * 2 + k2] = make_uint4(pack2(d[k2 * 8] * i0, d[k2 * 8 + 1] * i0), pack2(d[k2 * 8 + 2] * i1, d[k2 * 8 + 3] * i1),
                                       pack2(d[k2 * 8 + 4] * i0, d[k2 * 8 + 5] * i0), pack2(d[k2 * 8 + 6] * i1, d[k2 * 8 + 7] * i1));
            if (pub && !h) st_rlx4(first + (h * 2 + k2) * 1024, o[h * 2 + k2]);
          }
        }
#pragma unroll
        for (int i = 0; i < 16; i++) asm volatile("" : "+r"(pq[i]) :: "memory");
      };
      bar_sync(wg ? 7 : 8, 256);
      TS(12);
      q_mma(qa1, xo1, 0, 4);
      if (wg) {
        if (QX) {
          pin(qa0);
          wg_fence();
#pragma unroll
          for (int k = 0; k < 4 * QX; k++) wgmma_n64_ss<0, 1, 0>(qa0, dsc<1024, 1>((xoff(k >> 2, 1) >> 4) + xo0 + (k & 3) * 2), dsc<1024, 1>(dlo(sb + woff(k >> 2), 8192) + (k & 3) * 128), 1);
          wg_commit();
        }
        bar_arrive(8, 256);
        wg_wait<QX ? 1 : 0>();
      }
      else { bar_arrive(7, 256); wg_wait<0>(); }
      TS(13);
      if (tid == 0) mbar_arrive(mb + B_EMPTY + 16);
      cut<5>(zero);
      pin(qa1);
      q_phi(qa1, 1, pq, 0, 4);
      tid2 = __shfl_sync(~0u, tid, lane);
      uint32_t done = 0;
#pragma unroll
      for (int j = 0; j < 8; j++) done |= pq[2 * j] | pq[2 * j + 1] | xr[j][3];
      bar_sync(wg ? 7 : 8, 256 + (done & zero));
      TS(9);
      q_mma(qa0, xo0, wg * QX, 4);
      if (!wg) bar_arrive(7, 256);
      wg_wait<0>();
      pin(qa0);
      if (t128 == 0) mbar_arrive(mb + B_EMPTY + 8 * wg);
      TS(6);
#pragma unroll
      for (int i = 0; i < 16; i++) pq0[i] = 0;
#pragma unroll 1
      for (int r = 0;; r++) {
      if (ASYM && r == wg) { pin(qa0); q_phi(qa0, 0, pq0, 0, ASYM); }
      if (r) break;
      {
        uint4 a, v[8];
        uint32_t z[8], zs;
        const int blk = warp * 2 + wg;
        mbar_wait(mb + B_KVL, 0);
        static_for<0, 8>([&](auto ic) { constexpr int i = decltype(ic)::value; v[i] = lds4_o<sb + 11 * SLOT_B + i * 512>(own + (blk + (blk & 4)) * 4096 + lane * 16); });
#pragma unroll
        for (int i = 0; i < 8; i++) z[i] = lds1(sm + 2 * SLOT_B + i * 512 + t128 * 4);
#pragma unroll 1
        for (int it = 0;; it++) {
          zs = hadd2(hadd2(hadd2(z[0], z[1]), hadd2(z[2], z[3])), hadd2(hadd2(z[4], z[5]), hadd2(z[6], z[7])));
          a = hadd8(hadd8(hadd8(v[0], v[1]), hadd8(v[2], v[3])), hadd8(hadd8(v[4], v[5]), hadd8(v[6], v[7])));
          TSV(20, it + 1);
          if (!__any_sync(~0u, hnan(hadd2(hadd2(hadd2(a.x, a.y), hadd2(a.z, a.w)), zs)))) break;
          uint32_t mm = 0;
#pragma unroll
          for (int i = 0; i < 8; i++) mm = max4(max(mm, z[i]), v[i]);
          if (!__any_sync(~0u, mm == SENT)) break;
#pragma unroll
          for (int i = 0; i < 8; i++) { v[i] = ld_rlx4(&G.kvp[cg * 2304 + blk * 256 + i * 32 + lane]); z[i] = ld_rlx((const uint32_t*)&G.kvp[cg * 2304 + 2048 + i * 32] + t128); }
          SPINCHK(it, 4);
        }
        TS(23);
        const uint32_t kb0 = sm + OFF_KVB + blk * 1024 + (lane & 7) * 128;
        stsm4(kb0 + (((lane >> 3) ^ (lane & 7)) << 4), a.x, a.y, a.z, a.w);
        asm volatile("stmatrix.sync.aligned.m8n8.x1.shared.b16 [%0], {%1};" :: "r"(kb0 + ((4 ^ (lane & 7)) << 4)), "r"(zs >> (16 * wg)) : "memory");
        fence_async_smem();
        bar_sync(12, 256);
      }
      TS(7);
      if (t128 == 0) mbar_arrive_rem((wg << 24) + sb + bar3(48));
      to = clk();
      o_of(pq, abuf[1], &G.obuf[((mb3 ^ 1) * 64 + hf * 32 + c3) * 128 + (tid2 & 127)], true);
      TS(29);
      }
      if (!ASYM) cut<4>(zero);
      pin(qa0);
      q_phi(qa0, 0, pq0, ASYM, 4);
      o_of(pq0, abuf[0], nullptr, false);
#pragma unroll
      for (int q = 0; q < 32; q++) { asm volatile("" : "+r"(xr[q >> 2][q & 3])); acc[q * 2] = bf_lo(xr[q >> 2][q & 3]); acc[q * 2 + 1] = bf_hi(xr[q >> 2][q & 3]); }
      pin(acc);
    }
    {
    const int t128 = tid2 & 127, lane = tid2 & 31, g = lane >> 2, t = lane & 3;
    TS(8);
    uint32_t wa[32][4];
    auto load_gu = [&](int f, int lo = 0, int hi = 8) {
      const uint32_t ad = own + ((lane >> 3) & 1) * 8192 + ((lane >> 4) * 8 + (lane & 7)) * 64 + ((warp ^ ((lane >> 1) & 3)) << 4) + ((GU_SLOTS >> (16 * wg + 4 * f)) & 15) * SLOT_B;
      static_for<0, 8>([&](auto ic) { constexpr int i = decltype(ic)::value; if (i >= lo && i < hi) ldsm4t_o<sb + i * 1024>(ad, wa[f * 8 + i]); });
    };
    {
      const uint32_t la = own + wg * 8192 + t128 * 16, fa = sm + wg * 256;
      int pv = tid2 & zero;
      auto step = [&](const int p, auto jc) {
        constexpr int j = decltype(jc)::value;
        uint4 (&a)[4] = abuf[j == 3 ? 0 : (j + 1) % 3];
        uint4 (&n)[4] = abuf[j == 3 ? 1 : (j + 2) % 3];
        auto fetch = [&]() {
          const uint32_t ra = la + ((p + 1) & 3) * SLOT_B;
          mbar_wait(fa + bar3(0) + o3(p + 1), 0);
          n[0] = lds4_o<sb + 10 * SLOT_B>(ra); n[1] = lds4_o<sb + 10 * SLOT_B + 2048>(ra); n[2] = lds4_o<sb + 10 * SLOT_B + 4096>(ra); n[3] = lds4_o<sb + 10 * SLOT_B + 6144>(ra);
        };
        const bool early = j == 0 ? p > 1 : j == 1 ? true : j == 2 ? p < 15 : false;
        const uint32_t bs = dlo(sb, 8192) + (uint32_t)((WO_SLOTS >> (4 * p)) & 15) * (SLOT_B >> 4);
        if (early) fetch();
        if (p == 1) TS(28);
        pin(acc);
        wg_fence();
#pragma unroll
        for (int k = 0; k < 4; k++) {
          wgmma_n128_rs<1, 0>(acc, a[k].x, a[k].y, a[k].z, a[k].w, dsc<1024, 1>(bs + k * 128), 1);
          if (k == 0) { if (j != 2 || p < 15) mbar_wait(mb + B_FULL3 + 8 * p + 8, 0); wg_fence(); }
        }
        wg_commit();
        if (j == 3) {
#pragma unroll
          for (int i = 0; i < 4; i++) { abuf[2][i] = make_uint4(zero, zero, zero, zero); pin4(abuf[2][i]); }
          if (GUP == 0) { if (fidx >= 0) mbar_wait(mb + B_FULL, 0); load_gu(0); }
          if (GUP < 2) load_gu(1);
          delay(to, BDELAY);
#pragma unroll
          for (int k = 2; k < 4; k++) st_rlx4(&G.obuf[((mb3 ^ 1) * 64 + hf * 32 + c3) * 128 + t128 + k * 1024], n[k]);
          TS(24);
          fetch();
          TS(27);
        } else if (j == 0 && p == 1) fetch();
        pv++;
        if (__any_sync(~0u, max(max4(max4(0, n[0]), n[1]), max4(max4(0, n[2]), n[3])) == SENT)) {
          const uint4* q = &G.obuf[(mb3 * 64 + chunk_of(pv) * 4) * 128 + t128];
#pragma unroll 1
          for (int it = 0;; it++) {
#pragma unroll
            for (int i = 0; i < 4; i++) n[i] = ld_rlx4(q + i * 128);
            TSV(21, _ts | 1 << pv);
            if (!__any_sync(~0u, max(max4(max4(0, n[0]), n[1]), max4(max4(0, n[2]), n[3])) == SENT)) break;
            SPINCHK(it, 5);
          }
        }
        if (lane == 0 && p < 11) mbar_arrive_rem((wg << 24) + sb + bar3(48) + o3(p + 1));
        wg_wait<1>();
        pin(acc);
        if (j < 3) {
#pragma unroll
          for (int i = 0; i < 4; i++) pin4(abuf[j][i]);
        }
        if (j == 3 || (j == 0 && p == 1)) {
#pragma unroll
          for (int k = 0; k < 4; k++) if ((k < W0N) == (j == 3)) st_rlx4(&G.obuf[(mb3 * 64 + cg * 4 + k) * 128 + t128], abuf[0][k]);
        }
        if (lane == 0) mbar_arrive(sm + bar3(32) + o3(p));
      };
      if (GUP > 0) { if (fidx >= 0) mbar_wait(mb + B_FULL, 0); load_gu(0); }
      if (GUP == 2) load_gu(1);
      mbar_wait(mb + B_FULL3, 0);
      step(0, std::integral_constant<int, 3>{});
#pragma unroll 1
      for (int pp = 1; pp < 16; pp += 3) static_for<0, 3>([&](auto jc) { step(pp + decltype(jc)::value, jc); });
    }
    uint4 wb[4];
#pragma unroll
    for (int i = 0; i < 4; i++) wb[i] = lds4(sm + OFF_LNP + ((g & 1) ? t * 64 : 256) + i * 16);
    const float2 ah = lds2f(sm + OFF_MSC + 8);
    const int ta = __float_as_int((lane & 8) ? ah.y : ah.x);
    int sl = (ta & 7) * 4 + ((ta >> 3) & 1), son = lane < 16 && (ta >> 4) == wid;
    float sid = c3 ? 1.f : (float)((mb3 * 64 + (ta & 63)) * 16 + 1);
    uint4 *sp = &G.cst[(lane & 7) * 32 + (rb * 2 + hf) * 2 + ((lane >> 3) & 1)], *sq = &G.st2[mb3 * 64 + warp * 16 + (t & 1) * 8 + g];
    asm volatile("" : "+r"(sl), "+r"(son), "+f"(sid), "+l"(sp), "+l"(sq) :: "memory");
    if (T4) cut<7>(zero);
    wg_wait<0>();
    pin(acc);
#pragma unroll
    for (int i = 0; i < 4; i++) pin4(abuf[0][i]);
    TS(10);
    const uint32_t msc = sm + OFF_MSC;
    uint32_t hp[8][4];
    {
      float se[2][4], q[4] = {0.f, 0.f, 0.f, 0.f};
#pragma unroll
      for (int i = 0; i < 8; i++) se[i >> 2][i & 3] = 0.f;
#pragma unroll
      for (int j = 0; j < 8; j++) {
#pragma unroll
        for (int i = 0; i < 4; i++) { const float a = acc[j * 8 + i * 2], c = acc[j * 8 + i * 2 + 1]; hp[j][i] = pack2(a, c); q[i] = fmaf(a, a, fmaf(c, c, q[i])); }
        mma16816(se[j & 1], hp[j], (j & 1) ? wb[j >> 1].z : wb[j >> 1].x, (j & 1) ? wb[j >> 1].w : wb[j >> 1].y);
      }
      const bool od = t & 1;
      const float q0 = q[0] + q[2], q1 = q[1] + q[3];
      float qq = (od ? q1 : q0) + __shfl_xor_sync(~0u, od ? q0 : q1, 1);
      qq += __shfl_xor_sync(~0u, qq, 2);
      const float ss = od ? se[0][2] + se[1][2] : se[0][0] + se[1][0], ee = od ? se[0][3] + se[1][3] : se[0][1] + se[1][1];
      red4(son, sp, __shfl_sync(~0u, ss, sl), __shfl_sync(~0u, qq, sl), __shfl_sync(~0u, ee, sl), sid);
      red4(t < 2, sq, ss, qq, ee, 1.f);
#pragma unroll 1
      for (int c = 0; c < 2; c++) {
        const int tr = __float_as_int(c ? ah.y : ah.x);
        if ((tr >> 4) == wid && g == (tr & 7)) {
#pragma unroll
          for (int i = 0; i < 4; i++)
            st_rlx4(&G.hsel[((rb * 2 + hf) * 2 + c) * 128 + c3 * 16 + i * 4 + t], (tr & 8) ? make_uint4(hp[2 * i][1], hp[2 * i][3], hp[2 * i + 1][1], hp[2 * i + 1][3])
                                                                                           : make_uint4(hp[2 * i][0], hp[2 * i][2], hp[2 * i + 1][0], hp[2 * i + 1][2]));
        }
      }
      if (lane == 0) mbar_arrive(sm + bar3(61));
      TS(11);
    }
    uint32_t wd[8][2][4];
    const uint32_t dw = sm + ((D_SLOTS >> (2 * (wid & 6))) & 15) * SLOT_B + (wid & 1) * 8192;
    const uint32_t da = dw + ((lane >> 4) * 8 + (lane & 7)) * 128 + ((((lane >> 3) & 1) ^ (lane & 7)) << 4);
    const uint32_t xl = own + ((D_SLOTS >> (8 * wg + ((lane & 16) >> 2))) & 15) * SLOT_B + (lane & 8) * 1024 + (lane & 7) * 16;
    int pass = 0;
    if (!GUPOS) { if (fidx >= 0) mbar_wait(mb + B_FFN, 1); load_gu(2); load_gu(3); }
    {
      bar_sync(1, 256);
      const uint32_t ha = sm + HST + wid * 4096 + (lane & 15) * 256 + (((lane >> 4) ^ (lane & 7)) << 4);
      static_for<0, 8>([&](auto jc) { constexpr int j = decltype(jc)::value; stsm4_o<(j >> 2) * 128>(ha ^ ((j & 3) << 5), hp[j][0], hp[j][1], hp[j][2], hp[j][3]); });
      asm volatile("fence.acq_rel.cta;" ::: "memory");
      __syncwarp();
      if (lane == 0) mbar_arrive(sm + bar3(62));
    }
    auto load_d1 = [&]() {
      if (fidx >= 0) mbar_wait(mb + B_FFN + 8, 0);
      static_for<0, 8>([&](auto ic) { constexpr int i = decltype(ic)::value; ldsm4t_o<(i & 1) * 2048>(da ^ ((i >> 1) << 5), wd[i >> 1][i & 1]); });
    };
    if (GUPOS) { if (fidx >= 0) mbar_wait(mb + B_FFN, 1); load_gu(2); load_gu(3); }
    if (!D1POS) load_d1();
#pragma unroll 1
    for (;; pass++) {
      TS(15);
      mbar_wait(mb + B_SEL, 0);
      const uint4 sx = lds4(msc + 16 + pass * 32 + (lane & 16));
      TS(26);
      const uint4* xp = &G.hsel[sx.y * 128 + wid * 16 + (lane & 15)];
      uint4 xv = ld_rlx4(xp);
      if (D1POS && !pass) load_d1();
#pragma unroll 1
      for (int it = 0; __any_sync(~0u, max4(0, xv) == SENT); it++) { xv = ld_rlx4(xp); SPINCHK(it, 7); }
      const float f = __uint_as_float(sx.z), n = __uint_as_float(sx.w);
      sts4(dw + ((lane & 12) * 2 + (lane >> 4) * 4 + t) * 16, pack2(fmaf(bf_lo(xv.x), f, n), fmaf(bf_hi(xv.x), f, n)), pack2(fmaf(bf_lo(xv.y), f, n), fmaf(bf_hi(xv.y), f, n)),
           pack2(fmaf(bf_lo(xv.z), f, n), fmaf(bf_hi(xv.z), f, n)), pack2(fmaf(bf_lo(xv.w), f, n), fmaf(bf_hi(xv.w), f, n)));
      if (wid == rb && (g & 3) == (cg >> 2)) sts4(msc + 96 + (lane >> 4) * 16 + t * 32, xv.x, xv.y, xv.z, xv.w);
      bar_sync(2 + wg, 128);
      TS(14);
      float gu[4][4];
#pragma unroll
      for (int i = 0; i < 16; i++) gu[i >> 2][i & 3] = 0.f;
      uint4 xb[4];
      static_for<0, 4>([&](auto ic) { constexpr int i = decltype(ic)::value; xb[i] = lds4_o<sb + i * 128>(xl); });
#pragma unroll
      for (int i = 0; i < 16; i++) {
        const int ks = i & 7;
#pragma unroll
        for (int j = i < 8 ? 2 : 0; j < (i < 8 ? 4 : 2); j++) mma16816(gu[j], wa[j * 8 + ks], (ks & 1) ? xb[ks >> 1].z : xb[ks >> 1].x, (ks & 1) ? xb[ks >> 1].w : xb[ks >> 1].y);
        if (i == D2I) {
          const uint32_t dd = da | ((__float_as_uint(gu[2][0]) | __float_as_uint(gu[3][0])) & zero);
          static_for<0, 8>([&](auto jc) { constexpr int j = decltype(jc)::value; ldsm4t_o<4096 + (j & 1) * 2048>(dd ^ ((j >> 1) << 5), wd[4 + (j >> 1)][j & 1]); });
          if (T1) cut<8>(zero);
#pragma unroll
          for (int j = 0; j < 4; j++) { pin(gu[j]); pin4(xb[j]); }
        }
      }
      {
        float o[4];
#pragma unroll
        for (int j = 0; j < 4; j++) o[j] = t == 0 ? gu[0][j] : t == 1 ? gu[1][j] : t == 2 ? gu[2][j] : gu[3][j];
        const float e0 = ((t & 2) ? o[2] : o[0]) + __shfl_xor_sync(~0u, (t & 2) ? o[0] : o[2], 2), e1 = ((t & 2) ? o[3] : o[1]) + __shfl_xor_sync(~0u, (t & 2) ? o[1] : o[3], 2);
        sts1(sm + (wg ? DS1 : DS0) * SLOT_B + 1024 + t128 * 4, __float_as_uint(((t & 1) ? e1 : e0) + __shfl_xor_sync(~0u, (t & 1) ? e0 : e1, 1)));
      }
      TS(25);
      mbar_wait(mb + B_SEL2, 0);
      const uint32_t miss = lds1(msc + 80);
      bar_sync(1, 256);
      if (pass || !miss) break;
      load_gu(2); load_gu(3);
    }
    {
      const uint4 p0 = lds4_o<sb + DS0 * SLOT_B + 1024>(own + lane * 16), p1 = lds4_o<sb + DS1 * SLOT_B + 1024>(own + lane * 16);
      const float g0 = __uint_as_float(p0.x) + __uint_as_float(p1.x), g1 = __uint_as_float(p0.y) + __uint_as_float(p1.y);
      const float u0 = __uint_as_float(p0.z) + __uint_as_float(p1.z), u1 = __uint_as_float(p0.w) + __uint_as_float(p1.w);
      const uint32_t act = pack2(g0 * rcp(1.f + ex2(-1.4426950408889634f * g0)) * u0, g1 * rcp(1.f + ex2(-1.4426950408889634f * g1)) * u1);
      uint32_t bq[4];
#pragma unroll
      for (int i = 0; i < 4; i++) {
        const uint32_t lo = __shfl_sync(~0u, act, i * 8 + 2 * t), hi = __shfl_sync(~0u, act, i * 8 + 2 * t + 1);
        bq[i] = __byte_perm(lo, hi, (g & 1) ? 0x7632 : 0x5410);
      }
      TS(16);
      float ya[8][4];
#pragma unroll
      for (int i = 0; i < 8; i++) { ya[i][0] = 0.f; ya[i][1] = 0.f; ya[i][2] = 0.f; ya[i][3] = 0.f; }
#pragma unroll
      for (int ks = 0; ks < 2; ks++)
#pragma unroll
        for (int i = 0; i < 8; i++) mma16816(ya[i], wd[i][ks], bq[ks * 2], bq[ks * 2 + 1]);
    if (fidx >= 0) {
      uint2* const yp = (uint2*)&G.ybuf[((wid * 16 + t * 2) * NFFN + fidx) * 4] + g;
#pragma unroll
      for (int h = 0; h < 2; h++) {
        float o[4];
#pragma unroll
        for (int j = 0; j < 4; j++) o[j] = t == 0 ? ya[h * 4][j] : t == 1 ? ya[h * 4 + 1][j] : t == 2 ? ya[h * 4 + 2][j] : ya[h * 4 + 3][j];
        st_rlx2(yp + h * (8 * NFFN * 8), __float_as_uint(o[0]), __float_as_uint(o[1]));
        st_rlx2(yp + h * (8 * NFFN * 8) + NFFN * 8, __float_as_uint(o[2]), __float_as_uint(o[3]));
      }
    }
    }
    const uint32_t ty = clk();
    TS(17);
    if (wid < 7) {
      const uint4* const yq = &G.ybuf[b * NFFN * 4 + wid * 64 + lane];
      const uint4 sel = lds4(msc + 16 + pass * 32 + (lane & 1) * 16);
      const uint32_t fh = lds1(msc + 96 + (lane & 1) * 16 + (g & 3) * 32 + (cg & 3) * 4);
      const float r = __uint_as_float(sel.x ^ (~(uint32_t)((int)sel.x >> 31) | 0x80000000u));
      float sg = rcp(1.f + ex2(-1.4426950408889634f * r)), base = fmaf((lane & 2) ? bf_hi(fh) : bf_lo(fh), 1.f + __uint_as_float(sel.z), __uint_as_float(sel.w));
      __nv_bfloat16* op = P.out + (size_t)(2047 - (sel.x & 2047)) * D_ + b * 8 + ((lane >> 1) & 7);
      asm volatile("" : "+f"(sg), "+f"(base), "+l"(op) :: "memory");
      delay(ty | (__float_as_uint(sg) & zero), YDELAY);
      uint4 v0, v1;
#pragma unroll 1
      for (int it = 0;; it++) {
        v0 = ld_rlx4(yq); v1 = ld_rlx4(yq + 32);
        TSV(22, it + 1);
        if (!__any_sync(~0u, max(max4(0, v0), max4(0, v1)) == SENT)) break;
        SPINCHK(it, 8);
      }
      if (lane == 0) mbar_arrive(sm + bar3(63));
      TS(18);
      float y0 = __uint_as_float(v0.x) + __uint_as_float(v1.x), y1 = __uint_as_float(v0.y) + __uint_as_float(v1.y);
      float y2 = __uint_as_float(v0.z) + __uint_as_float(v1.z), y3 = __uint_as_float(v0.w) + __uint_as_float(v1.w);
      float z0 = ((lane & 16) ? y2 : y0) + __shfl_xor_sync(~0u, (lane & 16) ? y0 : y2, 16), z1 = ((lane & 16) ? y3 : y1) + __shfl_xor_sync(~0u, (lane & 16) ? y1 : y3, 16);
      z0 = ((lane & 8) ? z1 : z0) + __shfl_xor_sync(~0u, (lane & 8) ? z0 : z1, 8);
      z0 += __shfl_xor_sync(~0u, z0, 4);
      const uint32_t yx = sm + OFF_COLSUM;
      if (!(lane & 4)) sts1(yx + (t * 4 + (lane >> 3)) * 32 + wid * 4, __float_as_uint(z0));
      if (wid) bar_arrive(1, 224);
      else {
        bar_sync(1, 224);
        const uint4 a = lds4(yx + (lane & 15) * 32), c = lds4(yx + (lane & 15) * 32 + 16);
        const float y = ((__uint_as_float(a.x) + __uint_as_float(a.y)) + (__uint_as_float(a.z) + __uint_as_float(a.w))) + ((__uint_as_float(c.x) + __uint_as_float(c.y)) + __uint_as_float(c.z));
        if (lane < 16) *op = __float2bfloat16(fmaf(y, sg, base));
        if (b == 0 && lane == 16) G.epoch = lds1(mb + B_SW + 4);
      }
    }
    }
    TS(19); TSG(31);
    if (warp == 0) TS_DUMP(wg);
  }
}

typedef CUresult (*EncodeFn)(CUtensorMap*, CUtensorMapDataType, cuuint32_t, void*, const cuuint64_t*, const cuuint64_t*, const cuuint32_t*,
                             const cuuint32_t*, CUtensorMapInterleave, CUtensorMapSwizzle, CUtensorMapL2promotion, CUtensorMapFloatOOBfill);
void make_map(EncodeFn enc, CUtensorMap* m, const void* p, uint64_t cols, uint64_t rows, uint64_t d0, uint32_t b0, uint32_t b1, uint32_t b2, CUtensorMapSwizzle sw,
              CUtensorMapL2promotion promo = CU_TENSOR_MAP_L2_PROMOTION_L2_128B) {
  cuuint64_t dims[3] = {d0, rows, cols / d0}, str[2] = {cols * 2, d0 * 2};
  cuuint32_t box[3] = {b0, b1, b2}, es[3] = {1, 1, 1};
  enc(m, CU_TENSOR_MAP_DATA_TYPE_BFLOAT16, b2 ? 3 : 2, const_cast<void*>(p), dims, str, box, es, CU_TENSOR_MAP_INTERLEAVE_NONE, sw,
      promo, CU_TENSOR_MAP_FLOAT_OOB_FILL_NONE);
}

}

extern "C" void kernel_launch(void* const* d_in, const int* in_sizes, int n_in, void* d_out, int out_size) {
  (void)in_sizes; (void)n_in; (void)out_size;
  Ptrs P;
  P.x = (const __nv_bfloat16*)d_in[0]; P.wqkv = (const __nv_bfloat16*)d_in[1]; P.wo = (const __nv_bfloat16*)d_in[2];
  P.wr = (const __nv_bfloat16*)d_in[4]; P.wg = (const __nv_bfloat16*)d_in[5]; P.wu = (const __nv_bfloat16*)d_in[6];
  P.wd = (const __nv_bfloat16*)d_in[7]; P.out = (__nv_bfloat16*)d_out;
  void* fn = nullptr;
  cudaDriverEntryPointQueryResult q;
  cudaGetDriverEntryPoint("cuTensorMapEncodeTiled", &fn, cudaEnableDefault, &q);
  EncodeFn enc = (EncodeFn)fn;
  CUtensorMap tmX, tmW, tmO, tmG, tmU, tmD, tmM, tmPG, tmPU, tmPD;
  make_map(enc, &tmX, P.x, D_, S_, D_, 64, 128, 0, CU_TENSOR_MAP_SWIZZLE_128B);
  make_map(enc, &tmW, P.wqkv, 3 * D_, D_, 3 * D_, 64, 64, 0, CU_TENSOR_MAP_SWIZZLE_128B);
  make_map(enc, &tmG, P.wg, F_, D_, F_, 32, 128, 0, CU_TENSOR_MAP_SWIZZLE_64B);
  make_map(enc, &tmU, P.wu, F_, D_, F_, 32, 128, 0, CU_TENSOR_MAP_SWIZZLE_64B);
  make_map(enc, &tmD, P.wd, D_, F_, 64, 64, 32, 4, CU_TENSOR_MAP_SWIZZLE_128B);
  make_map(enc, &tmPG, P.wg, F_, D_, F_, 8, 32, 0, CU_TENSOR_MAP_SWIZZLE_NONE);
  make_map(enc, &tmPU, P.wu, F_, D_, F_, 8, 32, 0, CU_TENSOR_MAP_SWIZZLE_NONE);
  make_map(enc, &tmPD, P.wd, 128, F_ * 8, 128, 8, 32, 0, CU_TENSOR_MAP_SWIZZLE_NONE, CU_TENSOR_MAP_L2_PROMOTION_L2_256B);
  for (int m = 0; m < 2; m++) {
    cuuint64_t dims[4] = {64, m ? 64u : 16u, m ? 16u : 64u, 16}, str[3] = {2 * D_, (m ? 128u : 32u) * D_, 128};
    cuuint32_t box[4] = {64, 16, 4, 2}, es[4] = {1, 1, 1, 1};
    enc(m ? &tmM : &tmO, CU_TENSOR_MAP_DATA_TYPE_BFLOAT16, 4, const_cast<__nv_bfloat16*>(P.wo), dims, str, box, es, CU_TENSOR_MAP_INTERLEAVE_NONE,
        CU_TENSOR_MAP_SWIZZLE_128B, CU_TENSOR_MAP_L2_PROMOTION_L2_128B, CU_TENSOR_MAP_FLOAT_OOB_FILL_NONE);
  }
  cudaFuncSetAttribute(fused_kernel, cudaFuncAttributeMaxDynamicSharedMemorySize, SMEM_BYTES);
  fused_kernel<<<NCTA, 384, SMEM_BYTES>>>(P, tmX, tmW, tmO, tmG, tmU, tmD, tmM, tmPG, tmPU, tmPD);
}
```

```cpp
#include <cuda_runtime.h>
#include <cuda.h>
#include <cuda_bf16.h>
#include <stdint.h>
#include <type_traits>

namespace {

constexpr int S_ = 2048, D_ = 1024, F_ = 3584;
constexpr int NCTA = 128, NFFN = 112;
constexpr uint32_t SENT = 0xFFFFFFFFu;
constexpr int SPIN_LIMIT = 1 << 20;

#define ADELAY 900
#define NPK 0x233333333333ull
#define KDELAY 700
#define SBAR 2
#define NOOUT 0
#define OHOLD 72
#define OUTEF 0
#define CUTS 2
#define EFO 0
#define EFWO 0
#define TMPF 1
#define INIF 0
#define DEV 0xFFEE
#define FDT 100
#define ASTEP 300
#define BDELAY 1100
#define LATEP 0x20
#define GEV 0xDCCB
#define PDS 2
#define D1POS 1
#define GUPOS 1
#define ASYM 2
#define GUP 2
#define PEEL 1
#define B6E 2
#define D2I 5
#define T1 1
#define T4 1
#define QX 0
#define B6H 2
#define XWPF 1
#define PD0 2
#define PDT 60
#define KORD 0xBA9F87E6D54C3210ull
#define SDELAY 450
#define LDELAY 500
#define NOSPEC 0
#define LOCK 1
#define STLD 2
#define RELK 1
#define PERT 5
#define QHOLD 3
#define CDELAY 0
#define YDELAY 500
#define EFX 0
#define EFW 1
#define EFF 1
#define GDELAY 800
#define PFST 1
#define OPOS 0x4411
#define B2POS 1
constexpr uint32_t STAGE_B = 57344;
__host__ __device__ constexpr uint32_t xoff(int s, int w) { return ((0x87CA3651u >> (4 * (s + 4 * w))) & 15) * 16384; }
__host__ __device__ constexpr uint32_t woff(int s) { return (s < 2 ? 9 * 16384 : 0) + (s & 1) * 8192; }
constexpr uint32_t WSTR = 32768;
constexpr uint32_t OFF_BARS = 229376;
constexpr uint32_t OFF_COLSUM = 229632;
constexpr uint32_t OFF_STATS = 230400;
constexpr uint32_t SMEM_BYTES = 232448;
constexpr uint32_t B_FULL = 0, B_EMPTY = 32, B_AUX = 64, B_SEL2 = 72, B_KVL = 80, B_FULL3 = 88, B_SW = 216, B_OUT = 224, B_LATE = 232, B_SEL = B_FULL + 8, B_FFN = 240;
__host__ __device__ constexpr uint32_t o3(int p) { return p * 8 + (p & 8) * 8; }
__host__ __device__ constexpr uint32_t bar3(int i) { return OFF_STATS + 1024 + (i >> 3) * 128 + ((i & 32) ? 0 : 64) + (i & 7) * 8; }
constexpr uint32_t SLOT_B = 16384;
constexpr uint32_t sb = 1024;
constexpr uint32_t bars = sb + OFF_BARS;
constexpr uint64_t WO_SLOTS = 0x8794208794208794ull;
constexpr uint32_t GU_SLOTS = 0x35356161u, D_SLOTS = 0x9420;
constexpr uint32_t HST = 7 * SLOT_B;
constexpr uint32_t OFF_LNP = OFF_STATS;
constexpr uint32_t OFF_MSC = OFF_COLSUM + 512;
constexpr uint32_t OFF_XS = 10 * SLOT_B;
constexpr uint32_t OFF_KVB = 2 * SLOT_B + 8192;

struct Scratch {
  uint4 st1[64 * 48];
  uint4 csp[16 * 8 * 48];
  uint4 kvp[16 * 2304];
  uint4 obuf[32 * 64 * 128];
  uint4 st2[S_];
  uint32_t pred[S_];
  uint4 cst[8 * 32];
  uint4 hsel[64 * 128];
  uint32_t cand[8 * 32];
  uint4 ybuf[NCTA * NFFN * 4];
  unsigned epoch;
};
__device__ __align__(1024) Scratch G;
#define TS_DECL
#define TS(i)
#define TSG(i)
#define TSV(i, v)
#define TS_DUMP(slot)
#define PTS(i)

__device__ __forceinline__ uint32_t smem_u32(const void* p) { return (uint32_t)__cvta_generic_to_shared(p); }
__device__ __forceinline__ void mbar_init(uint32_t bar, uint32_t cnt) { asm volatile("mbarrier.init.shared::cta.b64 [%0], %1;" :: "r"(bar), "r"(cnt) : "memory"); }
__device__ __forceinline__ void mbar_expect_tx(uint32_t bar, uint32_t bytes) { asm volatile("mbarrier.arrive.expect_tx.shared::cta.b64 _, [%0], %1;" :: "r"(bar), "r"(bytes) : "memory"); }
__device__ __forceinline__ void mbar_arrive(uint32_t bar) { asm volatile("mbarrier.arrive.shared::cta.b64 _, [%0];" :: "r"(bar) : "memory"); }
#define SPINCHK(it, code) if ((it) > SPIN_LIMIT) break
__device__ __forceinline__ void mbar_wait(uint32_t bar, uint32_t parity) {
  asm volatile("{\n.reg .pred p, q;\n.reg .u32 c;\nmov.u32 c, 0;\n"
               "WL:\nmbarrier.try_wait.parity.shared::cta.b64 p, [%0], %1;\nadd.u32 c, c, 1;\nsetp.lt.u32 q, c, 1048576;\n"
               "not.pred p, p;\nand.pred p, p, q;\n@p bra WL;\n}" :: "r"(bar), "r"(parity) : "memory");
}
__device__ __forceinline__ uint64_t l2_stream() { uint64_t p; asm("createpolicy.fractional.L2::evict_first.b64 %0, 1.0;" : "=l"(p)); return p; }
__device__ __forceinline__ void tma_2d(uint32_t dst, const CUtensorMap* tm, int c0, int c1, uint32_t bar, bool stream) {
  if (stream) asm volatile("cp.async.bulk.tensor.2d.shared::cluster.global.mbarrier::complete_tx::bytes.L2::cache_hint [%0], [%1, {%3, %4}], [%2], %5;"
                           :: "r"(dst), "l"(tm), "r"(bar), "r"(c0), "r"(c1), "l"(l2_stream()) : "memory");
  else asm volatile("cp.async.bulk.tensor.2d.shared::cluster.global.mbarrier::complete_tx::bytes [%0], [%1, {%3, %4}], [%2];"
                    :: "r"(dst), "l"(tm), "r"(bar), "r"(c0), "r"(c1) : "memory");
}
__device__ __forceinline__ void tma_3d(uint32_t dst, const CUtensorMap* tm, int c0, int c1, int c2, uint32_t bar, bool stream) {
  if (stream) asm volatile("cp.async.bulk.tensor.3d.shared::cluster.global.mbarrier::complete_tx::bytes.L2::cache_hint [%0], [%1, {%3, %4, %5}], [%2], %6;"
                           :: "r"(dst), "l"(tm), "r"(bar), "r"(c0), "r"(c1), "r"(c2), "l"(l2_stream()) : "memory");
  else asm volatile("cp.async.bulk.tensor.3d.shared::cluster.global.mbarrier::complete_tx::bytes [%0], [%1, {%3, %4, %5}], [%2];"
                    :: "r"(dst), "l"(tm), "r"(bar), "r"(c0), "r"(c1), "r"(c2) : "memory");
}
__device__ __forceinline__ void tma_2d_mc(uint32_t dst, const CUtensorMap* tm, int c0, int c1, uint32_t bar, bool stream) {
  if (stream) asm volatile("cp.async.bulk.tensor.2d.shared::cluster.global.mbarrier::complete_tx::bytes.multicast::cluster.L2::cache_hint [%0], [%1, {%3, %4}], [%2], %5, %6;"
                           :: "r"(dst), "l"(tm), "r"(bar), "r"(c0), "r"(c1), "h"((uint16_t)3), "l"(l2_stream()) : "memory");
  else asm volatile("cp.async.bulk.tensor.2d.shared::cluster.global.mbarrier::complete_tx::bytes.multicast::cluster [%0], [%1, {%3, %4}], [%2], %5;"
                    :: "r"(dst), "l"(tm), "r"(bar), "r"(c0), "r"(c1), "h"((uint16_t)3) : "memory");
}
__device__ __forceinline__ bool elect_one() {
  uint32_t p;
  asm volatile("{\n.reg .pred q;\nelect.sync _|q, 0xFFFFFFFF;\nselp.u32 %0, 1, 0, q;\n}" : "=r"(p));
  return p;
}
__device__ __forceinline__ void bulk_load_mc(uint32_t dst, const void* src, uint32_t bar, uint16_t mask) {
  if (EFO) asm volatile("cp.async.bulk.shared::cluster.global.mbarrier::complete_tx::bytes.multicast::cluster.L2::cache_hint [%0], [%1], 8192, [%2], %3, %4;"
               :: "r"(dst), "l"(src), "r"(bar), "h"(mask), "l"(l2_stream()) : "memory");
  else asm volatile("cp.async.bulk.shared::cluster.global.mbarrier::complete_tx::bytes.multicast::cluster [%0], [%1], 8192, [%2], %3;"
               :: "r"(dst), "l"(src), "r"(bar), "h"(mask) : "memory");
}
__device__ __forceinline__ void bulk_load(uint32_t dst, const void* src, uint32_t bytes, uint32_t bar) {
  asm volatile("cp.async.bulk.shared::cluster.global.mbarrier::complete_tx::bytes [%0], [%1], %2, [%3];" :: "r"(dst), "l"(src), "r"(bytes), "r"(bar) : "memory");
}
__device__ __forceinline__ void mbar_arrive_rem(uint32_t bar) { asm volatile("mbarrier.arrive.shared::cluster.b64 _, [%0];" :: "r"(bar) : "memory"); }
template <uint32_t O> __device__ __forceinline__ void ldsm4_o(uint32_t addr, uint32_t& a, uint32_t& b, uint32_t& c, uint32_t& d) {
  asm volatile("ldmatrix.sync.aligned.m8n8.x4.shared.b16 {%0,%1,%2,%3}, [%4+%5];" : "=r"(a), "=r"(b), "=r"(c), "=r"(d) : "r"(addr), "n"(O) : "memory");
}
template <uint32_t O> __device__ __forceinline__ void ldsm4t_o(uint32_t addr, uint32_t (&r)[4]) {
  asm volatile("ldmatrix.sync.aligned.m8n8.x4.trans.shared.b16 {%0,%1,%2,%3}, [%4+%5];" : "=r"(r[0]), "=r"(r[1]), "=r"(r[2]), "=r"(r[3]) : "r"(addr), "n"(O) : "memory");
}
__device__ __forceinline__ void mma16816(float (&c)[4], const uint32_t (&a)[4], uint32_t b0, uint32_t b1) {
  asm("mma.sync.aligned.m16n8k16.row.col.f32.bf16.bf16.f32 {%0,%1,%2,%3}, {%4,%5,%6,%7}, {%8,%9}, {%0,%1,%2,%3};"
      : "+f"(c[0]), "+f"(c[1]), "+f"(c[2]), "+f"(c[3]) : "r"(a[0]), "r"(a[1]), "r"(a[2]), "r"(a[3]), "r"(b0), "r"(b1));
}
__device__ __forceinline__ void l2_prefetch(const void* p) { asm volatile("prefetch.global.L2 [%0];" :: "l"(p) : "memory"); }
__device__ __forceinline__ uint32_t clk() { uint32_t t; asm volatile("mov.u32 %0, %%clock;" : "=r"(t) :: "memory"); return t; }
__device__ __forceinline__ void delay(uint32_t t0, uint32_t n) { while (clk() - t0 < n) {} }
template <int ID> __device__ __forceinline__ void cut(uint32_t zero) { asm volatile("{\n.reg .pred p;\nsetp.eq.u32 p, %0, %1;\nCUT:\n@p nanosleep.u32 1;\n@p bra.uni CUT;\n}" :: "r"(zero), "n"(ID) : "memory"); }
__device__ __forceinline__ void tmap_prefetch(const CUtensorMap* tm) { asm volatile("prefetch.tensormap [%0];" :: "l"(tm) : "memory"); }
__device__ __forceinline__ void wg_fence() { asm volatile("wgmma.fence.sync.aligned;" ::: "memory"); }
__device__ __forceinline__ void wg_commit() { asm volatile("wgmma.commit_group.sync.aligned;" ::: "memory"); }
template <int N> __device__ __forceinline__ void wg_wait() { asm volatile("wgmma.wait_group.sync.aligned %0;" :: "n"(N) : "memory"); }
template <int N> __device__ __forceinline__ void pin(float (&d)[N]) {
#pragma unroll
  for (int i = 0; i < N; i++) asm volatile("" : "+f"(d[i]) :: "memory");
}
__device__ __forceinline__ void pin4(uint4& v) { asm volatile("" : "+r"(v.x), "+r"(v.y), "+r"(v.z), "+r"(v.w) :: "memory"); }
template <uint32_t SBO, uint32_t SWZ> __device__ __forceinline__ uint64_t dsc(uint32_t lo) { return ((uint64_t)((SBO >> 4) | (SWZ << 30)) << 32) | lo; }
__host__ __device__ constexpr uint32_t dlo(uint32_t addr, uint32_t lbo) { return (addr >> 4) | ((lbo >> 4) << 16); }
__device__ __forceinline__ void bar_sync(int id, int n) { asm volatile("bar.sync %0, %1;" :: "r"(id), "r"(n) : "memory"); }
__device__ __forceinline__ void bar_arrive(int id, int n) { asm volatile("bar.arrive %0, %1;" :: "r"(id), "r"(n) : "memory"); }
__device__ __forceinline__ void fence_async_smem() { asm volatile("fence.proxy.async.shared::cta;" ::: "memory"); }
__device__ __forceinline__ void fence_gpu() { asm volatile("fence.acq_rel.gpu;" ::: "memory"); }
__device__ __forceinline__ uint4 ld_cg4(const void* p) { uint4 v; asm volatile("ld.global.cg.v4.u32 {%0,%1,%2,%3}, [%4];" : "=r"(v.x), "=r"(v.y), "=r"(v.z), "=r"(v.w) : "l"(p) : "memory"); return v; }
__device__ __forceinline__ uint4 ld_rlx4(const void* p) { uint4 v; asm volatile("ld.relaxed.gpu.global.v4.u32 {%0,%1,%2,%3}, [%4];" : "=r"(v.x), "=r"(v.y), "=r"(v.z), "=r"(v.w) : "l"(p) : "memory"); return v; }
__device__ __forceinline__ uint32_t ld_rlx(const void* p) { uint32_t v; asm volatile("ld.relaxed.gpu.global.u32 %0, [%1];" : "=r"(v) : "l"(p) : "memory"); return v; }
__device__ __forceinline__ void st_rlx4(void* p, uint4 v) { asm volatile("st.relaxed.gpu.global.v4.u32 [%0], {%1,%2,%3,%4};" :: "l"(p), "r"(v.x), "r"(v.y), "r"(v.z), "r"(v.w) : "memory"); }
__device__ __forceinline__ void st_rlx2(void* p, uint32_t a, uint32_t b) { asm volatile("st.relaxed.gpu.global.v2.u32 [%0], {%1,%2};" :: "l"(p), "r"(a), "r"(b) : "memory"); }
__device__ __forceinline__ void st_rlx(void* p, uint32_t a) { asm volatile("st.relaxed.gpu.global.u32 [%0], %1;" :: "l"(p), "r"(a) : "memory"); }
__device__ __forceinline__ void red4(bool on, void* p, float a, float b, float c, float d) {
  asm volatile("{\n.reg .pred q;\nsetp.ne.b32 q, %5, 0;\n@q red.relaxed.gpu.global.add.v4.f32 [%0], {%1,%2,%3,%4};\n}" :: "l"(p), "f"(a), "f"(b), "f"(c), "f"(d), "r"((int)on) : "memory");
}
__device__ __forceinline__ uint32_t pack2(float lo, float hi) { uint32_t r; asm("cvt.rn.bf16x2.f32 %0, %1, %2;" : "=r"(r) : "f"(hi), "f"(lo)); return r; }
__device__ __forceinline__ float bf_lo(uint32_t v) { return __uint_as_float(v << 16); }
__device__ __forceinline__ float bf_hi(uint32_t v) { return __uint_as_float(v & 0xFFFF0000u); }
__device__ __forceinline__ void stsm4(uint32_t addr, uint32_t a, uint32_t b, uint32_t c, uint32_t d) {
  asm volatile("stmatrix.sync.aligned.m8n8.x4.shared.b16 [%0], {%1,%2,%3,%4};" :: "r"(addr), "r"(a), "r"(b), "r"(c), "r"(d) : "memory");
}
template <uint32_t O> __device__ __forceinline__ void stsm4_o(uint32_t addr, uint32_t a, uint32_t b, uint32_t c, uint32_t d) {
  asm volatile("stmatrix.sync.aligned.m8n8.x4.shared.b16 [%0+%5], {%1,%2,%3,%4};" :: "r"(addr), "r"(a), "r"(b), "r"(c), "r"(d), "n"(O) : "memory");
}
__device__ __forceinline__ void sts4(uint32_t addr, uint32_t a, uint32_t b, uint32_t c, uint32_t d) { asm volatile("st.shared.v4.u32 [%0], {%1,%2,%3,%4};" :: "r"(addr), "r"(a), "r"(b), "r"(c), "r"(d) : "memory"); }
__device__ __forceinline__ void sts2f(uint32_t addr, float a, float b) { asm volatile("st.shared.v2.f32 [%0], {%1,%2};" :: "r"(addr), "f"(a), "f"(b) : "memory"); }
__device__ __forceinline__ void sts1(uint32_t addr, uint32_t a) { asm volatile("st.shared.u32 [%0], %1;" :: "r"(addr), "r"(a) : "memory"); }
__device__ __forceinline__ float2 lds2f(uint32_t addr) { float2 v; asm volatile("ld.shared.v2.f32 {%0,%1}, [%2];" : "=f"(v.x), "=f"(v.y) : "r"(addr) : "memory"); return v; }
template <uint32_t O> __device__ __forceinline__ float2 lds2f_o(uint32_t addr) { float2 v; asm volatile("ld.shared.v2.f32 {%0,%1}, [%2+%3];" : "=f"(v.x), "=f"(v.y) : "r"(addr), "n"(O) : "memory"); return v; }
template <int I, int N, class F> __device__ __forceinline__ void static_for(F&& f) { if constexpr (I < N) { f(std::integral_constant<int, I>{}); static_for<I + 1, N>(f); } }
__device__ __forceinline__ uint4 lds4(uint32_t addr) { uint4 v; asm volatile("ld.shared.v4.u32 {%0,%1,%2,%3}, [%4];" : "=r"(v.x), "=r"(v.y), "=r"(v.z), "=r"(v.w) : "r"(addr) : "memory"); return v; }
__device__ __forceinline__ uint32_t lds1(uint32_t addr) { uint32_t v; asm volatile("ld.shared.u32 %0, [%1];" : "=r"(v) : "r"(addr) : "memory"); return v; }
__device__ __forceinline__ float ex2(float x) { float y; asm("ex2.approx.ftz.f32 %0, %1;" : "=f"(y) : "f"(x)); return y; }
__device__ __forceinline__ uint32_t max4(uint32_t m, const uint4& v) { return __vimax3_u32(__vimax3_u32(m, v.x, v.y), v.z, v.w); }
__device__ __forceinline__ float rsq(float x) { float y; asm("rsqrt.approx.ftz.f32 %0, %1;" : "=f"(y) : "f"(x)); return y; }
__device__ __forceinline__ float rcp(float x) { float y; asm("rcp.approx.ftz.f32 %0, %1;" : "=f"(y) : "f"(x)); return y; }
__device__ __forceinline__ uint2 ld_rlx2(const void* p) { uint2 v; asm volatile("ld.relaxed.gpu.global.v2.u32 {%0,%1}, [%2];" : "=r"(v.x), "=r"(v.y) : "l"(p) : "memory"); return v; }
template <uint32_t O> __device__ __forceinline__ uint4 lds4_o(uint32_t addr) { uint4 v; asm volatile("ld.shared.v4.u32 {%0,%1,%2,%3}, [%4+%5];" : "=r"(v.x), "=r"(v.y), "=r"(v.z), "=r"(v.w) : "r"(addr), "n"(O) : "memory"); return v; }
__device__ __forceinline__ uint32_t hadd2(uint32_t a, uint32_t b) { uint32_t r; asm("add.rn.bf16x2 %0, %1, %2;" : "=r"(r) : "r"(a), "r"(b)); return r; }
__device__ __forceinline__ uint4 hadd8(const uint4& a, const uint4& b) { return make_uint4(hadd2(a.x, b.x), hadd2(a.y, b.y), hadd2(a.z, b.z), hadd2(a.w, b.w)); }
__device__ __forceinline__ bool hnan(uint32_t a) { return (a & 0x7FFF0000u) > 0x7F800000u; }
__device__ __forceinline__ uint32_t hfma2(uint32_t a, uint32_t b, uint32_t c) { uint32_t r; asm("fma.rn.bf16x2 %0, %1, %2, %3;" : "=r"(r) : "r"(a), "r"(b), "r"(c)); return r; }
__device__ __forceinline__ uint32_t ordered(float v) { const uint32_t u = __float_as_uint(v); return u ^ ((uint32_t)((int)u >> 31) | 0x80000000u); }
__device__ __forceinline__ uint32_t route(const uint4& v, float sw, int row, float2& pr) {
  const float mean = __uint_as_float(v.x) * (1.f / D_);
  pr.x = rsq(fmaxf(fmaf(-mean, mean, __uint_as_float(v.y) * (1.f / D_)), 0.f) + 1e-5f);
  pr.y = -mean * pr.x;
  return min(ordered(pr.x * fmaf(-mean, sw, __uint_as_float(v.z))) & ~2047u, 0xFFFFF000u) | (2047 - row);
}
__device__ __forceinline__ uint2 top2(uint32_t a, uint32_t b, uint32_t c, uint32_t d) {
  const uint32_t h0 = max(a, b), h1 = max(c, d), h = max(h0, h1), l = __vimax3_u32(min(h0, h1), min(a, b), min(c, d));
  const uint32_t m1 = __reduce_max_sync(~0u, h);
  return make_uint2(m1, __reduce_max_sync(~0u, h == m1 ? l : h));
}
__device__ __forceinline__ uint32_t hmul2(uint32_t a, uint32_t b) { uint32_t r; asm("mul.rn.bf16x2 %0, %1, %2;" : "=r"(r) : "r"(a), "r"(b)); return r; }
__device__ __forceinline__ uint32_t phi2(float u0, float u1, uint32_t r2, float rl) {
  uint32_t p, r;
  asm("cvt.rn.relu.bf16x2.f32 %0, %1, %2;" : "=r"(p) : "f"(u1), "f"(u0));
  asm("fma.rn.bf16x2 %0, %1, %2, %3;" : "=r"(r) : "r"(p), "r"(r2), "r"(pack2(__saturatef(ex2(u0 * rl) + 1e-6f), __saturatef(ex2(u1 * rl) + 1e-6f))));
  return r;
}

template<int TA, int TB, int OFF, int SZ> __device__ __forceinline__ void wgmma_n192_ss(float (&d)[SZ], uint64_t da, uint64_t db, int scale_d) {
  asm volatile("{\n.reg .pred p;\nsetp.ne.b32 p, %98, 0;\n"
    "wgmma.mma_async.sync.aligned.m64n192k16.f32.bf16.bf16 {%0,%1,%2,%3,%4,%5,%6,%7,%8,%9,%10,%11,%12,%13,%14,%15,%16,%17,%18,%19,%20,%21,%22,%23,%24,%25,%26,%27,%28,%29,%30,%31,%32,%33,%34,%35,%36,%37,%38,%39,%40,%41,%42,%43,%44,%45,%46,%47,%48,%49,%50,%51,%52,%53,%54,%55,%56,%57,%58,%59,%60,%61,%62,%63,%64,%65,%66,%67,%68,%69,%70,%71,%72,%73,%74,%75,%76,%77,%78,%79,%80,%81,%82,%83,%84,%85,%86,%87,%88,%89,%90,%91,%92,%93,%94,%95}, %96, %97, p, 1, 1, %99, %100;\n}\n"
    : "+f"(d[OFF+0]), "+f"(d[OFF+1]), "+f"(d[OFF+2]), "+f"(d[OFF+3]), "+f"(d[OFF+4]), "+f"(d[OFF+5]), "+f"(d[OFF+6]), "+f"(d[OFF+7]),
      "+f"(d[OFF+8]), "+f"(d[OFF+9]), "+f"(d[OFF+10]), "+f"(d[OFF+11]), "+f"(d[OFF+12]), "+f"(d[OFF+13]), "+f"(d[OFF+14]), "+f"(d[OFF+15]),
      "+f"(d[OFF+16]), "+f"(d[OFF+17]), "+f"(d[OFF+18]), "+f"(d[OFF+19]), "+f"(d[OFF+20]), "+f"(d[OFF+21]), "+f"(d[OFF+22]), "+f"(d[OFF+23]),
      "+f"(d[OFF+24]), "+f"(d[OFF+25]), "+f"(d[OFF+26]), "+f"(d[OFF+27]), "+f"(d[OFF+28]), "+f"(d[OFF+29]), "+f"(d[OFF+30]), "+f"(d[OFF+31]),
      "+f"(d[OFF+32]), "+f"(d[OFF+33]), "+f"(d[OFF+34]), "+f"(d[OFF+35]), "+f"(d[OFF+36]), "+f"(d[OFF+37]), "+f"(d[OFF+38]), "+f"(d[OFF+39]),
      "+f"(d[OFF+40]), "+f"(d[OFF+41]), "+f"(d[OFF+42]), "+f"(d[OFF+43]), "+f"(d[OFF+44]), "+f"(d[OFF+45]), "+f"(d[OFF+46]), "+f"(d[OFF+47]),
      "+f"(d[OFF+48]), "+f"(d[OFF+49]), "+f"(d[OFF+50]), "+f"(d[OFF+51]), "+f"(d[OFF+52]), "+f"(d[OFF+53]), "+f"(d[OFF+54]), "+f"(d[OFF+55]),
      "+f"(d[OFF+56]), "+f"(d[OFF+57]), "+f"(d[OFF+58]), "+f"(d[OFF+59]), "+f"(d[OFF+60]), "+f"(d[OFF+61]), "+f"(d[OFF+62]), "+f"(d[OFF+63]),
      "+f"(d[OFF+64]), "+f"(d[OFF+65]), "+f"(d[OFF+66]), "+f"(d[OFF+67]), "+f"(d[OFF+68]), "+f"(d[OFF+69]), "+f"(d[OFF+70]), "+f"(d[OFF+71]),
      "+f"(d[OFF+72]), "+f"(d[OFF+73]), "+f"(d[OFF+74]), "+f"(d[OFF+75]), "+f"(d[OFF+76]), "+f"(d[OFF+77]), "+f"(d[OFF+78]), "+f"(d[OFF+79]),
      "+f"(d[OFF+80]), "+f"(d[OFF+81]), "+f"(d[OFF+82]), "+f"(d[OFF+83]), "+f"(d[OFF+84]), "+f"(d[OFF+85]), "+f"(d[OFF+86]), "+f"(d[OFF+87]),
      "+f"(d[OFF+88]), "+f"(d[OFF+89]), "+f"(d[OFF+90]), "+f"(d[OFF+91]), "+f"(d[OFF+92]), "+f"(d[OFF+93]), "+f"(d[OFF+94]), "+f"(d[OFF+95])
    : "l"(da), "l"(db), "r"(scale_d), "n"(TA), "n"(TB));
}
template<int TA, int TB, int OFF, int SZ> __device__ __forceinline__ void wgmma_n128_ss(float (&d)[SZ], uint64_t da, uint64_t db, int scale_d) {
  asm volatile("{\n.reg .pred p;\nsetp.ne.b32 p, %66, 0;\n"
    "wgmma.mma_async.sync.aligned.m64n128k16.f32.bf16.bf16 {%0,%1,%2,%3,%4,%5,%6,%7,%8,%9,%10,%11,%12,%13,%14,%15,%16,%17,%18,%19,%20,%21,%22,%23,%24,%25,%26,%27,%28,%29,%30,%31,%32,%33,%34,%35,%36,%37,%38,%39,%40,%41,%42,%43,%44,%45,%46,%47,%48,%49,%50,%51,%52,%53,%54,%55,%56,%57,%58,%59,%60,%61,%62,%63}, %64, %65, p, 1, 1, %67, %68;\n}\n"
    : "+f"(d[OFF+0]), "+f"(d[OFF+1]), "+f"(d[OFF+2]), "+f"(d[OFF+3]), "+f"(d[OFF+4]), "+f"(d[OFF+5]), "+f"(d[OFF+6]), "+f"(d[OFF+7]),
      "+f"(d[OFF+8]), "+f"(d[OFF+9]), "+f"(d[OFF+10]), "+f"(d[OFF+11]), "+f"(d[OFF+12]), "+f"(d[OFF+13]), "+f"(d[OFF+14]), "+f"(d[OFF+15]),
      "+f"(d[OFF+16]), "+f"(d[OFF+17]), "+f"(d[OFF+18]), "+f"(d[OFF+19]), "+f"(d[OFF+20]), "+f"(d[OFF+21]), "+f"(d[OFF+22]), "+f"(d[OFF+23]),
      "+f"(d[OFF+24]), "+f"(d[OFF+25]), "+f"(d[OFF+26]), "+f"(d[OFF+27]), "+f"(d[OFF+28]), "+f"(d[OFF+29]), "+f"(d[OFF+30]), "+f"(d[OFF+31]),
      "+f"(d[OFF+32]), "+f"(d[OFF+33]), "+f"(d[OFF+34]), "+f"(d[OFF+35]), "+f"(d[OFF+36]), "+f"(d[OFF+37]), "+f"(d[OFF+38]), "+f"(d[OFF+39]),
      "+f"(d[OFF+40]), "+f"(d[OFF+41]), "+f"(d[OFF+42]), "+f"(d[OFF+43]), "+f"(d[OFF+44]), "+f"(d[OFF+45]), "+f"(d[OFF+46]), "+f"(d[OFF+47]),
      "+f"(d[OFF+48]), "+f"(d[OFF+49]), "+f"(d[OFF+50]), "+f"(d[OFF+51]), "+f"(d[OFF+52]), "+f"(d[OFF+53]), "+f"(d[OFF+54]), "+f"(d[OFF+55]),
      "+f"(d[OFF+56]), "+f"(d[OFF+57]), "+f"(d[OFF+58]), "+f"(d[OFF+59]), "+f"(d[OFF+60]), "+f"(d[OFF+61]), "+f"(d[OFF+62]), "+f"(d[OFF+63])
    : "l"(da), "l"(db), "r"(scale_d), "n"(TA), "n"(TB));
}
template<int TA, int TB, int OFF, int SZ> __device__ __forceinline__ void wgmma_n64_ss(float (&d)[SZ], uint64_t da, uint64_t db, int scale_d) {
  asm volatile("{\n.reg .pred p;\nsetp.ne.b32 p, %34, 0;\n"
    "wgmma.mma_async.sync.aligned.m64n64k16.f32.bf16.bf16 {%0,%1,%2,%3,%4,%5,%6,%7,%8,%9,%10,%11,%12,%13,%14,%15,%16,%17,%18,%19,%20,%21,%22,%23,%24,%25,%26,%27,%28,%29,%30,%31}, %32, %33, p, 1, 1, %35, %36;\n}\n"
    : "+f"(d[OFF+0]), "+f"(d[OFF+1]), "+f"(d[OFF+2]), "+f"(d[OFF+3]), "+f"(d[OFF+4]), "+f"(d[OFF+5]), "+f"(d[OFF+6]), "+f"(d[OFF+7]),
      "+f"(d[OFF+8]), "+f"(d[OFF+9]), "+f"(d[OFF+10]), "+f"(d[OFF+11]), "+f"(d[OFF+12]), "+f"(d[OFF+13]), "+f"(d[OFF+14]), "+f"(d[OFF+15]),
      "+f"(d[OFF+16]), "+f"(d[OFF+17]), "+f"(d[OFF+18]), "+f"(d[OFF+19]), "+f"(d[OFF+20]), "+f"(d[OFF+21]), "+f"(d[OFF+22]), "+f"(d[OFF+23]),
      "+f"(d[OFF+24]), "+f"(d[OFF+25]), "+f"(d[OFF+26]), "+f"(d[OFF+27]), "+f"(d[OFF+28]), "+f"(d[OFF+29]), "+f"(d[OFF+30]), "+f"(d[OFF+31])
    : "l"(da), "l"(db), "r"(scale_d), "n"(TA), "n"(TB));
}
template<int TB, int OFF, int SZ> __device__ __forceinline__ void wgmma_n64_rs(float (&d)[SZ], uint32_t a0, uint32_t a1, uint32_t a2, uint32_t a3, uint64_t db, int scale_d) {
  asm volatile("{\n.reg .pred p;\nsetp.ne.b32 p, %37, 0;\n"
    "wgmma.mma_async.sync.aligned.m64n64k16.f32.bf16.bf16 {%0,%1,%2,%3,%4,%5,%6,%7,%8,%9,%10,%11,%12,%13,%14,%15,%16,%17,%18,%19,%20,%21,%22,%23,%24,%25,%26,%27,%28,%29,%30,%31}, {%32,%33,%34,%35}, %36, p, 1, 1, %38;\n}\n"
    : "+f"(d[OFF+0]), "+f"(d[OFF+1]), "+f"(d[OFF+2]), "+f"(d[OFF+3]), "+f"(d[OFF+4]), "+f"(d[OFF+5]), "+f"(d[OFF+6]), "+f"(d[OFF+7]),
      "+f"(d[OFF+8]), "+f"(d[OFF+9]), "+f"(d[OFF+10]), "+f"(d[OFF+11]), "+f"(d[OFF+12]), "+f"(d[OFF+13]), "+f"(d[OFF+14]), "+f"(d[OFF+15]),
      "+f"(d[OFF+16]), "+f"(d[OFF+17]), "+f"(d[OFF+18]), "+f"(d[OFF+19]), "+f"(d[OFF+20]), "+f"(d[OFF+21]), "+f"(d[OFF+22]), "+f"(d[OFF+23]),
      "+f"(d[OFF+24]), "+f"(d[OFF+25]), "+f"(d[OFF+26]), "+f"(d[OFF+27]), "+f"(d[OFF+28]), "+f"(d[OFF+29]), "+f"(d[OFF+30]), "+f"(d[OFF+31])
    : "r"(a0), "r"(a1), "r"(a2), "r"(a3), "l"(db), "r"(scale_d), "n"(TB));
}
template<int TA, int TB, int OFF, int SZ> __device__ __forceinline__ void wgmma_n72_ss(float (&d)[SZ], uint64_t da, uint64_t db, int scale_d) {
  asm volatile("{\n.reg .pred p;\nsetp.ne.b32 p, %38, 0;\n"
    "wgmma.mma_async.sync.aligned.m64n72k16.f32.bf16.bf16 {%0,%1,%2,%3,%4,%5,%6,%7,%8,%9,%10,%11,%12,%13,%14,%15,%16,%17,%18,%19,%20,%21,%22,%23,%24,%25,%26,%27,%28,%29,%30,%31,%32,%33,%34,%35}, %36, %37, p, 1, 1, %39, %40;\n}\n"
    : "+f"(d[OFF+0]), "+f"(d[OFF+1]), "+f"(d[OFF+2]), "+f"(d[OFF+3]), "+f"(d[OFF+4]), "+f"(d[OFF+5]), "+f"(d[OFF+6]), "+f"(d[OFF+7]),
      "+f"(d[OFF+8]), "+f"(d[OFF+9]), "+f"(d[OFF+10]), "+f"(d[OFF+11]), "+f"(d[OFF+12]), "+f"(d[OFF+13]), "+f"(d[OFF+14]), "+f"(d[OFF+15]),
      "+f"(d[OFF+16]), "+f"(d[OFF+17]), "+f"(d[OFF+18]), "+f"(d[OFF+19]), "+f"(d[OFF+20]), "+f"(d[OFF+21]), "+f"(d[OFF+22]), "+f"(d[OFF+23]),
      "+f"(d[OFF+24]), "+f"(d[OFF+25]), "+f"(d[OFF+26]), "+f"(d[OFF+27]), "+f"(d[OFF+28]), "+f"(d[OFF+29]), "+f"(d[OFF+30]), "+f"(d[OFF+31]),
      "+f"(d[OFF+32]), "+f"(d[OFF+33]), "+f"(d[OFF+34]), "+f"(d[OFF+35])
    : "l"(da), "l"(db), "r"(scale_d), "n"(TA), "n"(TB));
}
template<int TB, int OFF, int SZ> __device__ __forceinline__ void wgmma_n40_rs(float (&d)[SZ], uint32_t a0, uint32_t a1, uint32_t a2, uint32_t a3, uint64_t db, int scale_d) {
  asm volatile("{\n.reg .pred p;\nsetp.ne.b32 p, %25, 0;\n"
    "wgmma.mma_async.sync.aligned.m64n40k16.f32.bf16.bf16 {%0,%1,%2,%3,%4,%5,%6,%7,%8,%9,%10,%11,%12,%13,%14,%15,%16,%17,%18,%19}, {%20,%21,%22,%23}, %24, p, 1, 1, %26;\n}\n"
    : "+f"(d[OFF+0]), "+f"(d[OFF+1]), "+f"(d[OFF+2]), "+f"(d[OFF+3]), "+f"(d[OFF+4]), "+f"(d[OFF+5]), "+f"(d[OFF+6]), "+f"(d[OFF+7]),
      "+f"(d[OFF+8]), "+f"(d[OFF+9]), "+f"(d[OFF+10]), "+f"(d[OFF+11]), "+f"(d[OFF+12]), "+f"(d[OFF+13]), "+f"(d[OFF+14]), "+f"(d[OFF+15]),
      "+f"(d[OFF+16]), "+f"(d[OFF+17]), "+f"(d[OFF+18]), "+f"(d[OFF+19])
    : "r"(a0), "r"(a1), "r"(a2), "r"(a3), "l"(db), "r"(scale_d), "n"(TB));
}
template<int TB, int OFF, int SZ> __device__ __forceinline__ void wgmma_n128_rs(float (&d)[SZ], uint32_t a0, uint32_t a1, uint32_t a2, uint32_t a3, uint64_t db, int scale_d) {
  asm volatile("{\n.reg .pred p;\nsetp.ne.b32 p, %69, 0;\n"
    "wgmma.mma_async.sync.aligned.m64n128k16.f32.bf16.bf16 {%0,%1,%2,%3,%4,%5,%6,%7,%8,%9,%10,%11,%12,%13,%14,%15,%16,%17,%18,%19,%20,%21,%22,%23,%24,%25,%26,%27,%28,%29,%30,%31,%32,%33,%34,%35,%36,%37,%38,%39,%40,%41,%42,%43,%44,%45,%46,%47,%48,%49,%50,%51,%52,%53,%54,%55,%56,%57,%58,%59,%60,%61,%62,%63}, {%64,%65,%66,%67}, %68, p, 1, 1, %70;\n}\n"
    : "+f"(d[OFF+0]), "+f"(d[OFF+1]), "+f"(d[OFF+2]), "+f"(d[OFF+3]), "+f"(d[OFF+4]), "+f"(d[OFF+5]), "+f"(d[OFF+6]), "+f"(d[OFF+7]),
      "+f"(d[OFF+8]), "+f"(d[OFF+9]), "+f"(d[OFF+10]), "+f"(d[OFF+11]), "+f"(d[OFF+12]), "+f"(d[OFF+13]), "+f"(d[OFF+14]), "+f"(d[OFF+15]),
      "+f"(d[OFF+16]), "+f"(d[OFF+17]), "+f"(d[OFF+18]), "+f"(d[OFF+19]), "+f"(d[OFF+20]), "+f"(d[OFF+21]), "+f"(d[OFF+22]), "+f"(d[OFF+23]),
      "+f"(d[OFF+24]), "+f"(d[OFF+25]), "+f"(d[OFF+26]), "+f"(d[OFF+27]), "+f"(d[OFF+28]), "+f"(d[OFF+29]), "+f"(d[OFF+30]), "+f"(d[OFF+31]),
      "+f"(d[OFF+32]), "+f"(d[OFF+33]), "+f"(d[OFF+34]), "+f"(d[OFF+35]), "+f"(d[OFF+36]), "+f"(d[OFF+37]), "+f"(d[OFF+38]), "+f"(d[OFF+39]),
      "+f"(d[OFF+40]), "+f"(d[OFF+41]), "+f"(d[OFF+42]), "+f"(d[OFF+43]), "+f"(d[OFF+44]), "+f"(d[OFF+45]), "+f"(d[OFF+46]), "+f"(d[OFF+47]),
      "+f"(d[OFF+48]), "+f"(d[OFF+49]), "+f"(d[OFF+50]), "+f"(d[OFF+51]), "+f"(d[OFF+52]), "+f"(d[OFF+53]), "+f"(d[OFF+54]), "+f"(d[OFF+55]),
      "+f"(d[OFF+56]), "+f"(d[OFF+57]), "+f"(d[OFF+58]), "+f"(d[OFF+59]), "+f"(d[OFF+60]), "+f"(d[OFF+61]), "+f"(d[OFF+62]), "+f"(d[OFF+63])
    : "r"(a0), "r"(a1), "r"(a2), "r"(a3), "l"(db), "r"(scale_d), "n"(TB));
}

struct Ptrs { const __nv_bfloat16 *x, *wqkv, *wo, *wr, *wg, *wu, *wd; __nv_bfloat16* out; };

__global__ void __cluster_dims__(2, 1, 1) __launch_bounds__(384, 1) fused_kernel(const Ptrs P, const __grid_constant__ CUtensorMap tmX, const __grid_constant__ CUtensorMap tmW,
                                                       const __grid_constant__ CUtensorMap tmO, const __grid_constant__ CUtensorMap tmG,
                                                       const __grid_constant__ CUtensorMap tmU, const __grid_constant__ CUtensorMap tmD,
                                                       const __grid_constant__ CUtensorMap tmM, const __grid_constant__ CUtensorMap tmPG,
                                                       const __grid_constant__ CUtensorMap tmPU, const __grid_constant__ CUtensorMap tmPD) {
  extern __shared__ __align__(1024) uint8_t smem_raw[];
  if (TMPF && threadIdx.x == 0) { tmap_prefetch(&tmX); tmap_prefetch(&tmW); }
  const int tid = threadIdx.x, wid = __shfl_sync(~0u, tid >> 5, 0), wg = __shfl_sync(~0u, tid >> 7, 0), lane = tid & 31;
  const int pj = blockIdx.x >> 1, pi = pj - 36;
  const int b = (pj < 4 ? 32 + pj * 8 : pj < 36 ? pj - 4 : 33 + pi + ((pi * 37) >> 8)) * 2 + (blockIdx.x & 1);
  const int rb = b >> 4, cg = b & 15, hf = cg >> 3, c3 = cg & 7;
  const int jp = cg >> 1;
  const int fidx = jp == rb ? -1 : b - 2 * rb - (jp > rb ? 2 : 0);
  const uint32_t rank = b & 1, own = rank << 24;
  const uint32_t zero = gridDim.y - 1;
  const uint32_t sm = own + sb, mb = own + bars;
  const uint64_t chunks = 0x1765432FEDCBA980ull ^ ((cg & 8) * 0x1111111111111111ull) ^ ((cg & 6) * 0x1111111000000001ull) ^ ((cg & 1) * 0x1000000000000001ull);
  auto chunk_of = [&](int p) { return (int)(chunks >> (4 * p)) & 15; };
  const int kl = (jp & 3) * 256;
  auto k_of = [&](int kb) { return kb >= 12 ? kl + (kb - 12) * 64 : kb * 64 < kl ? kb * 64 : kb * 64 + 256; };
  auto load_w = [&](int kb) {
#pragma unroll
    for (int i = 0; i < 3; i++) tma_2d(sm + woff(kb & 3) + i * WSTR, &tmW, i * D_ + cg * 64, k_of(kb), mb + B_FULL + 8 * (kb & 3), EFW);
  };
  if (XWPF && tid >= 32 && tid < 128) {
    const int k0 = kl ? 0 : 256;
    if (tid < 56) l2_prefetch(P.wqkv + (k0 + rb * 8 + (lane & 7)) * 3072 + (lane >> 3) * 1024 + cg * 64);
    else if (tid >= 64 && (!kl || tid < 86)) l2_prefetch(P.x + (rb * 256 + (kl ? min((cg - 2 - 2 * hf) * 22 + lane, 255) : (hf * 2 + rank) * 64 + tid - 64)) * D_ + k0);
  }
  TS_DECL; TS(0); TSG(30);
  if (wid == 8) {
    if (elect_one()) {
      if (smem_u32(smem_raw) != sm) {
#pragma unroll
        for (int i = 0; i < PERT; i++) sts1(mb, lds1(mb));
        asm volatile("trap;");
      }
#pragma unroll
      for (int s = 0; s < 4; s++) mbar_init(mb + B_FULL + 8 * s, 1);
      asm volatile("fence.mbarrier_init.release.cluster;" ::: "memory");
      if (INIF) fence_async_smem();
    }
  } else if (wid == 9) {
    if (elect_one()) {
#pragma unroll
      for (int i = 4; i < 32; i++)
        if (i != 27) mbar_init(mb + 8 * i, i < 8 ? 8 : i == 8 ? 64 : i == 26 ? 2 : i == 29 ? 4 : 1);
      asm volatile("fence.mbarrier_init.release.cluster;" ::: "memory");
      if (INIF) fence_async_smem();
    }
  }
  __syncwarp();
  asm volatile("barrier.cluster.arrive.relaxed.aligned;" ::: "memory");
  if (wid == 8) {
    if (elect_one()) {
      mbar_expect_tx(mb + B_FULL, STAGE_B);
      tma_2d(sm + xoff(0, 0), &tmX, k_of(0), rb * 256, mb + B_FULL, EFX);
      tma_2d(sm + xoff(0, 1), &tmX, k_of(0), rb * 256 + 128, mb + B_FULL, EFX);
      load_w(0);
    }
    __syncwarp();
  }
  asm volatile("barrier.cluster.wait.aligned;" ::: "memory");

  if (wg == 2) {
    asm volatile("setmaxnreg.dec.sync.aligned.u32 56;");
    auto wait3 = [&](int i) { mbar_wait(sm + bar3(i), 0); };
    if (wid == 8) {
      if (elect_one()) {
        int np = fidx >= 0 ? 0 : 32;
        if (fidx >= 0) mbar_expect_tx(mb + B_FFN, 32 * 512);
#pragma unroll 1
        for (int kb = 1; kb < 16 - PEEL; kb++) {
          const uint32_t fb = mb + B_FULL + 8 * (kb & 3);
          mbar_wait(fb + B_EMPTY, ((kb >> 2) & 1) ^ 1);
          mbar_expect_tx(fb, STAGE_B);
          tma_2d_mc(sm + xoff(kb & 3, rank), &tmX, k_of(kb), rb * 256 + rank * 128, fb, EFX);
          load_w(kb);
          if (kb >= 12) asm volatile("mbarrier.arrive.shared::cta.b64 _, [%0], 7;" :: "r"(fb + B_EMPTY) : "memory");
#pragma unroll 1
          for (int n = ((NPK << 16) >> (4 * kb)) & 15; n > 0 && np < 32; n--, np++)
            tma_2d(sm + OFF_STATS + 512, (np & 1) ? &tmPU : &tmPG, (fidx >> 1) * 64, (np >> 1) * 64 + rank * 32, mb + B_FFN, false);
        }
        if (PEEL) {
          mbar_wait(mb + B_EMPTY + 24, 0);
          tma_2d_mc(sm + xoff(3, rank), &tmX, kl + 192, rb * 256 + rank * 128, mb + B_FULL + 24, EFX);
          load_w(15);
          mbar_expect_tx(mb + B_FULL + 24, STAGE_B);
        }
        if (fidx >= 0) { mbar_wait(mb + B_FFN, 0); mbar_expect_tx(mb + B_FFN, 65536 + 8 * 512); mbar_expect_tx(mb + B_FFN + 8, 65536); }
#pragma unroll
        for (int p = 4; p < 8; p++) sts4(sm + OFF_STATS + p * 144, 0x3F803F80u, 0x3F803F80u, 0x3F803F80u, 0x3F803F80u);
        fence_async_smem();
        mbar_arrive(mb + B_LATE);
        PTS(2);
        mbar_expect_tx(mb + B_KVL, 36864);
        mbar_wait(mb + B_LATE, 0);
        wait3(60);
        delay(clk(), KDELAY);
        bulk_load(sm + 11 * SLOT_B, &G.kvp[cg * 2304], SLOT_B, mb + B_KVL);
        bulk_load(sm + 13 * SLOT_B, &G.kvp[cg * 2304 + 1024], SLOT_B, mb + B_KVL);
        bulk_load(sm + 2 * SLOT_B, &G.kvp[cg * 2304 + 2048], 4096, mb + B_KVL);
        PTS(3);
        const uint4* src = &G.obuf[(rb * 4 + rank * 2 + hf) * 64 * 128];
        wait3(48);
        const uint32_t t1 = clk();
#pragma unroll
        for (int p = 1; p < 5; p++) {
          delay(t1, ADELAY + (p - 1) * ASTEP);
          bulk_load_mc(sm + (10 + (p & 3)) * SLOT_B + rank * 8192, src + ((hf ^ 1) * 8 + p - 1) * 512, sm + bar3(p) + rank * 256, 3);
        }
        PTS(7);
#pragma unroll 1
        for (int i = 5; i < 17; i++) {
          const int p = min(i, 15);
          const uint32_t d = sm + (10 + (p & 3)) * SLOT_B + rank * 8192, fb = sm + bar3(0) + o3(p) + rank * 256;
          const uint4* q = src + chunk_of(i & 15) * 512;
          mbar_wait(sm + bar3(48) + o3(p - 4 + ((LATEP >> p) & 1)), 0);
          bulk_load_mc(d, q, fb, i < 15 ? 3 : 1 << ((i ^ rank ^ 1) & 1));
        }
        PTS(15);
      }
    } else {
      const int r4 = lane >> 3, c8 = lane & 7;
      const uint32_t eb = (lane << 24) + bars + B_EMPTY;
      auto tagged = [](float v, uint32_t tag) { return ((__float_as_uint(v) + 128) & ~255u) | tag; };
      auto gather = [&](uint32_t tag) {
        const int q = (wid - 9) * 24 + lane;
        const uint4* cp = lane < 24 ? &G.csp[cg * 8 * 48 + q] : &G.st1[rb * 8 * 48 + (wid - 9) * 8 + lane - 24];
        uint4 v[8];
        delay(clk(), GDELAY);
#pragma unroll 1
        for (int it = 0;; it++) {
#pragma unroll
          for (int i = 0; i < 8; i++) v[i] = ld_rlx4(cp + i * 48);
          uint32_t x = 0;
#pragma unroll
          for (int i = 0; i < 8; i++) { v[i].x ^= tag; v[i].y ^= tag; v[i].z ^= tag; v[i].w ^= tag; x |= v[i].x | v[i].y | v[i].z | v[i].w; }
          if (!__any_sync(~0u, (x & 255) != 0)) break;
          SPINCHK(it, 3);
        }
        float c[4] = {0.f, 0.f, 0.f, 0.f};
#pragma unroll
        for (int i = 0; i < 8; i++) { c[0] += __uint_as_float(v[i].x); c[1] += __uint_as_float(v[i].y); c[2] += __uint_as_float(v[i].z); c[3] += __uint_as_float(v[i].w); }
        const uint32_t h0 = pack2(c[0], c[1]), h1 = pack2(c[2], c[3]), ca = sm + OFF_COLSUM + (q >> 1) * 32 + (q & 1) * 8;
        if (lane < 24) {
          sts2f(ca, __uint_as_float(h0), __uint_as_float(h1));
          sts2f(ca + 16, __uint_as_float(pack2(c[0] - bf_lo(h0), c[1] - bf_hi(h0))), __uint_as_float(pack2(c[2] - bf_lo(h1), c[3] - bf_hi(h1))));
        }
        fence_async_smem();
        mbar_arrive(mb + B_AUX);
      };
      const int r2 = lane >> 4, c16 = lane & 15;
      float a[12];
#pragma unroll
      for (int i = 0; i < 12; i++) a[i] = 0.f;
      auto kb_of = [](int it) { return (int)(KORD >> (4 * it)) & 15; };
      if (wid == 9) {
        const uint32_t a0 = sm + rb * 1024 + r2 * 128 + (((c16 >> 1) ^ r2) << 4) + (c16 & 1) * 8;
        const uint2* gw = (const uint2*)(P.wqkv + (kl + rb * 8 + r2) * 3072 + cg * 64) + c16;
#pragma unroll 1
        for (int it = 0; it < 16; it++) {
          uint2 w[12];
          const int kb = kb_of(it);
          if (kb >= 12) {
#pragma unroll
            for (int j = 0; j < 12; j++) w[j] = ld_rlx2(gw + (j >> 2) * 256 + (j & 3) * 1536);
            gw += 64 * 768;
          } else {
            const uint32_t so = a0 + woff(kb & 3);
            mbar_wait(mb + B_FULL + 8 * (kb & 3), (kb >> 2) & 1);
            static_for<0, 12>([&](auto ic) { constexpr int i = decltype(ic)::value;
              const float2 v = lds2f_o<(i >> 2) * WSTR + (i & 3) * 256>(so ^ ((i & 3) << 5)); w[i] = make_uint2(__float_as_uint(v.x), __float_as_uint(v.y)); });
            uint32_t done = 0;
#pragma unroll
            for (int i = 0; i < 12; i++) done |= w[i].y;
            if (lane < 2) mbar_arrive_rem(eb + 8 * (kb & 3) + (done & zero));
          }
#pragma unroll
          for (int i = 0; i < 12; i++) { float* q = a + (i >> 2) * 4; q[0] += bf_lo(w[i].x); q[1] += bf_hi(w[i].x); q[2] += bf_lo(w[i].y); q[3] += bf_hi(w[i].y); }
        }
        if (lane == 0) PTS(8);
        float c[6];
#pragma unroll
        for (int i = 0; i < 6; i++) {
          const int o = (i >> 1) * 4 + (i & 1);
          c[i] = (r2 ? a[o + 2] : a[o]) + __shfl_xor_sync(~0u, r2 ? a[o] : a[o + 2], 16);
        }
        bar_sync(5, 96);
        if (lane == 0) PTS(5);
        const uint32_t tag = lds1(mb + B_SW + 4) & 255;
#pragma unroll
        for (int sg = 0; sg < 3; sg++) st_rlx2((uint2*)&G.csp[(cg * 8 + rb) * 48] + sg * 32 + c16 * 2 + r2, tagged(c[sg * 2], tag), tagged(c[sg * 2 + 1], tag));
      } else {
       if (wid == 10) {
        if (lane < 24 && (lane & 28) != 4) sts4(sm + OFF_STATS + (lane < 16 ? lane * 128 + c8 * 16 : c8 * 16), 0x3F803F80u, 0x3F803F80u, 0x3F803F80u, 0x3F803F80u);
       } else {
        mbar_wait(mb + B_FULL + 8 * PFST, 0);
        const uint32_t ep = ld_rlx(&G.epoch);
        uint4 v[4];
#pragma unroll
        for (int i = 0; i < 4; i++) v[i] = ld_cg4((const uint4*)P.wr + lane + i * 32);
        if (elect_one()) { tmap_prefetch(&tmO); tmap_prefetch(&tmG); tmap_prefetch(&tmU); tmap_prefetch(&tmD); tmap_prefetch(&tmPD); tmap_prefetch(&tmM); }
        __syncwarp();
        const uint4 sv = make_uint4(SENT, SENT, SENT, SENT);
#pragma unroll 1
        for (int i = 0; i < 9; i++) {
          uint4* q = i < 8 ? &G.obuf[((rb * 4 + (i >> 1)) * 64 + cg * 4) * 128 + (i & 1) * 256 + lane] : &G.kvp[cg * 2304 + rb * 288 + lane];
#pragma unroll
          for (int j = 0; j < 8; j++) q[j * 32] = sv;
          if (i == 8) q[256] = sv;
          else if (lane < ((i & 1) ? 24 : 16)) l2_prefetch((i & 1) ? P.wqkv + (kl + (i >> 1) * 64 + rb * 8 + c8) * 3072 + r4 * 1024 + cg * 64 : P.x + (b * 16 + lane) * D_ + kl + i * 32);
        }
        float s = 0.f;
#pragma unroll 1
        for (int i = 0; i < 4; i++) {
          s += (bf_lo(v[0].x) + bf_hi(v[0].x)) + (bf_lo(v[0].y) + bf_hi(v[0].y)) + (bf_lo(v[0].z) + bf_hi(v[0].z)) + (bf_lo(v[0].w) + bf_hi(v[0].w));
          v[0] = v[1]; v[1] = v[2]; v[2] = v[3];
        }
#pragma unroll
        for (int o = 16; o; o >>= 1) s += __shfl_xor_sync(~0u, s, o);
        if (lane == 0) sts2f(mb + B_SW, s, __uint_as_float(ep + 1));
       }
        const uint32_t xa = sm + (c3 * 16 + r4) * 128 + ((c8 ^ r4) << 4);
        const uint4* gx = (const uint4*)(P.x + (b * 16 + r4) * D_ + kl) + c8;
        uint32_t e[4] = {0, 0, 0, 0};
        uint4 wq;
#pragma unroll 1
        for (int kb = wid == 10 ? 0 : 12; kb < (wid == 10 ? 12 : 16); kb++) {
          uint4 v[4];
          if (!(kb & 3)) wq = ld_cg4((const uint4*)(P.wr + k_of(kb + r4)) + c8);
          if (kb >= 12) {
#pragma unroll
            for (int j = 0; j < 4; j++) v[j] = ld_cg4(gx + j * 512);
            gx += 8;
          } else {
            const uint32_t so = xa + xoff(kb & 3, hf);
            mbar_wait(mb + B_FULL + 8 * (kb & 3), (kb >> 2) & 1);
            v[0] = lds4_o<0>(so); v[1] = lds4_o<512>(so ^ 64); v[2] = lds4_o<1024>(so); v[3] = lds4_o<1536>(so ^ 64);
            if (lane < 2) mbar_arrive_rem(eb + 8 * (kb & 3) + ((v[0].x | v[1].x | v[2].x | v[3].x) & zero));
          }
#pragma unroll
          for (int j = 0; j < 16; j++) {
            const uint32_t u = (j & 3) == 0 ? v[j >> 2].x : (j & 3) == 1 ? v[j >> 2].y : (j & 3) == 2 ? v[j >> 2].z : v[j >> 2].w;
            const float d0 = bf_lo(u), d1 = bf_hi(u);
            a[j >> 2] += d0 + d1; a[4 + (j >> 2)] = fmaf(d0, d0, fmaf(d1, d1, a[4 + (j >> 2)]));
          }
          cut<1>(zero);
          const int sl = (kb & 3) * 8 + c8;
          const uint4 wn = make_uint4(__shfl_sync(~0u, wq.x, sl), __shfl_sync(~0u, wq.y, sl), __shfl_sync(~0u, wq.z, sl), __shfl_sync(~0u, wq.w, sl));
#pragma unroll
          for (int j = 0; j < 4; j++) e[j] = hfma2(v[j].x, wn.x, hfma2(v[j].y, wn.y, hfma2(v[j].z, wn.z, hfma2(v[j].w, wn.w, e[j]))));
        }
        float mean, pd;
#pragma unroll 1
        for (int h = 0; h < 2; h++) {
          float u[4], v[2];
#pragma unroll
          for (int i = 0; i < 4; i++) u[i] = ((lane & 4) ? a[4 + i] : a[i]) + __shfl_xor_sync(~0u, (lane & 4) ? a[i] : a[4 + i], 4);
#pragma unroll
          for (int i = 0; i < 2; i++) v[i] = ((lane & 2) ? u[2 + i] : u[i]) + __shfl_xor_sync(~0u, (lane & 2) ? u[i] : u[2 + i], 2);
          mean = pd;
          pd = ((lane & 1) ? v[1] : v[0]) + __shfl_xor_sync(~0u, (lane & 1) ? v[0] : v[1], 1);
#pragma unroll
          for (int j = 0; j < 4; j++) { a[j] = bf_lo(e[j]); a[4 + j] = bf_hi(e[j]); }
        }
        if (wid == 11) {
          sts2f(sm + OFF_COLSUM + 512 + lane * 8, mean, pd);
          fence_gpu();
          bar_arrive(5, 96); PTS(0);
          if (elect_one()) {
#pragma unroll 1
            for (int p = 0; p < 16; p++) {
              const uint32_t ad = sm + bar3(0) + o3(p);
              mbar_init(ad, 1); mbar_init(ad + 256, 1); mbar_init(ad + 448, 8); mbar_init(ad + 704, p == 0 ? 2 : p == 12 ? 1 : p == 15 ? 7 : 8);
              mbar_expect_tx(ad, 8192); mbar_expect_tx(ad + 256, 8192); mbar_expect_tx(mb + B_FULL3 + 8 * p, SLOT_B);
            }
            asm volatile("fence.mbarrier_init.release.cluster;" ::: "memory");
            fence_async_smem();
            mbar_arrive_rem(bars + B_LATE); mbar_arrive_rem((1u << 24) + bars + B_LATE);
          }
          __syncwarp();
        } else {
          if (lane == 0) PTS(1);
          bar_sync(5, 96);
          const float2 u = lds2f(sm + OFF_COLSUM + 512 + lane * 8), sw = lds2f(mb + B_SW);
          mean = (mean + u.x) * (1.f / D_);
          pd += u.y;
          pd += __shfl_xor_sync(~0u, pd, 4);
          const float var = fmaxf(fmaf(-mean, mean, __shfl_xor_sync(~0u, mean, 4)), 0.f);
          const uint32_t tag = __float_as_uint(sw.y) & 255;
          if (c8 < 4) {
            st_rlx2((uint2*)G.st1 + (b >> 1) * 96 + rank * 16 + r4 + 4 * c8, tagged(-mean, tag), tagged(rsq(var + 1e-5f), tag));
            st_rlx(&G.pred[b * 16 + r4 + 4 * c8], (ordered(fmaf(-mean, sw.x, pd)) & ~255u) | tag);
          }
        }
      }
      if (wid < 11) gather(lds1(mb + B_SW + 4) & 255);
      if (wid == 9) {
        if (lane == 0) PTS(6);
        {
          const uint4 sv = make_uint4(SENT, SENT, SENT, SENT);
          uint4* y = &G.ybuf[b * NFFN * 4 + lane];
#pragma unroll
          for (int i = 0; i < 14; i++) y[i * 32] = sv;
          if (lane < 16) G.st2[b * 16 + lane] = make_uint4(0, 0, 0, 0);
          G.hsel[b * 64 + lane] = sv; G.hsel[b * 64 + 32 + lane] = sv;
          if (b < 8) { G.cand[b * 32 + lane] = SENT; G.cst[b * 32 + lane] = make_uint4(0, 0, 0, 0); }
          fence_gpu();
          __syncwarp();
          if (lane == 0) mbar_arrive(mb + B_LATE);
        }
      } else if (wid == 10) {
        {
          mbar_wait(mb + B_FULL + 24, 1);
#pragma unroll 1
          for (int r = -4; r < (fidx >= 0 ? 16 : 0); r++) {
            l2_prefetch((r < 0 ? (const char*)P.wo + (b + 1) * 16384 : (const char*)P.wd + fidx * 65536) + r * 4096 + lane * 128);
            delay(clk(), PDT);
          }
          PTS(4);
        }
      }
      mbar_wait(mb + B_LATE, 0);
      if (wid == 9) {
        if (elect_one()) {
          wait3(60);
#pragma unroll 1
          for (int p = 0; p < 16; p++) {
            const bool mix = (unsigned)(p - 1) < 8;
            const int c1 = mix ? ((p - 1) >> 1) * 16 : 0, c2 = mix ? (hf ^ 1) * 8 + ((p - 1) & 1) * 4 : chunk_of(p) * 4;
            const uint32_t d = sm + (uint32_t)((WO_SLOTS >> (4 * p)) & 15) * SLOT_B;
            if ((0xFFE2 >> p) & 1) mbar_wait(p == 1 ? mb + B_EMPTY + 8 : sm + bar3(32) + o3(p - 5), p == 1);
            if (EFWO) asm volatile("cp.async.bulk.tensor.4d.shared::cluster.global.mbarrier::complete_tx::bytes.L2::cache_hint [%0], [%1, {0, %3, %4, %5}], [%2], %6;"
                         :: "r"(d), "l"(mix ? &tmM : &tmO), "r"(mb + B_FULL3 + 8 * p), "r"(c1), "r"(c2), "r"(c3 * 2), "l"(l2_stream()) : "memory");
            else asm volatile("cp.async.bulk.tensor.4d.shared::cluster.global.mbarrier::complete_tx::bytes [%0], [%1, {0, %3, %4, %5}], [%2];"
                         :: "r"(d), "l"(mix ? &tmM : &tmO), "r"(mb + B_FULL3 + 8 * p), "r"(c1), "r"(c2), "r"(c3 * 2) : "memory");
            if (p >= 10) PTS(7 + p);
          }
          if (fidx >= 0) {
#pragma unroll
            for (int i = 0; i < 4; i++) {
              if (i == 0 || ((DEV >> (4 * i)) & 15) != ((DEV >> (4 * i - 4)) & 15)) wait3(32 + ((DEV >> (4 * i)) & 15));
              tma_3d(sm + ((D_SLOTS >> (4 * i)) & 15) * SLOT_B, &tmD, 0, fidx * 32, i * 4, mb + B_FFN + 8, EFF);
            }
          }
        }
      } else if (wid == 11) {
        const uint2 w = ld_rlx2((const uint2*)(P.wr + c3 * 128) + lane);
        wait3(32);
        sts1(sm + OFF_LNP + (lane & 1) * 128 + (lane >> 1) * 4, w.x); sts1(sm + OFF_LNP + (lane & 1) * 128 + 64 + (lane >> 1) * 4, w.y);
        if (lane < 16) sts1(sm + OFF_LNP + 256 + lane * 4, 0x3F803F80u);
        const uint32_t tag = lds1(mb + B_SW + 4) & 255;
        uint4 k;
        for (int it = 0;; it++) {
          k = ld_rlx4((const uint4*)&G.pred[rb * 256 + hf * 64 + r2 * 128] + c16);
          k.x ^= tag; k.y ^= tag; k.z ^= tag; k.w ^= tag;
          if (!__any_sync(~0u, (k.x | k.y | k.z | k.w) & 255)) break;
          SPINCHK(it, 13);
        }
        const uint2 ahead = top2(k.x | (lane * 4), k.y | (lane * 4 + 1), k.z | (lane * 4 + 2), k.w | (lane * 4 + 3));
        if (lane == 0) sts2f(sm + OFF_MSC + 8, __uint_as_float((ahead.x & 127) ^ NOSPEC), __uint_as_float((ahead.y & 127) ^ NOSPEC));
        __syncwarp();
        if (lane == 0) mbar_arrive(mb + B_FULL3 + 8 * 15);
        if (fidx >= 0 && elect_one()) {
#pragma unroll 1
        for (int j = 0; j < 8; j++) { mbar_wait(sm + bar3(32) + o3(PD0 + j * PDS / 2), 0); tma_2d(sm + OFF_COLSUM, &tmPD, 0, fidx * 256 + j * 32, mb + B_FFN, false); }
        }
      } else if (fidx >= 0 && elect_one()) {
        wait3(60);
        mbar_expect_tx(mb + B_FULL, 65536);
#pragma unroll 1
        for (int h = 0; h < 2; h++) {
          const int up = h ^ hf ^ 1;
          mbar_wait(mb + B_EMPTY + 16 - 16 * h, 1);
#pragma unroll
          for (int i = 0; i < 4; i++) {
            const int f = (0x5140 >> (4 * i)) & 15;
            tma_2d(sm + ((GU_SLOTS >> (4 * f)) & 15) * SLOT_B + up * 8192, up ? &tmU : &tmG, fidx * 32, f * 128, mb + B_FULL, EFF);
            if (FDT) delay(clk(), FDT);
          }
          PTS(23 + h);
        }
#pragma unroll 1
        for (int i = 0; i < 4; i++) {
          const int f = (0x7362 >> (4 * i)) & 15;
          const uint32_t d = sm + ((GU_SLOTS >> (4 * f)) & 15) * SLOT_B;
          mbar_wait(sm + bar3(32) + o3((GEV >> (4 * i)) & 15), 0);
          tma_2d(d, &tmG, fidx * 32, f * 128, mb + B_FFN, EFF);
          tma_2d(d + 8192, &tmU, fidx * 32, f * 128, mb + B_FFN, EFF);
          PTS(27 + i);
        }
      }
    }
    bar_sync(15, 32);
    const float sw = __uint_as_float(lds1(mb + B_SW));
    const int rr = lane >> 4, row00 = rb * 256 + hf * 64;
    uint2 pick;
    if (wid == 8) {
      wait3(61);
      delay(clk(), SDELAY);
      uint4 v;
      int id;
      for (int it = 0;; it++) {
        v = ld_rlx4(&G.cst[jp * 32 + lane]);
        id = __float2int_rn(__uint_as_float(v.w));
        if (!__any_sync(~0u, (id & 15) != 8)) break;
        SPINCHK(it, 14);
      }
      float2 pr;
      const uint32_t k = route(v, sw, id >> 4, pr);
      pick.x = __reduce_max_sync(~0u, k); pick.y = __reduce_max_sync(~0u, k == pick.x ? 0 : k);
      if (k == pick.x || k == pick.y) sts4(sm + OFF_MSC + 16 + (k == pick.y) * 16, k, lane, __float_as_uint(pr.x), __float_as_uint(pr.y));
      __syncwarp();
      if (lane == 0) { mbar_arrive(mb + B_SEL); PTS(16); }
    } else if (wid == 9) {
      wait3(61);
      delay(clk(), LDELAY);
      uint4 v[4];
      for (int it = 0;; it++) {
#pragma unroll
        for (int i = 0; i < 4; i++) v[i] = ld_rlx4(&G.st2[row00 + (i >> 1) * 128 + (i & 1) * 32 + lane]);
        if (!__any_sync(~0u, (v[0].w & v[1].w & v[2].w & v[3].w) != 0x41000000u)) break;
        SPINCHK(it, 6);
      }
      uint32_t k[4];
#pragma unroll
      for (int i = 0; i < 4; i++) {
        float2 pr;
        k[i] = route(v[i], sw, row00 + (i >> 1) * 128 + (i & 1) * 32 + lane, pr);
        const float nm = __uint_as_float(v[i].x) * (-1.f / D_);
        sts2f(sm + OFF_LNP + (i * 32 + lane) * 8, __uint_as_float(pack2(pr.x, pr.x)), __uint_as_float(pack2(nm, nm)));
      }
      const uint2 m = top2(k[0], k[1], k[2], k[3]);
      if (lane == 0) { st_rlx2(&G.cand[c3 * 32 + (rb * 2 + hf) * 2], m.x, m.y); sts2f(sm + OFF_MSC + 0, __uint_as_float(m.x), __uint_as_float(m.y)); }
      wait3(62);
      __syncwarp();
      if (lane == 0) { mbar_arrive(mb + B_OUT); PTS(12); }
      const int ca = 2047 - (((lane & 4) ? m.y : m.x) & 2047), ta = ((ca >> 1) & 64) + (ca & 63);
      uint32_t h0, h1, h2, h3;
      ldsm4_o<0>(sm + HST + ta * 256 + ((((lane & 3) * 4 + (lane >> 3)) ^ (ta & 7)) << 4), h0, h1, h2, h3);
      st_rlx4(&G.hsel[(32 + (rb * 2 + hf) * 2 + rr) * 128 + c3 * 16 + (lane & 15)], make_uint4(h0, h1, h2, h3));
    }
    mbar_wait(mb + B_OUT, 0);
    const float2 cf = lds2f(sm + OFF_MSC + 0);
    const int ca0 = ~__float_as_int(cf.x), ca1 = ~__float_as_int(cf.y), cand0 = ((ca0 >> 1) & 64) + (ca0 & 63), cand1 = ((ca1 >> 1) & 64) + (ca1 & 63);
    auto norm = [](const uint4& v, const float2& pr) {
      const uint32_t r = __float_as_uint(pr.x), m = __float_as_uint(pr.y);
      return make_uint4(hfma2(hadd2(v.x, m), r, v.x), hfma2(hadd2(v.y, m), r, v.y), hfma2(hadd2(v.z, m), r, v.z), hfma2(hadd2(v.w, m), r, v.w));
    };
    uint4* const og = (uint4*)(P.out + row00 * D_ + c3 * 128) + (lane & 15);
    if (wid == 8) {
      delay(clk(), CDELAY);
      uint32_t k;
      for (int it = 0;; it++) { k = ld_rlx(&G.cand[c3 * 32 + lane]); if (!__any_sync(~0u, k == SENT)) break; SPINCHK(it, 12); }
      const uint32_t m1 = __reduce_max_sync(~0u, k), m2 = __reduce_max_sync(~0u, k == m1 ? 0 : k);
      const uint32_t miss = ((m1 ^ pick.x) | (m2 ^ pick.y)) & 2047;
      if (miss && (k == m1 || k == m2)) {
        float2 pr;
        route(ld_rlx4(&G.st2[2047 - (k & 2047)]), sw, 0, pr);
        sts4(sm + OFF_MSC + 48 + (k == m2) * 16, k, 32 + lane, __float_as_uint(pr.x), __float_as_uint(pr.y));
      }
      if (lane == 0) sts1(sm + OFF_MSC + 80, miss);
      __syncwarp();
      if (lane == 0) { mbar_arrive(mb + B_SEL2); PTS(13); }
      if (lane == 0 && b == 0) G.epoch = lds1(mb + B_SW + 4);
      const uint32_t kc = __float_as_uint(rr ? cf.y : cf.x);
      const int c = rr ? cand1 : cand0;
      if (kc != m1 && kc != m2) og[(c + (c & 64)) * 128] = norm(lds4(sm + HST + c * 256 + (((lane & 15) ^ (c & 7)) << 4)), lds2f(sm + OFF_LNP + c * 8));
    }
#pragma unroll 1
    for (int t0 = wid == 8 ? 120 : (11 - wid) * 8; t0 < (wid == 8 ? 128 : 120) * !NOOUT; t0 += 24) {
      uint4 v[4];
      float2 pr[4];
      const uint32_t ad = sm + HST + t0 * 256 + lane * 16;
      static_for<0, 4>([&](auto ic) { constexpr int i = decltype(ic)::value; v[i] = lds4_o<i * 512>(ad ^ (rr << 4) ^ (i << 5)); pr[i] = lds2f_o<i * 16>(sm + OFF_LNP + (t0 + rr) * 8); });
#pragma unroll
      for (int i = 0; i < 4; i++) v[i] = norm(v[i], pr[i]);
      if (t0 >= OHOLD) wait3(63);
#pragma unroll
      for (int i = 0; i < 4; i++) {
        const int tr = t0 + rr + 2 * i;
        if (tr != cand0 && tr != cand1) {
          if (OUTEF) asm volatile("st.global.L2::cache_hint.v4.u32 [%0], {%1,%2,%3,%4}, %5;" :: "l"(og + (tr + (tr & 64)) * 128), "r"(v[i].x), "r"(v[i].y), "r"(v[i].z), "r"(v[i].w), "l"(l2_stream()) : "memory");
          else og[(tr + (tr & 64)) * 128] = v[i];
        }
      }
    }
    if (wid == 11 && lane == 0) PTS(31);
  } else {
    asm volatile("setmaxnreg.inc.sync.aligned.u32 224;");
    const int t128 = tid & 127, warp = wid & 3, g = lane >> 2, t = lane & 3;
    const int mb3 = rb * 4 + wg * 2 + hf;
    float acc[64];
    uint4 abuf[3][4];
    uint32_t to;
    int tid2;
    {
      float acc0[96], acc1[96];
#pragma unroll
      for (int i = 0; i < 96; i++) { asm volatile("" : "=f"(acc0[i])); asm volatile("" : "=f"(acc1[i])); }
      const uint32_t xo0 = dlo(sb, 16) + hf * 512, xo1 = dlo(sb, 16) + (hf ^ 1) * 512;
      const uint32_t eb0 = (t128 << 24) + bars + B_EMPTY;
#pragma unroll 1
      for (int kb = 0; kb < 12; kb++) {
        const int s = kb & 3;
        mbar_wait(mb + B_FULL + 8 * s, (kb >> 2) & 1);
        if (LOCK) bar_sync(13, 256);
        if (kb == 0) TS(1);
        const uint32_t xs = xoff(s, wg) >> 4, ws = dlo(sb + woff(s), WSTR);
        pin(acc0); pin(acc1);
        wg_fence();
#pragma unroll
        for (int k = 0; k < 4; k++) {
          const uint64_t db = dsc<1024, 1>(ws + k * 128);
          const int sd = k == 0 ? kb : 1;
          wgmma_n192_ss<0, 1, 0>(acc0, dsc<1024, 1>(xs + xo0 + k * 2), db, sd);
          wgmma_n192_ss<0, 1, 0>(acc1, dsc<1024, 1>(xs + xo1 + k * 2), db, sd);
          if (k == RELK || k == 3) wg_commit();
          if (k == RELK) {
            wg_wait<1>();
            if (kb > 0 && t128 < 2) mbar_arrive_rem(eb0 + 8 * ((kb - 1) & 3));
          }
        }
        pin(acc0); pin(acc1);
      }
      float qa0[32], qa1[32], kv0[64], kv1[64];
#pragma unroll
      for (int i = 0; i < 96; i++) { if (i < 32) { qa0[i] = acc0[i]; qa1[i] = acc1[i]; } else { kv0[i - 32] = acc0[i]; kv1[i - 32] = acc1[i]; } }
      uint2 st[2][2];
      uint4 am;
      auto center = [&](float (&q)[32], float (&kv)[64], const uint2 (&v)[2]) {
        const uint32_t n0 = v[0].x & (t == 0 ? ~255u : 0u), n1 = v[1].x & (t == 0 ? ~255u : 0u);
        am = make_uint4(__byte_perm(n0, 0, 0x3232), __byte_perm(n1, 0, 0x3232),
                        __byte_perm(__float_as_uint(__uint_as_float(n0) - bf_hi(n0)), 0, 0x3232), __byte_perm(__float_as_uint(__uint_as_float(n1) - bf_hi(n1)), 0, 0x3232));
        wg_fence();
        wgmma_n64_rs<1, 0>(q, am.x, am.y, am.z, am.w, dsc<32, 0>(dlo(sb + OFF_COLSUM, 0)), 1);
        wgmma_n128_rs<1, 0>(kv, am.x, am.y, am.z, am.w, dsc<32, 0>(dlo(sb + OFF_COLSUM + 256, 0)), 1);
      };
      auto load_st = [&]() {
        mbar_wait(mb + B_AUX, 0);
#pragma unroll
        for (int i = 0; i < 4; i++) st[i >> 1][i & 1] = ld_rlx2((const uint2*)G.st1 + ((rb * 4 + wg * 2 + ((i >> 1) ^ hf)) * 2 + (warp >> 1)) * 96 + (warp & 1) * 16 + (i & 1) * 8 + g);
      };
      if (!wg) {
        wg_wait<0>();
        if (t128 < 2) mbar_arrive_rem(eb0 + 24);
        load_st();
#pragma unroll 1
        for (int s = 0; s < (B6E < 3 ? 3 : 4); s++) mbar_wait(mb + B_FULL + 8 * s, 1);
        bar_sync(6, 256);
      }
      static_for<0, 4>([&](auto sc) {
        constexpr int s = decltype(sc)::value;
        if (wg || (B6E < 3 && s == 3)) mbar_wait(mb + B_FULL + 8 * s, 1);
        const uint32_t xs = (wg ? xoff(s, 1) : xoff(s, 0)) >> 4, ws = dlo(sb + woff(s) + WSTR, WSTR);
        pin(kv0); pin(kv1); pin(qa0); pin(qa1);
        wg_fence();
#pragma unroll
        for (int k = 0; k < 4; k++) {
          const uint64_t db = dsc<1024, 1>(ws + k * 128);
          wgmma_n128_ss<0, 1, 0>(kv0, dsc<1024, 1>(xs + xo0 + k * 2), db, 1);
          wgmma_n128_ss<0, 1, 0>(kv1, dsc<1024, 1>(xs + xo1 + k * 2), db, 1);
          if (s == 0 && k == B6H - 1) { if (!wg) bar_sync(14, 256); wg_fence(); }
          if (k == 3 || (k == 2 && s == 0)) wg_commit();
          if (k == (s ? 3 : 2) && s < 3) {
            wg_wait<1>();
            if (s == 0) { if (wg && t128 < 2) mbar_arrive_rem(eb0 + 24); }
            else if (!wg) bar_arrive(8 + s, 256);
          }
        }
        if (s == B6E && wg) bar_arrive(6, 256);
        if (s == 3 && B6H && wg) bar_arrive(14, 256);
        if (s == STLD && wg) load_st();
      });
      if (CUTS & 2) {
        cut<6>(zero);
#pragma unroll
        for (int i = 0; i < 4; i++) asm volatile("" : "+r"(st[i >> 1][i & 1].x), "+r"(st[i >> 1][i & 1].y) :: "memory");
      }
      center(qa0, kv0, st[0]);
      wg_commit();
      if (B6E > 3 && wg) bar_arrive(6, 256);
      float rs[2][2];
#pragma unroll
      for (int i = 0; i < 4; i++) rs[i >> 1][i & 1] = __uint_as_float(st[i >> 1][i & 1].y & ~255u);
      const uint32_t sad = sm + (wg ? 11 : 2) * SLOT_B + (warp * 16 + (lane & 15)) * 128 + (((lane >> 4) ^ (lane & 7)) << 4);
      wg_wait<0>();
      pin(kv0); pin(kv1); pin(qa0); pin(qa1); pin4(am);
      center(qa1, kv1, st[1]);
      wg_commit();
      if (wg) bar_arrive(11, 256);
      if (CUTS & 1) cut<2>(zero);
      TS(2);
      float rl[2];
      uint32_t r2[2];
      auto scales = [&](int m, uint32_t z) {
#pragma unroll
        for (int h = 0; h < 2; h++) { const float r = __uint_as_float(__float_as_uint(rs[m][h]) + z); r2[h] = pack2(r, r); rl[h] = r * 1.4426950408889634f; }
      };
      auto phi8 = [&](const float* a) {
        return make_uint4(phi2(a[0], a[1], r2[0], rl[0]), phi2(a[2], a[3], r2[1], rl[1]), phi2(a[4], a[5], r2[0], rl[0]), phi2(a[6], a[7], r2[1], rl[1]));
      };
      auto stage = [&](float (&a)[64], auto mc) {
        constexpr int m = decltype(mc)::value;
        uint4 r[4];
        scales(m, 0);
#pragma unroll
        for (int j = 0; j < 4; j++) r[j] = phi8(a + j * 8);
        if (m == 0 || wg) bar_sync(wg ? 9 + m : 11, 256 + (r[SBAR].x & zero));
#pragma unroll
        for (int j = 0; j < 4; j++) {
          const int v = 32 + j * 8;
          stsm4_o<WSTR + m * 8192>(sad ^ (j << 5), hmul2(pack2(a[v], a[v + 1]), r2[0]), hmul2(pack2(a[v + 2], a[v + 3]), r2[1]),
                                                   hmul2(pack2(a[v + 4], a[v + 5]), r2[0]), hmul2(pack2(a[v + 6], a[v + 7]), r2[1]));
        }
#pragma unroll
        for (int j = 0; j < 4; j++) stsm4_o<m * 8192>(sad ^ (j << 5), r[j].x, r[j].y, r[j].z, r[j].w);
      };
      stage(kv0, std::integral_constant<int, 0>{});
      wg_wait<0>();
      pin(kv1); pin(qa1); pin4(am);
      stage(kv1, std::integral_constant<int, 1>{});
      fence_async_smem();
      TS(3);
      uint32_t xr[8][4];
      auto load_xr = [&]() {
        const uint32_t xa = sm + hf * 8192 + (warp * 16 + (lane & 15)) * 128 + (((lane >> 4) ^ (lane & 7)) << 4);
#pragma unroll
        for (int q = 0; q < 8; q++) ldsm4_o<0>((xa ^ ((q & 3) << 5)) + xoff(rank * 2 + (q >> 2), wg), xr[q][0], xr[q][1], xr[q][2], xr[q][3]);
      };
      if (!wg) { bar_arrive(4, 256); load_xr(); }
      else {
        float ka[36];
#pragma unroll
        for (int i = 0; i < 36; i++) ka[i] = 0.f;
        auto kv_mma = [&](auto ic) {
          constexpr int i = decltype(ic)::value;
          constexpr uint32_t o = sb + (i < 8 ? 11 : 2) * SLOT_B + (i & 7) * 2048;
          wgmma_n72_ss<1, 1, 0>(ka, dsc<1024, 1>(dlo(o, 8192)), dsc<1024, 1>(dlo(o + WSTR, sb + OFF_STATS - o - WSTR)), i);
        };
        mbar_wait(mb + B_LATE, 0);
        bar_sync(3, 128);
        wg_fence();
        static_for<0, 8>(kv_mma);
        wg_commit();
        uint4* dst = &G.kvp[cg * 2304 + rb * 32];
        if (CUTS & 4) cut<3>(zero);
        load_xr();
        bar_sync(4, 256);
        static_for<8, 16>(kv_mma);
        wg_commit();
        if (QHOLD == 1) bar_arrive(8, 256);
        wg_wait<0>();
        pin(ka);
        if (QHOLD == 2) bar_arrive(8, 256);
        TS(4);
        if (warp < 2) {
          st_rlx4(dst + warp * 512 + lane, make_uint4(pack2(ka[0], ka[1]), pack2(ka[4], ka[5]), pack2(ka[8], ka[9]), pack2(ka[12], ka[13])));
          st_rlx4(dst + warp * 512 + 256 + lane, make_uint4(pack2(ka[2], ka[3]), pack2(ka[6], ka[7]), pack2(ka[10], ka[11]), pack2(ka[14], ka[15])));
        } else {
          st_rlx4(dst + warp * 512 + lane, make_uint4(pack2(ka[16], ka[17]), pack2(ka[20], ka[21]), pack2(ka[24], ka[25]), pack2(ka[28], ka[29])));
          st_rlx4(dst + warp * 512 + 256 + lane, make_uint4(pack2(ka[18], ka[19]), pack2(ka[22], ka[23]), pack2(ka[26], ka[27]), pack2(ka[30], ka[31])));
        }
        st_rlx((uint32_t*)(dst + 2048) + t128, pack2(ka[32], ka[34]));
        if (QHOLD == 3) bar_arrive(8, 256);
        if (t128 == 0) mbar_arrive(sm + bar3(60));
      }
      TS(5);
      uint32_t pq[16], pq0[16];
      auto q_mma = [&](float (&q)[32], uint32_t xo, int s0, int s1) {
#pragma unroll 1
        for (int s = s0; s < s1; s++) {
          const uint32_t xs = (xoff(s, wg) >> 4) + xo, ws = dlo(sb + woff(s), 8192);
          pin(q);
          wg_fence();
#pragma unroll
          for (int k = 0; k < 4; k++) wgmma_n64_ss<0, 1, 0>(q, dsc<1024, 1>(xs + k * 2), dsc<1024, 1>(ws + k * 128), 1);
          wg_commit();
        }
      };
      auto q_phi = [&](float (&q)[32], int m, uint32_t (&pq)[16], int lo, int hi) {
        scales(m, zero);
#pragma unroll
        for (int j = lo; j < hi; j++) { const uint4 r = phi8(q + j * 8); pq[j * 4] = r.x; pq[j * 4 + 1] = r.y; pq[j * 4 + 2] = r.z; pq[j * 4 + 3] = r.w; }
      };
      auto o_of = [&](uint32_t (&pq)[16], uint4 (&o)[4], uint4* first, bool pub) {
        float oa[2][20];
#pragma unroll
        for (int i = 0; i < 40; i++) oa[i / 20][i % 20] = 0.f;
        wg_fence();
#pragma unroll
        for (int ks = 0; ks < 4; ks++) {
          wgmma_n40_rs<1, 0>(oa[ks >> 1], pq[ks * 4], pq[ks * 4 + 1], pq[ks * 4 + 2], pq[ks * 4 + 3], dsc<1024, 1>(dlo(sb + OFF_KVB + ks * 2048, 8192)), ks & 1);
          if (ks & 1) wg_commit();
        }
#pragma unroll
        for (int h = 0; h < 2; h++) {
          if (h) wg_wait<0>(); else wg_wait<1>();
          pin(oa[h]);
          const float (&d)[20] = oa[h];
          const float i0 = rcp(d[16] + 1e-6f), i1 = rcp(d[18] + 1e-6f);
#pragma unroll
          for (int k2 = 0; k2 < 2; k2++) {
            o[h * 2 + k2] = make_uint4(pack2(d[k2 * 8] * i0, d[k2 * 8 + 1] * i0), pack2(d[k2 * 8 + 2] * i1, d[k2 * 8 + 3] * i1),
                                       pack2(d[k2 * 8 + 4] * i0, d[k2 * 8 + 5] * i0), pack2(d[k2 * 8 + 6] * i1, d[k2 * 8 + 7] * i1));
            if (pub && !h) st_rlx4(first + (h * 2 + k2) * 1024, o[h * 2 + k2]);
          }
        }
#pragma unroll
        for (int i = 0; i < 16; i++) asm volatile("" : "+r"(pq[i]) :: "memory");
      };
      bar_sync(wg ? 7 : 8, 256);
      TS(12);
      q_mma(qa1, xo1, 0, 4);
      if (wg) {
        if (QX) {
          pin(qa0);
          wg_fence();
#pragma unroll
          for (int k = 0; k < 4 * QX; k++) wgmma_n64_ss<0, 1, 0>(qa0, dsc<1024, 1>((xoff(k >> 2, 1) >> 4) + xo0 + (k & 3) * 2), dsc<1024, 1>(dlo(sb + woff(k >> 2), 8192) + (k & 3) * 128), 1);
          wg_commit();
        }
        bar_arrive(8, 256);
        wg_wait<QX ? 1 : 0>();
      }
      else { bar_arrive(7, 256); wg_wait<0>(); }
      TS(13);
      if (tid == 0) mbar_arrive(mb + B_EMPTY + 16);
      cut<5>(zero);
      pin(qa1);
      q_phi(qa1, 1, pq, 0, 4);
      tid2 = __shfl_sync(~0u, tid, lane);
      uint32_t done = 0;
#pragma unroll
      for (int j = 0; j < 8; j++) done |= pq[2 * j] | pq[2 * j + 1] | xr[j][3];
      bar_sync(wg ? 7 : 8, 256 + (done & zero));
      TS(9);
      q_mma(qa0, xo0, wg * QX, 4);
      if (!wg) bar_arrive(7, 256);
      wg_wait<0>();
      pin(qa0);
      if (t128 == 0) mbar_arrive(mb + B_EMPTY + 8 * wg);
      TS(6);
#pragma unroll
      for (int i = 0; i < 16; i++) pq0[i] = 0;
#pragma unroll 1
      for (int r = 0;; r++) {
      if (ASYM && r == wg) { pin(qa0); q_phi(qa0, 0, pq0, 0, ASYM); }
      if (r) break;
      {
        uint4 a, v[8];
        uint32_t z[8], zs;
        const int blk = warp * 2 + wg;
        mbar_wait(mb + B_KVL, 0);
        static_for<0, 8>([&](auto ic) { constexpr int i = decltype(ic)::value; v[i] = lds4_o<sb + 11 * SLOT_B + i * 512>(own + (blk + (blk & 4)) * 4096 + lane * 16); });
#pragma unroll
        for (int i = 0; i < 8; i++) z[i] = lds1(sm + 2 * SLOT_B + i * 512 + t128 * 4);
#pragma unroll 1
        for (int it = 0;; it++) {
          zs = hadd2(hadd2(hadd2(z[0], z[1]), hadd2(z[2], z[3])), hadd2(hadd2(z[4], z[5]), hadd2(z[6], z[7])));
          a = hadd8(hadd8(hadd8(v[0], v[1]), hadd8(v[2], v[3])), hadd8(hadd8(v[4], v[5]), hadd8(v[6], v[7])));
          TSV(20, it + 1);
          if (!__any_sync(~0u, hnan(hadd2(hadd2(hadd2(a.x, a.y), hadd2(a.z, a.w)), zs)))) break;
          uint32_t mm = 0;
#pragma unroll
          for (int i = 0; i < 8; i++) mm = max4(max(mm, z[i]), v[i]);
          if (!__any_sync(~0u, mm == SENT)) break;
#pragma unroll
          for (int i = 0; i < 8; i++) { v[i] = ld_rlx4(&G.kvp[cg * 2304 + blk * 256 + i * 32 + lane]); z[i] = ld_rlx((const uint32_t*)&G.kvp[cg * 2304 + 2048 + i * 32] + t128); }
          SPINCHK(it, 4);
        }
        TS(23);
        const uint32_t kb0 = sm + OFF_KVB + blk * 1024 + (lane & 7) * 128;
        stsm4(kb0 + (((lane >> 3) ^ (lane & 7)) << 4), a.x, a.y, a.z, a.w);
        asm volatile("stmatrix.sync.aligned.m8n8.x1.shared.b16 [%0], {%1};" :: "r"(kb0 + ((4 ^ (lane & 7)) << 4)), "r"(zs >> (16 * wg)) : "memory");
        fence_async_smem();
        bar_sync(12, 256);
      }
      TS(7);
      if (t128 == 0) mbar_arrive_rem((wg << 24) + sb + bar3(48));
      o_of(pq, abuf[1], &G.obuf[((mb3 ^ 1) * 64 + hf * 32 + c3) * 128 + (tid2 & 127)], true);
      to = clk();
      TS(29);
      }
      if (!ASYM) cut<4>(zero);
      pin(qa0);
      q_phi(qa0, 0, pq0, ASYM, 4);
      o_of(pq0, abuf[0], nullptr, false);
#pragma unroll
      for (int q = 0; q < 32; q++) { asm volatile("" : "+r"(xr[q >> 2][q & 3])); acc[q * 2] = bf_lo(xr[q >> 2][q & 3]); acc[q * 2 + 1] = bf_hi(xr[q >> 2][q & 3]); }
      pin(acc);
    }
    {
    const int t128 = tid2 & 127, lane = tid2 & 31, g = lane >> 2, t = lane & 3;
    TS(8);
    uint32_t wa[32][4];
    auto load_gu = [&](int f, int lo = 0, int hi = 8) {
      const uint32_t ad = own + ((lane >> 3) & 1) * 8192 + ((lane >> 4) * 8 + (lane & 7)) * 64 + ((warp ^ ((lane >> 1) & 3)) << 4) + ((GU_SLOTS >> (16 * wg + 4 * f)) & 15) * SLOT_B;
      static_for<0, 8>([&](auto ic) { constexpr int i = decltype(ic)::value; if (i >= lo && i < hi) ldsm4t_o<sb + i * 1024>(ad, wa[f * 8 + i]); });
    };
    {
      const uint32_t la = own + wg * 8192 + t128 * 16, fa = sm + wg * 256;
      int pv = tid2 & zero;
      auto second = [&]() {
        delay(to, BDELAY);
#pragma unroll
        for (int k = 2; k < 4; k++) st_rlx4(&G.obuf[((mb3 ^ 1) * 64 + hf * 32 + c3) * 128 + t128 + k * 1024], abuf[1][k]);
      };
      auto own_rows = [&](int at) {
#pragma unroll
        for (int k = 0; k < 4; k++) if (((OPOS >> (4 * k)) & 15) == at) st_rlx4(&G.obuf[(mb3 * 64 + cg * 4 + k) * 128 + t128], abuf[0][k]);
      };
      auto step = [&](const int p, auto jc) {
        constexpr int j = decltype(jc)::value;
        uint4 (&a)[4] = abuf[j == 3 ? 0 : (j + 1) % 3];
        uint4 (&n)[4] = abuf[j == 3 ? 1 : (j + 2) % 3];
        auto fetch = [&]() {
          const uint32_t ra = la + ((p + 1) & 3) * SLOT_B;
          mbar_wait(fa + bar3(0) + o3(p + 1), 0);
          n[0] = lds4_o<sb + 10 * SLOT_B>(ra); n[1] = lds4_o<sb + 10 * SLOT_B + 2048>(ra); n[2] = lds4_o<sb + 10 * SLOT_B + 4096>(ra); n[3] = lds4_o<sb + 10 * SLOT_B + 6144>(ra);
        };
        const bool early = j == 0 ? p > 1 : j == 1 ? true : j == 2 ? p < 15 : false;
        const uint32_t bs = dlo(sb, 8192) + (uint32_t)((WO_SLOTS >> (4 * p)) & 15) * (SLOT_B >> 4);
        if (early) fetch();
        if (p == 1) TS(28);
        pin(acc);
        wg_fence();
#pragma unroll
        for (int k = 0; k < 4; k++) {
          wgmma_n128_rs<1, 0>(acc, a[k].x, a[k].y, a[k].z, a[k].w, dsc<1024, 1>(bs + k * 128), 1);
          if (k == 0) { if (j != 2 || p < 15) mbar_wait(mb + B_FULL3 + 8 * p + 8, 0); wg_fence(); }
        }
        wg_commit();
        if (j == 3) {
#pragma unroll
          for (int i = 0; i < 4; i++) { abuf[2][i] = make_uint4(zero, zero, zero, zero); pin4(abuf[2][i]); }
          if (GUP == 0) { if (fidx >= 0) mbar_wait(mb + B_FULL, 0); load_gu(0); }
          if (GUP < 2) load_gu(1);
          if (B2POS == 1) second();
          own_rows(0);
          TS(24);
          fetch();
          TS(27);
        } else if (j == 0 && p == 1) { own_rows(2); fetch(); own_rows(3); }
        pv++;
        if (__any_sync(~0u, max(max4(max4(0, n[0]), n[1]), max4(max4(0, n[2]), n[3])) == SENT)) {
          const uint4* q = &G.obuf[(mb3 * 64 + chunk_of(pv) * 4) * 128 + t128];
#pragma unroll 1
          for (int it = 0;; it++) {
#pragma unroll
            for (int i = 0; i < 4; i++) n[i] = ld_rlx4(q + i * 128);
            TSV(21, _ts | 1 << pv);
            if (!__any_sync(~0u, max(max4(max4(0, n[0]), n[1]), max4(max4(0, n[2]), n[3])) == SENT)) break;
            SPINCHK(it, 5);
          }
        }
        if (lane == 0 && p < 11) mbar_arrive_rem((wg << 24) + sb + bar3(48) + o3(p + 1));
        wg_wait<1>();
        pin(acc);
        if (j < 3) {
#pragma unroll
          for (int i = 0; i < 4; i++) pin4(abuf[j][i]);
        }
        if (j == 3) own_rows(1); else if (j == 0 && p == 1) own_rows(4);
        if (lane == 0) mbar_arrive(sm + bar3(32) + o3(p));
      };
      if (B2POS == 0) second();
      if (GUP > 0) { if (fidx >= 0) mbar_wait(mb + B_FULL, 0); load_gu(0); }
      if (GUP == 2) load_gu(1);
      mbar_wait(mb + B_FULL3, 0);
      step(0, std::integral_constant<int, 3>{});
#pragma unroll 1
      for (int pp = 1; pp < 16; pp += 3) static_for<0, 3>([&](auto jc) { step(pp + decltype(jc)::value, jc); });
    }
    uint4 wb[4];
#pragma unroll
    for (int i = 0; i < 4; i++) wb[i] = lds4(sm + OFF_LNP + ((g & 1) ? t * 64 : 256) + i * 16);
    const float2 ah = lds2f(sm + OFF_MSC + 8);
    const int ta = __float_as_int((lane & 8) ? ah.y : ah.x);
    int sl = (ta & 7) * 4 + ((ta >> 3) & 1), son = lane < 16 && (ta >> 4) == wid;
    float sid = c3 ? 1.f : (float)((mb3 * 64 + (ta & 63)) * 16 + 1);
    uint4 *sp = &G.cst[(lane & 7) * 32 + (rb * 2 + hf) * 2 + ((lane >> 3) & 1)], *sq = &G.st2[mb3 * 64 + warp * 16 + (t & 1) * 8 + g];
    asm volatile("" : "+r"(sl), "+r"(son), "+f"(sid), "+l"(sp), "+l"(sq) :: "memory");
    if (T4) cut<7>(zero);
    wg_wait<0>();
    pin(acc);
#pragma unroll
    for (int i = 0; i < 4; i++) pin4(abuf[0][i]);
    TS(10);
    const uint32_t msc = sm + OFF_MSC;
    uint32_t hp[8][4];
    {
      float se[2][4], q[4] = {0.f, 0.f, 0.f, 0.f};
#pragma unroll
      for (int i = 0; i < 8; i++) se[i >> 2][i & 3] = 0.f;
#pragma unroll
      for (int j = 0; j < 8; j++) {
#pragma unroll
        for (int i = 0; i < 4; i++) { const float a = acc[j * 8 + i * 2], c = acc[j * 8 + i * 2 + 1]; hp[j][i] = pack2(a, c); q[i] = fmaf(a, a, fmaf(c, c, q[i])); }
        mma16816(se[j & 1], hp[j], (j & 1) ? wb[j >> 1].z : wb[j >> 1].x, (j & 1) ? wb[j >> 1].w : wb[j >> 1].y);
      }
      const bool od = t & 1;
      const float q0 = q[0] + q[2], q1 = q[1] + q[3];
      float qq = (od ? q1 : q0) + __shfl_xor_sync(~0u, od ? q0 : q1, 1);
      qq += __shfl_xor_sync(~0u, qq, 2);
      const float ss = od ? se[0][2] + se[1][2] : se[0][0] + se[1][0], ee = od ? se[0][3] + se[1][3] : se[0][1] + se[1][1];
      red4(son, sp, __shfl_sync(~0u, ss, sl), __shfl_sync(~0u, qq, sl), __shfl_sync(~0u, ee, sl), sid);
      red4(t < 2, sq, ss, qq, ee, 1.f);
#pragma unroll 1
      for (int c = 0; c < 2; c++) {
        const int tr = __float_as_int(c ? ah.y : ah.x);
        if ((tr >> 4) == wid && g == (tr & 7)) {
#pragma unroll
          for (int i = 0; i < 4; i++)
            st_rlx4(&G.hsel[((rb * 2 + hf) * 2 + c) * 128 + c3 * 16 + i * 4 + t], (tr & 8) ? make_uint4(hp[2 * i][1], hp[2 * i][3], hp[2 * i + 1][1], hp[2 * i + 1][3])
                                                                                           : make_uint4(hp[2 * i][0], hp[2 * i][2], hp[2 * i + 1][0], hp[2 * i + 1][2]));
        }
      }
      if (lane == 0) mbar_arrive(sm + bar3(61));
      TS(11);
    }
    uint32_t wd[8][2][4];
    const uint32_t da = sm + ((D_SLOTS >> (2 * (wid & 6))) & 15) * SLOT_B + (wid & 1) * 8192 + ((lane >> 4) * 8 + (lane & 7)) * 128 + ((((lane >> 3) & 1) ^ (lane & 7)) << 4);
    int pass = 0;
    if (!GUPOS) { if (fidx >= 0) mbar_wait(mb + B_FFN, 1); load_gu(2); load_gu(3); }
    {
      bar_sync(1, 256);
      const uint32_t ha = sm + HST + wid * 4096 + (lane & 15) * 256 + (((lane >> 4) ^ (lane & 7)) << 4);
      static_for<0, 8>([&](auto jc) { constexpr int j = decltype(jc)::value; stsm4_o<(j >> 2) * 128>(ha ^ ((j & 3) << 5), hp[j][0], hp[j][1], hp[j][2], hp[j][3]); });
      asm volatile("fence.acq_rel.cta;" ::: "memory");
      __syncwarp();
      if (lane == 0) mbar_arrive(sm + bar3(62));
    }
    auto load_d1 = [&]() {
      if (fidx >= 0) mbar_wait(mb + B_FFN + 8, 0);
      static_for<0, 8>([&](auto ic) { constexpr int i = decltype(ic)::value; ldsm4t_o<(i & 1) * 2048>(da ^ ((i >> 1) << 5), wd[i >> 1][i & 1]); });
    };
    if (GUPOS) { if (fidx >= 0) mbar_wait(mb + B_FFN, 1); load_gu(2); load_gu(3); }
    if (!D1POS) load_d1();
#pragma unroll 1
    for (;; pass++) {
      TS(15);
      mbar_wait(mb + B_SEL, 0);
      const uint4 sx = lds4(msc + 16 + pass * 32 + (lane & 16));
      TS(26);
      const uint4* xp = &G.hsel[sx.y * 128 + wid * 16 + (lane & 15)];
      uint4 xv = ld_rlx4(xp);
      if (D1POS == 1) load_d1();
#pragma unroll 1
      for (int it = 0; __any_sync(~0u, max4(0, xv) == SENT); it++) { xv = ld_rlx4(xp); SPINCHK(it, 7); }
      const float f = __uint_as_float(sx.z), n = __uint_as_float(sx.w);
      sts4(sm + OFF_XS + wid * 512 + ((lane & 12) * 2 + (lane >> 4) * 4 + t) * 16, pack2(fmaf(bf_lo(xv.x), f, n), fmaf(bf_hi(xv.x), f, n)), pack2(fmaf(bf_lo(xv.y), f, n), fmaf(bf_hi(xv.y), f, n)),
           pack2(fmaf(bf_lo(xv.z), f, n), fmaf(bf_hi(xv.z), f, n)), pack2(fmaf(bf_lo(xv.w), f, n), fmaf(bf_hi(xv.w), f, n)));
      if (wid == rb && (g & 3) == (cg >> 2)) sts4(msc + 96 + (lane >> 4) * 16 + t * 32, xv.x, xv.y, xv.z, xv.w);
      bar_sync(2 + wg, 128);
      TS(14);
      float gu[4][4];
#pragma unroll
      for (int i = 0; i < 16; i++) gu[i >> 2][i & 3] = 0.f;
      uint4 xb[4];
      static_for<0, 4>([&](auto ic) { constexpr int i = decltype(ic)::value; xb[i] = lds4_o<sb + OFF_XS + i * 128>(own + wg * 2048 + (lane >> 3) * 512 + (lane & 7) * 16); });
      if (D1POS == 2) load_d1();
#pragma unroll
      for (int i = 0; i < 16; i++) {
        const int ks = i & 7;
#pragma unroll
        for (int j = i < 8 ? 2 : 0; j < (i < 8 ? 4 : 2); j++) mma16816(gu[j], wa[j * 8 + ks], (ks & 1) ? xb[ks >> 1].z : xb[ks >> 1].x, (ks & 1) ? xb[ks >> 1].w : xb[ks >> 1].y);
        if (i == D2I) {
          if (D1POS == 3) load_d1();
          const uint32_t dd = da | ((__float_as_uint(gu[2][0]) | __float_as_uint(gu[3][0])) & zero);
          static_for<0, 8>([&](auto jc) { constexpr int j = decltype(jc)::value; ldsm4t_o<4096 + (j & 1) * 2048>(dd ^ ((j >> 1) << 5), wd[4 + (j >> 1)][j & 1]); });
          if (T1) cut<8>(zero);
#pragma unroll
          for (int j = 0; j < 4; j++) { pin(gu[j]); pin4(xb[j]); }
        }
      }
      {
        float o[4];
#pragma unroll
        for (int j = 0; j < 4; j++) o[j] = t == 0 ? gu[0][j] : t == 1 ? gu[1][j] : t == 2 ? gu[2][j] : gu[3][j];
        const float e0 = ((t & 2) ? o[2] : o[0]) + __shfl_xor_sync(~0u, (t & 2) ? o[0] : o[2], 2), e1 = ((t & 2) ? o[3] : o[1]) + __shfl_xor_sync(~0u, (t & 2) ? o[1] : o[3], 2);
        sts1(sm + OFF_XS + 4096 + tid2 * 4, __float_as_uint(((t & 1) ? e1 : e0) + __shfl_xor_sync(~0u, (t & 1) ? e0 : e1, 1)));
      }
      TS(25);
      mbar_wait(mb + B_SEL2, 0);
      const uint32_t miss = lds1(msc + 80);
      bar_sync(1, 256);
      if (pass || !miss) break;
      load_gu(2); load_gu(3);
    }
    {
      const uint4 p0 = lds4_o<sb + OFF_XS + 4096>(own + lane * 16), p1 = lds4_o<sb + OFF_XS + 4608>(own + lane * 16);
      const float g0 = __uint_as_float(p0.x) + __uint_as_float(p1.x), g1 = __uint_as_float(p0.y) + __uint_as_float(p1.y);
      const float u0 = __uint_as_float(p0.z) + __uint_as_float(p1.z), u1 = __uint_as_float(p0.w) + __uint_as_float(p1.w);
      const uint32_t act = pack2(g0 * rcp(1.f + ex2(-1.4426950408889634f * g0)) * u0, g1 * rcp(1.f + ex2(-1.4426950408889634f * g1)) * u1);
      uint32_t bq[4];
#pragma unroll
      for (int i = 0; i < 4; i++) {
        const uint32_t lo = __shfl_sync(~0u, act, i * 8 + 2 * t), hi = __shfl_sync(~0u, act, i * 8 + 2 * t + 1);
        bq[i] = __byte_perm(lo, hi, (g & 1) ? 0x7632 : 0x5410);
      }
      TS(16);
      float ya[8][4];
#pragma unroll
      for (int i = 0; i < 8; i++) { ya[i][0] = 0.f; ya[i][1] = 0.f; ya[i][2] = 0.f; ya[i][3] = 0.f; }
#pragma unroll
      for (int ks = 0; ks < 2; ks++)
#pragma unroll
        for (int i = 0; i < 8; i++) mma16816(ya[i], wd[i][ks], bq[ks * 2], bq[ks * 2 + 1]);
    if (fidx >= 0) {
      uint2* const yp = (uint2*)&G.ybuf[((wid * 16 + t * 2) * NFFN + fidx) * 4] + g;
#pragma unroll
      for (int h = 0; h < 2; h++) {
        float o[4];
#pragma unroll
        for (int j = 0; j < 4; j++) o[j] = t == 0 ? ya[h * 4][j] : t == 1 ? ya[h * 4 + 1][j] : t == 2 ? ya[h * 4 + 2][j] : ya[h * 4 + 3][j];
        st_rlx2(yp + h * (8 * NFFN * 8), __float_as_uint(o[0]), __float_as_uint(o[1]));
        st_rlx2(yp + h * (8 * NFFN * 8) + NFFN * 8, __float_as_uint(o[2]), __float_as_uint(o[3]));
      }
    }
    }
    const uint32_t ty = clk();
    TS(17);
    if (wid < 7) {
      const uint4* const yq = &G.ybuf[b * NFFN * 4 + wid * 64 + lane];
      const uint4 sel = lds4(msc + 16 + pass * 32 + (lane & 1) * 16);
      const uint32_t fh = lds1(msc + 96 + (lane & 1) * 16 + (g & 3) * 32 + (cg & 3) * 4);
      const float r = __uint_as_float(sel.x ^ (~(uint32_t)((int)sel.x >> 31) | 0x80000000u));
      float sg = rcp(1.f + ex2(-1.4426950408889634f * r)), base = fmaf((lane & 2) ? bf_hi(fh) : bf_lo(fh), 1.f + __uint_as_float(sel.z), __uint_as_float(sel.w));
      __nv_bfloat16* op = P.out + (size_t)(2047 - (sel.x & 2047)) * D_ + b * 8 + ((lane >> 1) & 7);
      asm volatile("" : "+f"(sg), "+f"(base), "+l"(op) :: "memory");
      delay(ty | (__float_as_uint(sg) & zero), YDELAY);
      uint4 v0, v1;
#pragma unroll 1
      for (int it = 0;; it++) {
        v0 = ld_rlx4(yq); v1 = ld_rlx4(yq + 32);
        TSV(22, it + 1);
        if (!__any_sync(~0u, max(max4(0, v0), max4(0, v1)) == SENT)) break;
        SPINCHK(it, 8);
      }
      if (lane == 0) mbar_arrive(sm + bar3(63));
      TS(18);
      float y0 = __uint_as_float(v0.x) + __uint_as_float(v1.x), y1 = __uint_as_float(v0.y) + __uint_as_float(v1.y);
      float y2 = __uint_as_float(v0.z) + __uint_as_float(v1.z), y3 = __uint_as_float(v0.w) + __uint_as_float(v1.w);
      float z0 = ((lane & 16) ? y2 : y0) + __shfl_xor_sync(~0u, (lane & 16) ? y0 : y2, 16), z1 = ((lane & 16) ? y3 : y1) + __shfl_xor_sync(~0u, (lane & 16) ? y1 : y3, 16);
      z0 = ((lane & 8) ? z1 : z0) + __shfl_xor_sync(~0u, (lane & 8) ? z0 : z1, 8);
      z0 += __shfl_xor_sync(~0u, z0, 4);
      const uint32_t yx = sm + OFF_COLSUM;
      if (!(lane & 4)) sts1(yx + (t * 4 + (lane >> 3)) * 32 + wid * 4, __float_as_uint(z0));
      if (wid) bar_arrive(1, 224);
      else {
        bar_sync(1, 224);
        const uint4 a = lds4(yx + (lane & 15) * 32), c = lds4(yx + (lane & 15) * 32 + 16);
        const float y = ((__uint_as_float(a.x) + __uint_as_float(a.y)) + (__uint_as_float(a.z) + __uint_as_float(a.w))) + ((__uint_as_float(c.x) + __uint_as_float(c.y)) + __uint_as_float(c.z));
        if (lane < 16) *op = __float2bfloat16(fmaf(y, sg, base));
      }
    }
    }
    TS(19); TSG(31);
    if (warp == 0) TS_DUMP(wg);
  }
}

typedef CUresult (*EncodeFn)(CUtensorMap*, CUtensorMapDataType, cuuint32_t, void*, const cuuint64_t*, const cuuint64_t*, const cuuint32_t*,
                             const cuuint32_t*, CUtensorMapInterleave, CUtensorMapSwizzle, CUtensorMapL2promotion, CUtensorMapFloatOOBfill);
void make_map(EncodeFn enc, CUtensorMap* m, const void* p, uint64_t cols, uint64_t rows, uint64_t d0, uint32_t b0, uint32_t b1, uint32_t b2, CUtensorMapSwizzle sw,
              CUtensorMapL2promotion promo = CU_TENSOR_MAP_L2_PROMOTION_L2_128B) {
  cuuint64_t dims[3] = {d0, rows, cols / d0}, str[2] = {cols * 2, d0 * 2};
  cuuint32_t box[3] = {b0, b1, b2}, es[3] = {1, 1, 1};
  enc(m, CU_TENSOR_MAP_DATA_TYPE_BFLOAT16, b2 ? 3 : 2, const_cast<void*>(p), dims, str, box, es, CU_TENSOR_MAP_INTERLEAVE_NONE, sw,
      promo, CU_TENSOR_MAP_FLOAT_OOB_FILL_NONE);
}

}

extern "C" void kernel_launch(void* const* d_in, const int* in_sizes, int n_in, void* d_out, int out_size) {
  (void)in_sizes; (void)n_in; (void)out_size;
  Ptrs P;
  P.x = (const __nv_bfloat16*)d_in[0]; P.wqkv = (const __nv_bfloat16*)d_in[1]; P.wo = (const __nv_bfloat16*)d_in[2];
  P.wr = (const __nv_bfloat16*)d_in[4]; P.wg = (const __nv_bfloat16*)d_in[5]; P.wu = (const __nv_bfloat16*)d_in[6];
  P.wd = (const __nv_bfloat16*)d_in[7]; P.out = (__nv_bfloat16*)d_out;
  void* fn = nullptr;
  cudaDriverEntryPointQueryResult q;
  cudaGetDriverEntryPoint("cuTensorMapEncodeTiled", &fn, cudaEnableDefault, &q);
  EncodeFn enc = (EncodeFn)fn;
  CUtensorMap tmX, tmW, tmO, tmG, tmU, tmD, tmM, tmPG, tmPU, tmPD;
  make_map(enc, &tmX, P.x, D_, S_, D_, 64, 128, 0, CU_TENSOR_MAP_SWIZZLE_128B);
  make_map(enc, &tmW, P.wqkv, 3 * D_, D_, 3 * D_, 64, 64, 0, CU_TENSOR_MAP_SWIZZLE_128B);
  make_map(enc, &tmG, P.wg, F_, D_, F_, 32, 128, 0, CU_TENSOR_MAP_SWIZZLE_64B);
  make_map(enc, &tmU, P.wu, F_, D_, F_, 32, 128, 0, CU_TENSOR_MAP_SWIZZLE_64B);
  make_map(enc, &tmD, P.wd, D_, F_, 64, 64, 32, 4, CU_TENSOR_MAP_SWIZZLE_128B);
  make_map(enc, &tmPG, P.wg, F_, D_, F_, 8, 32, 0, CU_TENSOR_MAP_SWIZZLE_NONE);
  make_map(enc, &tmPU, P.wu, F_, D_, F_, 8, 32, 0, CU_TENSOR_MAP_SWIZZLE_NONE);
  make_map(enc, &tmPD, P.wd, 128, F_ * 8, 128, 8, 32, 0, CU_TENSOR_MAP_SWIZZLE_NONE, CU_TENSOR_MAP_L2_PROMOTION_L2_256B);
  for (int m = 0; m < 2; m++) {
    cuuint64_t dims[4] = {64, m ? 64u : 16u, m ? 16u : 64u, 16}, str[3] = {2 * D_, (m ? 128u : 32u) * D_, 128};
    cuuint32_t box[4] = {64, 16, 4, 2}, es[4] = {1, 1, 1, 1};
    enc(m ? &tmM : &tmO, CU_TENSOR_MAP_DATA_TYPE_BFLOAT16, 4, const_cast<__nv_bfloat16*>(P.wo), dims, str, box, es, CU_TENSOR_MAP_INTERLEAVE_NONE,
        CU_TENSOR_MAP_SWIZZLE_128B, CU_TENSOR_MAP_L2_PROMOTION_L2_128B, CU_TENSOR_MAP_FLOAT_OOB_FILL_NONE);
  }
  cudaFuncSetAttribute(fused_kernel, cudaFuncAttributeMaxDynamicSharedMemorySize, SMEM_BYTES);
  fused_kernel<<<NCTA, 384, SMEM_BYTES>>>(P, tmX, tmW, tmO, tmG, tmU, tmD, tmM, tmPG, tmPU, tmPD);
}
```

```cpp
#include <cuda_runtime.h>
#include <cuda.h>
#include <cuda_bf16.h>
#include <stdint.h>
#include <type_traits>

namespace {

constexpr int S_ = 2048, D_ = 1024, F_ = 3584;
constexpr int NCTA = 128, NFFN = 112;
constexpr uint32_t SENT = 0xFFFFFFFFu;
constexpr int SPIN_LIMIT = 1 << 20;

#define ADELAY 900
#define NPK 0x233333333333ull
#define KDELAY 700
#define SBAR 2
#define NOOUT 0
#define OHOLD 72
#define OUTEF 0
#define CUTS 2
#define TMPF 1
#define INIF 0
#define DEV 0xFFEE
#define FDT 100
#define ASTEP 300
#define BDELAY 1100
#define GEV 0xDCCB
#define D1POS 1
#define GUPOS 1
#define ASYM 2
#define GUP 2
#define B6E 2
#define D2I 5
#define T1 1
#define T4 1
#define QX 0
#define B6H 2
#define XWPF 1
#define WDT 0
#define PRE 7
#define PD0 2
#define PDT 60
#define KORD 0xBA9F87E6D54C3210ull
#define SDELAY 450
#define LDELAY 500
#define NOSPEC 0
#define LOCK 1
#define STLD 2
#define RELK 1
#define PERT 7
#define QHOLD 3
#define CDELAY 0
#define YDELAY 500
#define EFX 0
#define EFW 1
#define EFF 1
#define GDELAY 800
#define PFST 1
#define OPOS 0x4411
#define B2POS 1
constexpr uint32_t STAGE_B = 57344;
__host__ __device__ constexpr uint32_t xoff(int s, int w) { return ((0x87CA3651u >> (4 * (s + 4 * w))) & 15) * 16384; }
__host__ __device__ constexpr uint32_t woff(int s) { return (s < 2 ? 9 * 16384 : 0) + (s & 1) * 8192; }
constexpr uint32_t WSTR = 32768;
constexpr uint32_t OFF_BARS = 229376;
constexpr uint32_t OFF_COLSUM = 229632;
constexpr uint32_t OFF_STATS = 230400;
constexpr uint32_t SMEM_BYTES = 232448;
constexpr uint32_t B_FULL = 0, B_EMPTY = 32, B_AUX = 64, B_SEL2 = 72, B_KVL = 80, B_FULL3 = 88, B_SW = 216, B_OUT = 224, B_LATE = 232, B_SEL = B_FULL + 8, B_FFN = 240;
__host__ __device__ constexpr uint32_t o3(int p) { return p * 8 + (p & 8) * 8; }
__host__ __device__ constexpr uint32_t bar3(int i) { return OFF_STATS + 1024 + (i >> 3) * 128 + ((i & 32) ? 0 : 64) + (i & 7) * 8; }
constexpr uint32_t SLOT_B = 16384;
constexpr uint32_t sb = 1024;
constexpr uint32_t bars = sb + OFF_BARS;
constexpr uint64_t WO_SLOTS = 0x8794208794208794ull;
constexpr uint32_t GU_SLOTS = 0x35356161u, D_SLOTS = 0x9420;
constexpr uint32_t HST = 7 * SLOT_B;
constexpr uint32_t OFF_LNP = OFF_STATS;
constexpr uint32_t OFF_MSC = OFF_COLSUM + 512;
constexpr uint32_t OFF_XS = 10 * SLOT_B;
constexpr uint32_t OFF_KVB = 2 * SLOT_B + 8192;

struct Scratch {
  uint4 st1[64 * 48];
  uint4 csp[16 * 8 * 48];
  uint4 kvp[16 * 2304];
  uint4 obuf[32 * 64 * 128];
  uint4 st2[S_];
  uint32_t pred[S_];
  uint4 cst[8 * 32];
  uint4 hsel[64 * 128];
  uint32_t cand[8 * 32];
  uint4 ybuf[NCTA * NFFN * 4];
  unsigned epoch;
};
__device__ __align__(1024) Scratch G;
#define TS_DECL
#define TS(i)
#define TSG(i)
#define TSV(i, v)
#define TS_DUMP(slot)
#define PTS(i)

__device__ __forceinline__ uint32_t smem_u32(const void* p) { return (uint32_t)__cvta_generic_to_shared(p); }
__device__ __forceinline__ void mbar_init(uint32_t bar, uint32_t cnt) { asm volatile("mbarrier.init.shared::cta.b64 [%0], %1;" :: "r"(bar), "r"(cnt) : "memory"); }
__device__ __forceinline__ void mbar_expect_tx(uint32_t bar, uint32_t bytes) { asm volatile("mbarrier.arrive.expect_tx.shared::cta.b64 _, [%0], %1;" :: "r"(bar), "r"(bytes) : "memory"); }
__device__ __forceinline__ void mbar_arrive(uint32_t bar) { asm volatile("mbarrier.arrive.shared::cta.b64 _, [%0];" :: "r"(bar) : "memory"); }
#define SPINCHK(it, code) if ((it) > SPIN_LIMIT) break
__device__ __forceinline__ void mbar_wait(uint32_t bar, uint32_t parity) {
  asm volatile("{\n.reg .pred p, q;\n.reg .u32 c;\nmov.u32 c, 0;\n"
               "WL:\nmbarrier.try_wait.parity.shared::cta.b64 p, [%0], %1;\nadd.u32 c, c, 1;\nsetp.lt.u32 q, c, 1048576;\n"
               "not.pred p, p;\nand.pred p, p, q;\n@p bra WL;\n}" :: "r"(bar), "r"(parity) : "memory");
}
__device__ __forceinline__ uint64_t l2_stream() { uint64_t p; asm("createpolicy.fractional.L2::evict_first.b64 %0, 1.0;" : "=l"(p)); return p; }
__device__ __forceinline__ void tma_2d(uint32_t dst, const CUtensorMap* tm, int c0, int c1, uint32_t bar, bool stream) {
  if (stream) asm volatile("cp.async.bulk.tensor.2d.shared::cluster.global.mbarrier::complete_tx::bytes.L2::cache_hint [%0], [%1, {%3, %4}], [%2], %5;"
                           :: "r"(dst), "l"(tm), "r"(bar), "r"(c0), "r"(c1), "l"(l2_stream()) : "memory");
  else asm volatile("cp.async.bulk.tensor.2d.shared::cluster.global.mbarrier::complete_tx::bytes [%0], [%1, {%3, %4}], [%2];"
                    :: "r"(dst), "l"(tm), "r"(bar), "r"(c0), "r"(c1) : "memory");
}
__device__ __forceinline__ void tma_3d(uint32_t dst, const CUtensorMap* tm, int c0, int c1, int c2, uint32_t bar, bool stream) {
  if (stream) asm volatile("cp.async.bulk.tensor.3d.shared::cluster.global.mbarrier::complete_tx::bytes.L2::cache_hint [%0], [%1, {%3, %4, %5}], [%2], %6;"
                           :: "r"(dst), "l"(tm), "r"(bar), "r"(c0), "r"(c1), "r"(c2), "l"(l2_stream()) : "memory");
  else asm volatile("cp.async.bulk.tensor.3d.shared::cluster.global.mbarrier::complete_tx::bytes [%0], [%1, {%3, %4, %5}], [%2];"
                    :: "r"(dst), "l"(tm), "r"(bar), "r"(c0), "r"(c1), "r"(c2) : "memory");
}
__device__ __forceinline__ void tma_2d_mc(uint32_t dst, const CUtensorMap* tm, int c0, int c1, uint32_t bar, bool stream) {
  if (stream) asm volatile("cp.async.bulk.tensor.2d.shared::cluster.global.mbarrier::complete_tx::bytes.multicast::cluster.L2::cache_hint [%0], [%1, {%3, %4}], [%2], %5, %6;"
                           :: "r"(dst), "l"(tm), "r"(bar), "r"(c0), "r"(c1), "h"((uint16_t)3), "l"(l2_stream()) : "memory");
  else asm volatile("cp.async.bulk.tensor.2d.shared::cluster.global.mbarrier::complete_tx::bytes.multicast::cluster [%0], [%1, {%3, %4}], [%2], %5;"
                    :: "r"(dst), "l"(tm), "r"(bar), "r"(c0), "r"(c1), "h"((uint16_t)3) : "memory");
}
__device__ __forceinline__ bool elect_one() {
  uint32_t p;
  asm volatile("{\n.reg .pred q;\nelect.sync _|q, 0xFFFFFFFF;\nselp.u32 %0, 1, 0, q;\n}" : "=r"(p));
  return p;
}
__device__ __forceinline__ void bulk_load_mc(uint32_t dst, const void* src, uint32_t bar, uint16_t mask) {
  asm volatile("cp.async.bulk.shared::cluster.global.mbarrier::complete_tx::bytes.multicast::cluster [%0], [%1], 8192, [%2], %3;"
               :: "r"(dst), "l"(src), "r"(bar), "h"(mask) : "memory");
}
__device__ __forceinline__ void bulk_load(uint32_t dst, const void* src, uint32_t bytes, uint32_t bar) {
  asm volatile("cp.async.bulk.shared::cluster.global.mbarrier::complete_tx::bytes [%0], [%1], %2, [%3];" :: "r"(dst), "l"(src), "r"(bytes), "r"(bar) : "memory");
}
__device__ __forceinline__ void mbar_arrive_rem(uint32_t bar) { asm volatile("mbarrier.arrive.shared::cluster.b64 _, [%0];" :: "r"(bar) : "memory"); }
template <uint32_t O> __device__ __forceinline__ void ldsm4_o(uint32_t addr, uint32_t& a, uint32_t& b, uint32_t& c, uint32_t& d) {
  asm volatile("ldmatrix.sync.aligned.m8n8.x4.shared.b16 {%0,%1,%2,%3}, [%4+%5];" : "=r"(a), "=r"(b), "=r"(c), "=r"(d) : "r"(addr), "n"(O) : "memory");
}
template <uint32_t O> __device__ __forceinline__ void ldsm4t_o(uint32_t addr, uint32_t (&r)[4]) {
  asm volatile("ldmatrix.sync.aligned.m8n8.x4.trans.shared.b16 {%0,%1,%2,%3}, [%4+%5];" : "=r"(r[0]), "=r"(r[1]), "=r"(r[2]), "=r"(r[3]) : "r"(addr), "n"(O) : "memory");
}
__device__ __forceinline__ void mma16816(float (&c)[4], const uint32_t (&a)[4], uint32_t b0, uint32_t b1) {
  asm("mma.sync.aligned.m16n8k16.row.col.f32.bf16.bf16.f32 {%0,%1,%2,%3}, {%4,%5,%6,%7}, {%8,%9}, {%0,%1,%2,%3};"
      : "+f"(c[0]), "+f"(c[1]), "+f"(c[2]), "+f"(c[3]) : "r"(a[0]), "r"(a[1]), "r"(a[2]), "r"(a[3]), "r"(b0), "r"(b1));
}
__device__ __forceinline__ void l2_prefetch(const void* p) { asm volatile("prefetch.global.L2 [%0];" :: "l"(p) : "memory"); }
__device__ __forceinline__ uint32_t clk() { uint32_t t; asm volatile("mov.u32 %0, %%clock;" : "=r"(t) :: "memory"); return t; }
__device__ __forceinline__ void delay(uint32_t t0, uint32_t n) { while (clk() - t0 < n) {} }
template <int ID> __device__ __forceinline__ void cut(uint32_t zero) { asm volatile("{\n.reg .pred p;\nsetp.eq.u32 p, %0, %1;\nCUT:\n@p nanosleep.u32 1;\n@p bra.uni CUT;\n}" :: "r"(zero), "n"(ID) : "memory"); }
__device__ __forceinline__ void tmap_prefetch(const CUtensorMap* tm) { asm volatile("prefetch.tensormap [%0];" :: "l"(tm) : "memory"); }
__device__ __forceinline__ void wg_fence() { asm volatile("wgmma.fence.sync.aligned;" ::: "memory"); }
__device__ __forceinline__ void wg_commit() { asm volatile("wgmma.commit_group.sync.aligned;" ::: "memory"); }
template <int N> __device__ __forceinline__ void wg_wait() { asm volatile("wgmma.wait_group.sync.aligned %0;" :: "n"(N) : "memory"); }
template <int N> __device__ __forceinline__ void pin(float (&d)[N]) {
#pragma unroll
  for (int i = 0; i < N; i++) asm volatile("" : "+f"(d[i]) :: "memory");
}
__device__ __forceinline__ void pin4(uint4& v) { asm volatile("" : "+r"(v.x), "+r"(v.y), "+r"(v.z), "+r"(v.w) :: "memory"); }
template <uint32_t SBO, uint32_t SWZ> __device__ __forceinline__ uint64_t dsc(uint32_t lo) { return ((uint64_t)((SBO >> 4) | (SWZ << 30)) << 32) | lo; }
__host__ __device__ constexpr uint32_t dlo(uint32_t addr, uint32_t lbo) { return (addr >> 4) | ((lbo >> 4) << 16); }
__device__ __forceinline__ void bar_sync(int id, int n) { asm volatile("bar.sync %0, %1;" :: "r"(id), "r"(n) : "memory"); }
__device__ __forceinline__ void bar_arrive(int id, int n) { asm volatile("bar.arrive %0, %1;" :: "r"(id), "r"(n) : "memory"); }
__device__ __forceinline__ void fence_async_smem() { asm volatile("fence.proxy.async.shared::cta;" ::: "memory"); }
__device__ __forceinline__ void fence_gpu() { asm volatile("fence.acq_rel.gpu;" ::: "memory"); }
__device__ __forceinline__ uint4 ld_cg4(const void* p) { uint4 v; asm volatile("ld.global.cg.v4.u32 {%0,%1,%2,%3}, [%4];" : "=r"(v.x), "=r"(v.y), "=r"(v.z), "=r"(v.w) : "l"(p) : "memory"); return v; }
__device__ __forceinline__ uint4 ld_rlx4(const void* p) { uint4 v; asm volatile("ld.relaxed.gpu.global.v4.u32 {%0,%1,%2,%3}, [%4];" : "=r"(v.x), "=r"(v.y), "=r"(v.z), "=r"(v.w) : "l"(p) : "memory"); return v; }
__device__ __forceinline__ uint32_t ld_rlx(const void* p) { uint32_t v; asm volatile("ld.relaxed.gpu.global.u32 %0, [%1];" : "=r"(v) : "l"(p) : "memory"); return v; }
__device__ __forceinline__ void st_rlx4(void* p, uint4 v) { asm volatile("st.relaxed.gpu.global.v4.u32 [%0], {%1,%2,%3,%4};" :: "l"(p), "r"(v.x), "r"(v.y), "r"(v.z), "r"(v.w) : "memory"); }
__device__ __forceinline__ void st_rlx2(void* p, uint32_t a, uint32_t b) { asm volatile("st.relaxed.gpu.global.v2.u32 [%0], {%1,%2};" :: "l"(p), "r"(a), "r"(b) : "memory"); }
__device__ __forceinline__ void st_rlx(void* p, uint32_t a) { asm volatile("st.relaxed.gpu.global.u32 [%0], %1;" :: "l"(p), "r"(a) : "memory"); }
__device__ __forceinline__ void red4(bool on, void* p, float a, float b, float c, float d) {
  asm volatile("{\n.reg .pred q;\nsetp.ne.b32 q, %5, 0;\n@q red.relaxed.gpu.global.add.v4.f32 [%0], {%1,%2,%3,%4};\n}" :: "l"(p), "f"(a), "f"(b), "f"(c), "f"(d), "r"((int)on) : "memory");
}
__device__ __forceinline__ uint32_t pack2(float lo, float hi) { uint32_t r; asm("cvt.rn.bf16x2.f32 %0, %1, %2;" : "=r"(r) : "f"(hi), "f"(lo)); return r; }
__device__ __forceinline__ float bf_lo(uint32_t v) { return __uint_as_float(v << 16); }
__device__ __forceinline__ float bf_hi(uint32_t v) { return __uint_as_float(v & 0xFFFF0000u); }
__device__ __forceinline__ void stsm4(uint32_t addr, uint32_t a, uint32_t b, uint32_t c, uint32_t d) {
  asm volatile("stmatrix.sync.aligned.m8n8.x4.shared.b16 [%0], {%1,%2,%3,%4};" :: "r"(addr), "r"(a), "r"(b), "r"(c), "r"(d) : "memory");
}
template <uint32_t O> __device__ __forceinline__ void stsm4_o(uint32_t addr, uint32_t a, uint32_t b, uint32_t c, uint32_t d) {
  asm volatile("stmatrix.sync.aligned.m8n8.x4.shared.b16 [%0+%5], {%1,%2,%3,%4};" :: "r"(addr), "r"(a), "r"(b), "r"(c), "r"(d), "n"(O) : "memory");
}
__device__ __forceinline__ void sts4(uint32_t addr, uint32_t a, uint32_t b, uint32_t c, uint32_t d) { asm volatile("st.shared.v4.u32 [%0], {%1,%2,%3,%4};" :: "r"(addr), "r"(a), "r"(b), "r"(c), "r"(d) : "memory"); }
__device__ __forceinline__ void sts2f(uint32_t addr, float a, float b) { asm volatile("st.shared.v2.f32 [%0], {%1,%2};" :: "r"(addr), "f"(a), "f"(b) : "memory"); }
__device__ __forceinline__ void sts1(uint32_t addr, uint32_t a) { asm volatile("st.shared.u32 [%0], %1;" :: "r"(addr), "r"(a) : "memory"); }
__device__ __forceinline__ float2 lds2f(uint32_t addr) { float2 v; asm volatile("ld.shared.v2.f32 {%0,%1}, [%2];" : "=f"(v.x), "=f"(v.y) : "r"(addr) : "memory"); return v; }
template <uint32_t O> __device__ __forceinline__ float2 lds2f_o(uint32_t addr) { float2 v; asm volatile("ld.shared.v2.f32 {%0,%1}, [%2+%3];" : "=f"(v.x), "=f"(v.y) : "r"(addr), "n"(O) : "memory"); return v; }
template <int I, int N, class F> __device__ __forceinline__ void static_for(F&& f) { if constexpr (I < N) { f(std::integral_constant<int, I>{}); static_for<I + 1, N>(f); } }
__device__ __forceinline__ uint4 lds4(uint32_t addr) { uint4 v; asm volatile("ld.shared.v4.u32 {%0,%1,%2,%3}, [%4];" : "=r"(v.x), "=r"(v.y), "=r"(v.z), "=r"(v.w) : "r"(addr) : "memory"); return v; }
__device__ __forceinline__ uint32_t lds1(uint32_t addr) { uint32_t v; asm volatile("ld.shared.u32 %0, [%1];" : "=r"(v) : "r"(addr) : "memory"); return v; }
__device__ __forceinline__ float ex2(float x) { float y; asm("ex2.approx.ftz.f32 %0, %1;" : "=f"(y) : "f"(x)); return y; }
__device__ __forceinline__ uint32_t max4(uint32_t m, const uint4& v) { return __vimax3_u32(__vimax3_u32(m, v.x, v.y), v.z, v.w); }
__device__ __forceinline__ float rsq(float x) { float y; asm("rsqrt.approx.ftz.f32 %0, %1;" : "=f"(y) : "f"(x)); return y; }
__device__ __forceinline__ float rcp(float x) { float y; asm("rcp.approx.ftz.f32 %0, %1;" : "=f"(y) : "f"(x)); return y; }
__device__ __forceinline__ uint2 ld_rlx2(const void* p) { uint2 v; asm volatile("ld.relaxed.gpu.global.v2.u32 {%0,%1}, [%2];" : "=r"(v.x), "=r"(v.y) : "l"(p) : "memory"); return v; }
template <uint32_t O> __device__ __forceinline__ uint4 lds4_o(uint32_t addr) { uint4 v; asm volatile("ld.shared.v4.u32 {%0,%1,%2,%3}, [%4+%5];" : "=r"(v.x), "=r"(v.y), "=r"(v.z), "=r"(v.w) : "r"(addr), "n"(O) : "memory"); return v; }
__device__ __forceinline__ uint32_t hadd2(uint32_t a, uint32_t b) { uint32_t r; asm("add.rn.bf16x2 %0, %1, %2;" : "=r"(r) : "r"(a), "r"(b)); return r; }
__device__ __forceinline__ uint4 hadd8(const uint4& a, const uint4& b) { return make_uint4(hadd2(a.x, b.x), hadd2(a.y, b.y), hadd2(a.z, b.z), hadd2(a.w, b.w)); }
__device__ __forceinline__ bool hnan(uint32_t a) { return (a & 0x7FFF0000u) > 0x7F800000u; }
__device__ __forceinline__ uint32_t hfma2(uint32_t a, uint32_t b, uint32_t c) { uint32_t r; asm("fma.rn.bf16x2 %0, %1, %2, %3;" : "=r"(r) : "r"(a), "r"(b), "r"(c)); return r; }
__device__ __forceinline__ uint32_t ordered(float v) { const uint32_t u = __float_as_uint(v); return u ^ ((uint32_t)((int)u >> 31) | 0x80000000u); }
__device__ __forceinline__ uint32_t route(const uint4& v, float sw, int row, float2& pr) {
  const float mean = __uint_as_float(v.x) * (1.f / D_);
  pr.x = rsq(fmaxf(fmaf(-mean, mean, __uint_as_float(v.y) * (1.f / D_)), 0.f) + 1e-5f);
  pr.y = -mean * pr.x;
  return min(ordered(pr.x * fmaf(-mean, sw, __uint_as_float(v.z))) & ~2047u, 0xFFFFF000u) | (2047 - row);
}
__device__ __forceinline__ uint2 top2(uint32_t a, uint32_t b, uint32_t c, uint32_t d) {
  const uint32_t h0 = max(a, b), h1 = max(c, d), h = max(h0, h1), l = __vimax3_u32(min(h0, h1), min(a, b), min(c, d));
  const uint32_t m1 = __reduce_max_sync(~0u, h);
  return make_uint2(m1, __reduce_max_sync(~0u, h == m1 ? l : h));
}
__device__ __forceinline__ uint32_t hmul2(uint32_t a, uint32_t b) { uint32_t r; asm("mul.rn.bf16x2 %0, %1, %2;" : "=r"(r) : "r"(a), "r"(b)); return r; }
__device__ __forceinline__ uint32_t phi2(float u0, float u1, uint32_t r2, float rl) {
  uint32_t p, r;
  asm("cvt.rn.relu.bf16x2.f32 %0, %1, %2;" : "=r"(p) : "f"(u1), "f"(u0));
  asm("fma.rn.bf16x2 %0, %1, %2, %3;" : "=r"(r) : "r"(p), "r"(r2), "r"(pack2(__saturatef(ex2(u0 * rl) + 1e-6f), __saturatef(ex2(u1 * rl) + 1e-6f))));
  return r;
}

template<int TA, int TB, int OFF, int SZ> __device__ __forceinline__ void wgmma_n192_ss(float (&d)[SZ], uint64_t da, uint64_t db, int scale_d) {
  asm volatile("{\n.reg .pred p;\nsetp.ne.b32 p, %98, 0;\n"
    "wgmma.mma_async.sync.aligned.m64n192k16.f32.bf16.bf16 {%0,%1,%2,%3,%4,%5,%6,%7,%8,%9,%10,%11,%12,%13,%14,%15,%16,%17,%18,%19,%20,%21,%22,%23,%24,%25,%26,%27,%28,%29,%30,%31,%32,%33,%34,%35,%36,%37,%38,%39,%40,%41,%42,%43,%44,%45,%46,%47,%48,%49,%50,%51,%52,%53,%54,%55,%56,%57,%58,%59,%60,%61,%62,%63,%64,%65,%66,%67,%68,%69,%70,%71,%72,%73,%74,%75,%76,%77,%78,%79,%80,%81,%82,%83,%84,%85,%86,%87,%88,%89,%90,%91,%92,%93,%94,%95}, %96, %97, p, 1, 1, %99, %100;\n}\n"
    : "+f"(d[OFF+0]), "+f"(d[OFF+1]), "+f"(d[OFF+2]), "+f"(d[OFF+3]), "+f"(d[OFF+4]), "+f"(d[OFF+5]), "+f"(d[OFF+6]), "+f"(d[OFF+7]),
      "+f"(d[OFF+8]), "+f"(d[OFF+9]), "+f"(d[OFF+10]), "+f"(d[OFF+11]), "+f"(d[OFF+12]), "+f"(d[OFF+13]), "+f"(d[OFF+14]), "+f"(d[OFF+15]),
      "+f"(d[OFF+16]), "+f"(d[OFF+17]), "+f"(d[OFF+18]), "+f"(d[OFF+19]), "+f"(d[OFF+20]), "+f"(d[OFF+21]), "+f"(d[OFF+22]), "+f"(d[OFF+23]),
      "+f"(d[OFF+24]), "+f"(d[OFF+25]), "+f"(d[OFF+26]), "+f"(d[OFF+27]), "+f"(d[OFF+28]), "+f"(d[OFF+29]), "+f"(d[OFF+30]), "+f"(d[OFF+31]),
      "+f"(d[OFF+32]), "+f"(d[OFF+33]), "+f"(d[OFF+34]), "+f"(d[OFF+35]), "+f"(d[OFF+36]), "+f"(d[OFF+37]), "+f"(d[OFF+38]), "+f"(d[OFF+39]),
      "+f"(d[OFF+40]), "+f"(d[OFF+41]), "+f"(d[OFF+42]), "+f"(d[OFF+43]), "+f"(d[OFF+44]), "+f"(d[OFF+45]), "+f"(d[OFF+46]), "+f"(d[OFF+47]),
      "+f"(d[OFF+48]), "+f"(d[OFF+49]), "+f"(d[OFF+50]), "+f"(d[OFF+51]), "+f"(d[OFF+52]), "+f"(d[OFF+53]), "+f"(d[OFF+54]), "+f"(d[OFF+55]),
      "+f"(d[OFF+56]), "+f"(d[OFF+57]), "+f"(d[OFF+58]), "+f"(d[OFF+59]), "+f"(d[OFF+60]), "+f"(d[OFF+61]), "+f"(d[OFF+62]), "+f"(d[OFF+63]),
      "+f"(d[OFF+64]), "+f"(d[OFF+65]), "+f"(d[OFF+66]), "+f"(d[OFF+67]), "+f"(d[OFF+68]), "+f"(d[OFF+69]), "+f"(d[OFF+70]), "+f"(d[OFF+71]),
      "+f"(d[OFF+72]), "+f"(d[OFF+73]), "+f"(d[OFF+74]), "+f"(d[OFF+75]), "+f"(d[OFF+76]), "+f"(d[OFF+77]), "+f"(d[OFF+78]), "+f"(d[OFF+79]),
      "+f"(d[OFF+80]), "+f"(d[OFF+81]), "+f"(d[OFF+82]), "+f"(d[OFF+83]), "+f"(d[OFF+84]), "+f"(d[OFF+85]), "+f"(d[OFF+86]), "+f"(d[OFF+87]),
      "+f"(d[OFF+88]), "+f"(d[OFF+89]), "+f"(d[OFF+90]), "+f"(d[OFF+91]), "+f"(d[OFF+92]), "+f"(d[OFF+93]), "+f"(d[OFF+94]), "+f"(d[OFF+95])
    : "l"(da), "l"(db), "r"(scale_d), "n"(TA), "n"(TB));
}
template<int TA, int TB, int OFF, int SZ> __device__ __forceinline__ void wgmma_n128_ss(float (&d)[SZ], uint64_t da, uint64_t db, int scale_d) {
  asm volatile("{\n.reg .pred p;\nsetp.ne.b32 p, %66, 0;\n"
    "wgmma.mma_async.sync.aligned.m64n128k16.f32.bf16.bf16 {%0,%1,%2,%3,%4,%5,%6,%7,%8,%9,%10,%11,%12,%13,%14,%15,%16,%17,%18,%19,%20,%21,%22,%23,%24,%25,%26,%27,%28,%29,%30,%31,%32,%33,%34,%35,%36,%37,%38,%39,%40,%41,%42,%43,%44,%45,%46,%47,%48,%49,%50,%51,%52,%53,%54,%55,%56,%57,%58,%59,%60,%61,%62,%63}, %64, %65, p, 1, 1, %67, %68;\n}\n"
    : "+f"(d[OFF+0]), "+f"(d[OFF+1]), "+f"(d[OFF+2]), "+f"(d[OFF+3]), "+f"(d[OFF+4]), "+f"(d[OFF+5]), "+f"(d[OFF+6]), "+f"(d[OFF+7]),
      "+f"(d[OFF+8]), "+f"(d[OFF+9]), "+f"(d[OFF+10]), "+f"(d[OFF+11]), "+f"(d[OFF+12]), "+f"(d[OFF+13]), "+f"(d[OFF+14]), "+f"(d[OFF+15]),
      "+f"(d[OFF+16]), "+f"(d[OFF+17]), "+f"(d[OFF+18]), "+f"(d[OFF+19]), "+f"(d[OFF+20]), "+f"(d[OFF+21]), "+f"(d[OFF+22]), "+f"(d[OFF+23]),
      "+f"(d[OFF+24]), "+f"(d[OFF+25]), "+f"(d[OFF+26]), "+f"(d[OFF+27]), "+f"(d[OFF+28]), "+f"(d[OFF+29]), "+f"(d[OFF+30]), "+f"(d[OFF+31]),
      "+f"(d[OFF+32]), "+f"(d[OFF+33]), "+f"(d[OFF+34]), "+f"(d[OFF+35]), "+f"(d[OFF+36]), "+f"(d[OFF+37]), "+f"(d[OFF+38]), "+f"(d[OFF+39]),
      "+f"(d[OFF+40]), "+f"(d[OFF+41]), "+f"(d[OFF+42]), "+f"(d[OFF+43]), "+f"(d[OFF+44]), "+f"(d[OFF+45]), "+f"(d[OFF+46]), "+f"(d[OFF+47]),
      "+f"(d[OFF+48]), "+f"(d[OFF+49]), "+f"(d[OFF+50]), "+f"(d[OFF+51]), "+f"(d[OFF+52]), "+f"(d[OFF+53]), "+f"(d[OFF+54]), "+f"(d[OFF+55]),
      "+f"(d[OFF+56]), "+f"(d[OFF+57]), "+f"(d[OFF+58]), "+f"(d[OFF+59]), "+f"(d[OFF+60]), "+f"(d[OFF+61]), "+f"(d[OFF+62]), "+f"(d[OFF+63])
    : "l"(da), "l"(db), "r"(scale_d), "n"(TA), "n"(TB));
}
template<int TA, int TB, int OFF, int SZ> __device__ __forceinline__ void wgmma_n64_ss(float (&d)[SZ], uint64_t da, uint64_t db, int scale_d) {
  asm volatile("{\n.reg .pred p;\nsetp.ne.b32 p, %34, 0;\n"
    "wgmma.mma_async.sync.aligned.m64n64k16.f32.bf16.bf16 {%0,%1,%2,%3,%4,%5,%6,%7,%8,%9,%10,%11,%12,%13,%14,%15,%16,%17,%18,%19,%20,%21,%22,%23,%24,%25,%26,%27,%28,%29,%30,%31}, %32, %33, p, 1, 1, %35, %36;\n}\n"
    : "+f"(d[OFF+0]), "+f"(d[OFF+1]), "+f"(d[OFF+2]), "+f"(d[OFF+3]), "+f"(d[OFF+4]), "+f"(d[OFF+5]), "+f"(d[OFF+6]), "+f"(d[OFF+7]),
      "+f"(d[OFF+8]), "+f"(d[OFF+9]), "+f"(d[OFF+10]), "+f"(d[OFF+11]), "+f"(d[OFF+12]), "+f"(d[OFF+13]), "+f"(d[OFF+14]), "+f"(d[OFF+15]),
      "+f"(d[OFF+16]), "+f"(d[OFF+17]), "+f"(d[OFF+18]), "+f"(d[OFF+19]), "+f"(d[OFF+20]), "+f"(d[OFF+21]), "+f"(d[OFF+22]), "+f"(d[OFF+23]),
      "+f"(d[OFF+24]), "+f"(d[OFF+25]), "+f"(d[OFF+26]), "+f"(d[OFF+27]), "+f"(d[OFF+28]), "+f"(d[OFF+29]), "+f"(d[OFF+30]), "+f"(d[OFF+31])
    : "l"(da), "l"(db), "r"(scale_d), "n"(TA), "n"(TB));
}
template<int TB, int OFF, int SZ> __device__ __forceinline__ void wgmma_n64_rs(float (&d)[SZ], uint32_t a0, uint32_t a1, uint32_t a2, uint32_t a3, uint64_t db, int scale_d) {
  asm volatile("{\n.reg .pred p;\nsetp.ne.b32 p, %37, 0;\n"
    "wgmma.mma_async.sync.aligned.m64n64k16.f32.bf16.bf16 {%0,%1,%2,%3,%4,%5,%6,%7,%8,%9,%10,%11,%12,%13,%14,%15,%16,%17,%18,%19,%20,%21,%22,%23,%24,%25,%26,%27,%28,%29,%30,%31}, {%32,%33,%34,%35}, %36, p, 1, 1, %38;\n}\n"
    : "+f"(d[OFF+0]), "+f"(d[OFF+1]), "+f"(d[OFF+2]), "+f"(d[OFF+3]), "+f"(d[OFF+4]), "+f"(d[OFF+5]), "+f"(d[OFF+6]), "+f"(d[OFF+7]),
      "+f"(d[OFF+8]), "+f"(d[OFF+9]), "+f"(d[OFF+10]), "+f"(d[OFF+11]), "+f"(d[OFF+12]), "+f"(d[OFF+13]), "+f"(d[OFF+14]), "+f"(d[OFF+15]),
      "+f"(d[OFF+16]), "+f"(d[OFF+17]), "+f"(d[OFF+18]), "+f"(d[OFF+19]), "+f"(d[OFF+20]), "+f"(d[OFF+21]), "+f"(d[OFF+22]), "+f"(d[OFF+23]),
      "+f"(d[OFF+24]), "+f"(d[OFF+25]), "+f"(d[OFF+26]), "+f"(d[OFF+27]), "+f"(d[OFF+28]), "+f"(d[OFF+29]), "+f"(d[OFF+30]), "+f"(d[OFF+31])
    : "r"(a0), "r"(a1), "r"(a2), "r"(a3), "l"(db), "r"(scale_d), "n"(TB));
}
template<int TA, int TB, int OFF, int SZ> __device__ __forceinline__ void wgmma_n72_ss(float (&d)[SZ], uint64_t da, uint64_t db, int scale_d) {
  asm volatile("{\n.reg .pred p;\nsetp.ne.b32 p, %38, 0;\n"
    "wgmma.mma_async.sync.aligned.m64n72k16.f32.bf16.bf16 {%0,%1,%2,%3,%4,%5,%6,%7,%8,%9,%10,%11,%12,%13,%14,%15,%16,%17,%18,%19,%20,%21,%22,%23,%24,%25,%26,%27,%28,%29,%30,%31,%32,%33,%34,%35}, %36, %37, p, 1, 1, %39, %40;\n}\n"
    : "+f"(d[OFF+0]), "+f"(d[OFF+1]), "+f"(d[OFF+2]), "+f"(d[OFF+3]), "+f"(d[OFF+4]), "+f"(d[OFF+5]), "+f"(d[OFF+6]), "+f"(d[OFF+7]),
      "+f"(d[OFF+8]), "+f"(d[OFF+9]), "+f"(d[OFF+10]), "+f"(d[OFF+11]), "+f"(d[OFF+12]), "+f"(d[OFF+13]), "+f"(d[OFF+14]), "+f"(d[OFF+15]),
      "+f"(d[OFF+16]), "+f"(d[OFF+17]), "+f"(d[OFF+18]), "+f"(d[OFF+19]), "+f"(d[OFF+20]), "+f"(d[OFF+21]), "+f"(d[OFF+22]), "+f"(d[OFF+23]),
      "+f"(d[OFF+24]), "+f"(d[OFF+25]), "+f"(d[OFF+26]), "+f"(d[OFF+27]), "+f"(d[OFF+28]), "+f"(d[OFF+29]), "+f"(d[OFF+30]), "+f"(d[OFF+31]),
      "+f"(d[OFF+32]), "+f"(d[OFF+33]), "+f"(d[OFF+34]), "+f"(d[OFF+35])
    : "l"(da), "l"(db), "r"(scale_d), "n"(TA), "n"(TB));
}
template<int TB, int OFF, int SZ> __device__ __forceinline__ void wgmma_n40_rs(float (&d)[SZ], uint32_t a0, uint32_t a1, uint32_t a2, uint32_t a3, uint64_t db, int scale_d) {
  asm volatile("{\n.reg .pred p;\nsetp.ne.b32 p, %25, 0;\n"
    "wgmma.mma_async.sync.aligned.m64n40k16.f32.bf16.bf16 {%0,%1,%2,%3,%4,%5,%6,%7,%8,%9,%10,%11,%12,%13,%14,%15,%16,%17,%18,%19}, {%20,%21,%22,%23}, %24, p, 1, 1, %26;\n}\n"
    : "+f"(d[OFF+0]), "+f"(d[OFF+1]), "+f"(d[OFF+2]), "+f"(d[OFF+3]), "+f"(d[OFF+4]), "+f"(d[OFF+5]), "+f"(d[OFF+6]), "+f"(d[OFF+7]),
      "+f"(d[OFF+8]), "+f"(d[OFF+9]), "+f"(d[OFF+10]), "+f"(d[OFF+11]), "+f"(d[OFF+12]), "+f"(d[OFF+13]), "+f"(d[OFF+14]), "+f"(d[OFF+15]),
      "+f"(d[OFF+16]), "+f"(d[OFF+17]), "+f"(d[OFF+18]), "+f"(d[OFF+19])
    : "r"(a0), "r"(a1), "r"(a2), "r"(a3), "l"(db), "r"(scale_d), "n"(TB));
}
template<int TB, int OFF, int SZ> __device__ __forceinline__ void wgmma_n128_rs(float (&d)[SZ], uint32_t a0, uint32_t a1, uint32_t a2, uint32_t a3, uint64_t db, int scale_d) {
  asm volatile("{\n.reg .pred p;\nsetp.ne.b32 p, %69, 0;\n"
    "wgmma.mma_async.sync.aligned.m64n128k16.f32.bf16.bf16 {%0,%1,%2,%3,%4,%5,%6,%7,%8,%9,%10,%11,%12,%13,%14,%15,%16,%17,%18,%19,%20,%21,%22,%23,%24,%25,%26,%27,%28,%29,%30,%31,%32,%33,%34,%35,%36,%37,%38,%39,%40,%41,%42,%43,%44,%45,%46,%47,%48,%49,%50,%51,%52,%53,%54,%55,%56,%57,%58,%59,%60,%61,%62,%63}, {%64,%65,%66,%67}, %68, p, 1, 1, %70;\n}\n"
    : "+f"(d[OFF+0]), "+f"(d[OFF+1]), "+f"(d[OFF+2]), "+f"(d[OFF+3]), "+f"(d[OFF+4]), "+f"(d[OFF+5]), "+f"(d[OFF+6]), "+f"(d[OFF+7]),
      "+f"(d[OFF+8]), "+f"(d[OFF+9]), "+f"(d[OFF+10]), "+f"(d[OFF+11]), "+f"(d[OFF+12]), "+f"(d[OFF+13]), "+f"(d[OFF+14]), "+f"(d[OFF+15]),
      "+f"(d[OFF+16]), "+f"(d[OFF+17]), "+f"(d[OFF+18]), "+f"(d[OFF+19]), "+f"(d[OFF+20]), "+f"(d[OFF+21]), "+f"(d[OFF+22]), "+f"(d[OFF+23]),
      "+f"(d[OFF+24]), "+f"(d[OFF+25]), "+f"(d[OFF+26]), "+f"(d[OFF+27]), "+f"(d[OFF+28]), "+f"(d[OFF+29]), "+f"(d[OFF+30]), "+f"(d[OFF+31]),
      "+f"(d[OFF+32]), "+f"(d[OFF+33]), "+f"(d[OFF+34]), "+f"(d[OFF+35]), "+f"(d[OFF+36]), "+f"(d[OFF+37]), "+f"(d[OFF+38]), "+f"(d[OFF+39]),
      "+f"(d[OFF+40]), "+f"(d[OFF+41]), "+f"(d[OFF+42]), "+f"(d[OFF+43]), "+f"(d[OFF+44]), "+f"(d[OFF+45]), "+f"(d[OFF+46]), "+f"(d[OFF+47]),
      "+f"(d[OFF+48]), "+f"(d[OFF+49]), "+f"(d[OFF+50]), "+f"(d[OFF+51]), "+f"(d[OFF+52]), "+f"(d[OFF+53]), "+f"(d[OFF+54]), "+f"(d[OFF+55]),
      "+f"(d[OFF+56]), "+f"(d[OFF+57]), "+f"(d[OFF+58]), "+f"(d[OFF+59]), "+f"(d[OFF+60]), "+f"(d[OFF+61]), "+f"(d[OFF+62]), "+f"(d[OFF+63])
    : "r"(a0), "r"(a1), "r"(a2), "r"(a3), "l"(db), "r"(scale_d), "n"(TB));
}

struct Ptrs { const __nv_bfloat16 *x, *wqkv, *wo, *wr, *wg, *wu, *wd; __nv_bfloat16* out; };

__global__ void __cluster_dims__(2, 1, 1) __launch_bounds__(384, 1) fused_kernel(const Ptrs P, const __grid_constant__ CUtensorMap tmX, const __grid_constant__ CUtensorMap tmW,
                                                       const __grid_constant__ CUtensorMap tmO, const __grid_constant__ CUtensorMap tmG,
                                                       const __grid_constant__ CUtensorMap tmU, const __grid_constant__ CUtensorMap tmD,
                                                       const __grid_constant__ CUtensorMap tmM, const __grid_constant__ CUtensorMap tmPG,
                                                       const __grid_constant__ CUtensorMap tmPU, const __grid_constant__ CUtensorMap tmPD) {
  extern __shared__ __align__(1024) uint8_t smem_raw[];
  if (TMPF && threadIdx.x == 0) { tmap_prefetch(&tmX); tmap_prefetch(&tmW); }
  const int tid = threadIdx.x, wid = __shfl_sync(~0u, tid >> 5, 0), wg = __shfl_sync(~0u, tid >> 7, 0), lane = tid & 31;
  const int pj = blockIdx.x >> 1, pi = pj - 36;
  const int b = (pj < 4 ? 32 + pj * 8 : pj < 36 ? pj - 4 : 33 + pi + ((pi * 37) >> 8)) * 2 + (blockIdx.x & 1);
  const int rb = b >> 4, cg = b & 15, hf = cg >> 3, c3 = cg & 7;
  const int jp = cg >> 1;
  const int fidx = jp == rb ? -1 : b - 2 * rb - (jp > rb ? 2 : 0);
  const uint32_t rank = b & 1, own = rank << 24;
  const uint32_t zero = gridDim.y - 1;
  const uint32_t sm = own + sb, mb = own + bars;
  const uint64_t chunks = 0x1765432FEDCBA980ull ^ ((cg & 8) * 0x1111111111111111ull) ^ ((cg & 6) * 0x1111111000000001ull) ^ ((cg & 1) * 0x1000000000000001ull);
  auto chunk_of = [&](int p) { return (int)(chunks >> (4 * p)) & 15; };
  const int kl = (jp & 3) * 256;
  auto k_of = [&](int kb) { return kb >= 12 ? kl + (kb - 12) * 64 : kb * 64 < kl ? kb * 64 : kb * 64 + 256; };
  auto load_w = [&](int kb) {
#pragma unroll
    for (int i = 0; i < 3; i++) tma_2d(sm + woff(kb & 3) + i * WSTR, &tmW, i * D_ + cg * 64, k_of(kb), mb + B_FULL + 8 * (kb & 3), EFW);
  };
  if (XWPF && tid >= 32 && tid < 128) {
    const int k0 = kl ? 0 : 256;
    if (tid < 56) l2_prefetch(P.wqkv + (k0 + rb * 8 + (lane & 7)) * 3072 + (lane >> 3) * 1024 + cg * 64);
    else if (tid >= 64 && (!kl || tid < 86)) l2_prefetch(P.x + (rb * 256 + (kl ? min((cg - 2 - 2 * hf) * 22 + lane, 255) : (hf * 2 + rank) * 64 + tid - 64)) * D_ + k0);
  }
  TS_DECL; TS(0); TSG(30);
  if (wid == 8) {
    if (elect_one()) {
      if (smem_u32(smem_raw) != sm) {
#pragma unroll
        for (int i = 0; i < PERT; i++) sts1(mb, lds1(mb));
        asm volatile("trap;");
      }
#pragma unroll
      for (int s = 0; s < 4; s++) mbar_init(mb + B_FULL + 8 * s, 1);
      asm volatile("fence.mbarrier_init.release.cluster;" ::: "memory");
      if (INIF) fence_async_smem();
    }
  } else if (wid == 9) {
    if (elect_one()) {
#pragma unroll
      for (int i = 4; i < 32; i++)
        if (i != 27) mbar_init(mb + 8 * i, i < 8 ? 8 : i == 8 ? 64 : i == 26 ? 2 : i == 29 ? 4 : 1);
      asm volatile("fence.mbarrier_init.release.cluster;" ::: "memory");
      if (INIF) fence_async_smem();
    }
  }
  __syncwarp();
  asm volatile("barrier.cluster.arrive.relaxed.aligned;" ::: "memory");
  if (wid == 8) {
    if (elect_one()) {
      mbar_expect_tx(mb + B_FULL, STAGE_B);
      tma_2d(sm + xoff(0, 0), &tmX, k_of(0), rb * 256, mb + B_FULL, EFX);
      tma_2d(sm + xoff(0, 1), &tmX, k_of(0), rb * 256 + 128, mb + B_FULL, EFX);
      load_w(0);
    }
    __syncwarp();
  }
  asm volatile("barrier.cluster.wait.aligned;" ::: "memory");

  if (wg == 2) {
    asm volatile("setmaxnreg.dec.sync.aligned.u32 56;");
    auto wait3 = [&](int i) { mbar_wait(sm + bar3(i), 0); };
    if (wid == 8) {
      int np = fidx >= 0 ? 0 : 32;
      if (fidx >= 0 && elect_one()) mbar_expect_tx(mb + B_FFN, 32 * 512);
#pragma unroll 1
      for (int kb = 1; kb < 16; kb++) {
        const uint32_t fb = mb + B_FULL + 8 * (kb & 3);
        uint32_t dx = sm + xoff(kb & 3, rank), dw = sm + woff(kb & 3);
        int k0 = k_of(kb);
        if (PRE & 4) asm volatile("" : "+r"(dx), "+r"(dw), "+r"(k0));
        mbar_wait(fb + B_EMPTY, ((kb >> 2) & 1) ^ 1);
        if (elect_one()) {
          tma_2d_mc(dx, &tmX, k0, rb * 256 + rank * 128, fb, EFX);
#pragma unroll
          for (int i = 2; i >= 0; i--) tma_2d(dw + i * WSTR, &tmW, i * D_ + cg * 64, k0, fb, EFW);
          mbar_expect_tx(fb, STAGE_B);
          if (kb >= 12) asm volatile("mbarrier.arrive.shared::cta.b64 _, [%0], 7;" :: "r"(fb + B_EMPTY) : "memory");
        }
#pragma unroll 1
        for (int n = ((NPK << 16) >> (4 * kb)) & 15; n > 0 && np < 32; n--, np++)
          if (elect_one()) tma_2d(sm + OFF_STATS + 512, (np & 1) ? &tmPU : &tmPG, (fidx >> 1) * 64, (np >> 1) * 64 + rank * 32, mb + B_FFN, false);
      }
      if (fidx >= 0) mbar_wait(mb + B_FFN, 0);
      if (elect_one()) {
        mbar_expect_tx(mb + B_FFN, 65536 + 8 * 512); mbar_expect_tx(mb + B_FFN + 8, 65536); mbar_expect_tx(mb + B_KVL, 36864);
#pragma unroll
        for (int p = 4; p < 8; p++) sts4(sm + OFF_STATS + p * 144, 0x3F803F80u, 0x3F803F80u, 0x3F803F80u, 0x3F803F80u);
        fence_async_smem();
        mbar_arrive(mb + B_LATE);
      }
      PTS(2);
      mbar_wait(mb + B_LATE, 0);
      wait3(60);
      delay(clk(), KDELAY);
      if (elect_one()) {
        bulk_load(sm + 11 * SLOT_B, &G.kvp[cg * 2304], SLOT_B, mb + B_KVL);
        bulk_load(sm + 13 * SLOT_B, &G.kvp[cg * 2304 + 1024], SLOT_B, mb + B_KVL);
        bulk_load(sm + 2 * SLOT_B, &G.kvp[cg * 2304 + 2048], 4096, mb + B_KVL);
      }
      PTS(3);
      const uint4* src = &G.obuf[(rb * 4 + rank * 2 + hf) * 64 * 128];
      wait3(48);
      const uint32_t t1 = clk();
#pragma unroll 1
      for (int p = 1; p < 16; p++) {
        uint32_t d = sm + (10 + (p & 3)) * SLOT_B + rank * 8192, fb = sm + bar3(0) + o3(p) + rank * 256;
        const uint4* q = src + chunk_of(p) * 512;
        if (PRE & 1) asm volatile("" : "+r"(d), "+r"(fb), "+l"(q));
        if (p < 5) delay(t1, ADELAY + (p - 1) * ASTEP);
        else mbar_wait(sm + bar3(48) + o3(p - 4), 0);
        if (elect_one()) bulk_load_mc(d, q, fb, p < 15 ? 3 : 1 << rank);
        if (p == 4) PTS(7);
      }
      if (elect_one()) bulk_load_mc(sm + 13 * SLOT_B + rank * 8192, src + cg * 512, sm + bar3(15) + rank * 256, 2 >> rank);
      PTS(15);
    } else {
      const int r4 = lane >> 3, c8 = lane & 7;
      const uint32_t eb = (lane << 24) + bars + B_EMPTY;
      auto tagged = [](float v, uint32_t tag) { return ((__float_as_uint(v) + 128) & ~255u) | tag; };
      auto gather = [&](uint32_t tag) {
        const int q = (wid - 9) * 24 + lane;
        const uint4* cp = lane < 24 ? &G.csp[cg * 8 * 48 + q] : &G.st1[rb * 8 * 48 + (wid - 9) * 8 + lane - 24];
        uint4 v[8];
        delay(clk(), GDELAY);
#pragma unroll 1
        for (int it = 0;; it++) {
#pragma unroll
          for (int i = 0; i < 8; i++) v[i] = ld_rlx4(cp + i * 48);
          uint32_t x = 0;
#pragma unroll
          for (int i = 0; i < 8; i++) { v[i].x ^= tag; v[i].y ^= tag; v[i].z ^= tag; v[i].w ^= tag; x |= v[i].x | v[i].y | v[i].z | v[i].w; }
          if (!__any_sync(~0u, (x & 255) != 0)) break;
          SPINCHK(it, 3);
        }
        float c[4] = {0.f, 0.f, 0.f, 0.f};
#pragma unroll
        for (int i = 0; i < 8; i++) { c[0] += __uint_as_float(v[i].x); c[1] += __uint_as_float(v[i].y); c[2] += __uint_as_float(v[i].z); c[3] += __uint_as_float(v[i].w); }
        const uint32_t h0 = pack2(c[0], c[1]), h1 = pack2(c[2], c[3]), ca = sm + OFF_COLSUM + (q >> 1) * 32 + (q & 1) * 8;
        if (lane < 24) {
          sts2f(ca, __uint_as_float(h0), __uint_as_float(h1));
          sts2f(ca + 16, __uint_as_float(pack2(c[0] - bf_lo(h0), c[1] - bf_hi(h0))), __uint_as_float(pack2(c[2] - bf_lo(h1), c[3] - bf_hi(h1))));
        }
        fence_async_smem();
        mbar_arrive(mb + B_AUX);
      };
      const int r2 = lane >> 4, c16 = lane & 15;
      float a[12];
#pragma unroll
      for (int i = 0; i < 12; i++) a[i] = 0.f;
      auto kb_of = [](int it) { return (int)(KORD >> (4 * it)) & 15; };
      if (wid == 9) {
        const uint32_t a0 = sm + rb * 1024 + r2 * 128 + (((c16 >> 1) ^ r2) << 4) + (c16 & 1) * 8;
        const uint2* gw = (const uint2*)(P.wqkv + (kl + rb * 8 + r2) * 3072 + cg * 64) + c16;
#pragma unroll 1
        for (int it = 0; it < 16; it++) {
          uint2 w[12];
          const int kb = kb_of(it);
          if (kb >= 12) {
#pragma unroll
            for (int j = 0; j < 12; j++) w[j] = ld_rlx2(gw + (j >> 2) * 256 + (j & 3) * 1536);
            gw += 64 * 768;
          } else {
            const uint32_t so = a0 + woff(kb & 3);
            mbar_wait(mb + B_FULL + 8 * (kb & 3), (kb >> 2) & 1);
            static_for<0, 12>([&](auto ic) { constexpr int i = decltype(ic)::value;
              const float2 v = lds2f_o<(i >> 2) * WSTR + (i & 3) * 256>(so ^ ((i & 3) << 5)); w[i] = make_uint2(__float_as_uint(v.x), __float_as_uint(v.y)); });
            uint32_t done = 0;
#pragma unroll
            for (int i = 0; i < 12; i++) done |= w[i].y;
            if (lane < 2) mbar_arrive_rem(eb + 8 * (kb & 3) + (done & zero));
          }
#pragma unroll
          for (int i = 0; i < 12; i++) { float* q = a + (i >> 2) * 4; q[0] += bf_lo(w[i].x); q[1] += bf_hi(w[i].x); q[2] += bf_lo(w[i].y); q[3] += bf_hi(w[i].y); }
        }
        if (lane == 0) PTS(8);
        float c[6];
#pragma unroll
        for (int i = 0; i < 6; i++) {
          const int o = (i >> 1) * 4 + (i & 1);
          c[i] = (r2 ? a[o + 2] : a[o]) + __shfl_xor_sync(~0u, r2 ? a[o] : a[o + 2], 16);
        }
        bar_sync(5, 96);
        if (lane == 0) PTS(5);
        const uint32_t tag = lds1(mb + B_SW + 4) & 255;
#pragma unroll
        for (int sg = 0; sg < 3; sg++) st_rlx2((uint2*)&G.csp[(cg * 8 + rb) * 48] + sg * 32 + c16 * 2 + r2, tagged(c[sg * 2], tag), tagged(c[sg * 2 + 1], tag));
      } else {
       if (wid == 10) {
        if (lane < 24 && (lane & 28) != 4) sts4(sm + OFF_STATS + (lane < 16 ? lane * 128 + c8 * 16 : c8 * 16), 0x3F803F80u, 0x3F803F80u, 0x3F803F80u, 0x3F803F80u);
       } else {
        mbar_wait(mb + B_FULL + 8 * PFST, 0);
        const uint32_t ep = ld_rlx(&G.epoch);
        uint4 v[4];
#pragma unroll
        for (int i = 0; i < 4; i++) v[i] = ld_cg4((const uint4*)P.wr + lane + i * 32);
        if (elect_one()) { tmap_prefetch(&tmO); tmap_prefetch(&tmG); tmap_prefetch(&tmU); tmap_prefetch(&tmD); tmap_prefetch(&tmPD); tmap_prefetch(&tmM); }
        __syncwarp();
        const uint4 sv = make_uint4(SENT, SENT, SENT, SENT);
#pragma unroll 1
        for (int i = 0; i < 9; i++) {
          uint4* q = i < 8 ? &G.obuf[((rb * 4 + (i >> 1)) * 64 + cg * 4) * 128 + (i & 1) * 256 + lane] : &G.kvp[cg * 2304 + rb * 288 + lane];
#pragma unroll
          for (int j = 0; j < 8; j++) q[j * 32] = sv;
          if (i == 8) q[256] = sv;
          else if (lane < ((i & 1) ? 24 : 16)) l2_prefetch((i & 1) ? P.wqkv + (kl + (i >> 1) * 64 + rb * 8 + c8) * 3072 + r4 * 1024 + cg * 64 : P.x + (b * 16 + lane) * D_ + kl + i * 32);
        }
        float s = 0.f;
#pragma unroll 1
        for (int i = 0; i < 4; i++) {
          s += (bf_lo(v[0].x) + bf_hi(v[0].x)) + (bf_lo(v[0].y) + bf_hi(v[0].y)) + (bf_lo(v[0].z) + bf_hi(v[0].z)) + (bf_lo(v[0].w) + bf_hi(v[0].w));
          v[0] = v[1]; v[1] = v[2]; v[2] = v[3];
        }
#pragma unroll
        for (int o = 16; o; o >>= 1) s += __shfl_xor_sync(~0u, s, o);
        if (lane == 0) sts2f(mb + B_SW, s, __uint_as_float(ep + 1));
       }
        const uint32_t xa = sm + (c3 * 16 + r4) * 128 + ((c8 ^ r4) << 4);
        const uint4* gx = (const uint4*)(P.x + (b * 16 + r4) * D_ + kl) + c8;
        uint32_t e[4] = {0, 0, 0, 0};
        uint4 wq;
#pragma unroll 1
        for (int kb = wid == 10 ? 0 : 12; kb < (wid == 10 ? 12 : 16); kb++) {
          uint4 v[4];
          if (!(kb & 3)) wq = ld_cg4((const uint4*)(P.wr + k_of(kb + r4)) + c8);
          if (kb >= 12) {
#pragma unroll
            for (int j = 0; j < 4; j++) v[j] = ld_cg4(gx + j * 512);
            gx += 8;
          } else {
            const uint32_t so = xa + xoff(kb & 3, hf);
            mbar_wait(mb + B_FULL + 8 * (kb & 3), (kb >> 2) & 1);
            v[0] = lds4_o<0>(so); v[1] = lds4_o<512>(so ^ 64); v[2] = lds4_o<1024>(so); v[3] = lds4_o<1536>(so ^ 64);
            if (lane < 2) mbar_arrive_rem(eb + 8 * (kb & 3) + ((v[0].x | v[1].x | v[2].x | v[3].x) & zero));
          }
#pragma unroll
          for (int j = 0; j < 16; j++) {
            const uint32_t u = (j & 3) == 0 ? v[j >> 2].x : (j & 3) == 1 ? v[j >> 2].y : (j & 3) == 2 ? v[j >> 2].z : v[j >> 2].w;
            const float d0 = bf_lo(u), d1 = bf_hi(u);
            a[j >> 2] += d0 + d1; a[4 + (j >> 2)] = fmaf(d0, d0, fmaf(d1, d1, a[4 + (j >> 2)]));
          }
          cut<1>(zero);
          const int sl = (kb & 3) * 8 + c8;
          const uint4 wn = make_uint4(__shfl_sync(~0u, wq.x, sl), __shfl_sync(~0u, wq.y, sl), __shfl_sync(~0u, wq.z, sl), __shfl_sync(~0u, wq.w, sl));
#pragma unroll
          for (int j = 0; j < 4; j++) e[j] = hfma2(v[j].x, wn.x, hfma2(v[j].y, wn.y, hfma2(v[j].z, wn.z, hfma2(v[j].w, wn.w, e[j]))));
        }
        float mean, pd;
#pragma unroll 1
        for (int h = 0; h < 2; h++) {
          float u[4], v[2];
#pragma unroll
          for (int i = 0; i < 4; i++) u[i] = ((lane & 4) ? a[4 + i] : a[i]) + __shfl_xor_sync(~0u, (lane & 4) ? a[i] : a[4 + i], 4);
#pragma unroll
          for (int i = 0; i < 2; i++) v[i] = ((lane & 2) ? u[2 + i] : u[i]) + __shfl_xor_sync(~0u, (lane & 2) ? u[i] : u[2 + i], 2);
          mean = pd;
          pd = ((lane & 1) ? v[1] : v[0]) + __shfl_xor_sync(~0u, (lane & 1) ? v[0] : v[1], 1);
#pragma unroll
          for (int j = 0; j < 4; j++) { a[j] = bf_lo(e[j]); a[4 + j] = bf_hi(e[j]); }
        }
        if (wid == 11) {
          sts2f(sm + OFF_COLSUM + 512 + lane * 8, mean, pd);
          fence_gpu();
          bar_arrive(5, 96); PTS(0);
          if (elect_one()) {
#pragma unroll 1
            for (int p = 0; p < 16; p++) {
              const uint32_t ad = sm + bar3(0) + o3(p);
              mbar_init(ad, 1); mbar_init(ad + 256, 1); mbar_init(ad + 448, 8); mbar_init(ad + 704, p == 0 ? 2 : p == 12 ? 1 : p == 15 ? 7 : 8);
              mbar_expect_tx(ad, 8192); mbar_expect_tx(ad + 256, 8192); mbar_expect_tx(mb + B_FULL3 + 8 * p, SLOT_B);
            }
            asm volatile("fence.mbarrier_init.release.cluster;" ::: "memory");
            fence_async_smem();
            mbar_arrive_rem(bars + B_LATE); mbar_arrive_rem((1u << 24) + bars + B_LATE);
          }
          __syncwarp();
        } else {
          if (lane == 0) PTS(1);
          bar_sync(5, 96);
          const float2 u = lds2f(sm + OFF_COLSUM + 512 + lane * 8), sw = lds2f(mb + B_SW);
          mean = (mean + u.x) * (1.f / D_);
          pd += u.y;
          pd += __shfl_xor_sync(~0u, pd, 4);
          const float var = fmaxf(fmaf(-mean, mean, __shfl_xor_sync(~0u, mean, 4)), 0.f);
          const uint32_t tag = __float_as_uint(sw.y) & 255;
          if (c8 < 4) {
            st_rlx2((uint2*)G.st1 + (b >> 1) * 96 + rank * 16 + r4 + 4 * c8, tagged(-mean, tag), tagged(rsq(var + 1e-5f), tag));
            st_rlx(&G.pred[b * 16 + r4 + 4 * c8], (ordered(fmaf(-mean, sw.x, pd)) & ~255u) | tag);
          }
        }
      }
      if (wid < 11) gather(lds1(mb + B_SW + 4) & 255);
      if (wid == 9) {
        if (lane == 0) PTS(6);
        {
          const uint4 sv = make_uint4(SENT, SENT, SENT, SENT);
          uint4* y = &G.ybuf[b * NFFN * 4 + lane];
#pragma unroll
          for (int i = 0; i < 14; i++) y[i * 32] = sv;
          if (lane < 16) G.st2[b * 16 + lane] = make_uint4(0, 0, 0, 0);
          G.hsel[b * 64 + lane] = sv; G.hsel[b * 64 + 32 + lane] = sv;
          if (b < 8) { G.cand[b * 32 + lane] = SENT; G.cst[b * 32 + lane] = make_uint4(0, 0, 0, 0); }
          fence_gpu();
          __syncwarp();
          if (lane == 0) mbar_arrive(mb + B_LATE);
        }
      } else if (wid == 10) {
        {
          mbar_wait(mb + B_FULL + 24, 1);
#pragma unroll 1
          for (int r = -4; r < (fidx >= 0 ? 16 : 0); r++) {
            l2_prefetch((r < 0 ? (const char*)P.wo + (b + 1) * 16384 : (const char*)P.wd + fidx * 65536) + r * 4096 + lane * 128);
            delay(clk(), PDT);
          }
          PTS(4);
        }
      }
      mbar_wait(mb + B_LATE, 0);
      if (wid == 9) {
        wait3(60);
#pragma unroll 1
        for (int p = 0; p < 16; p++) {
          const bool mix = (unsigned)(p - 1) < 8;
          int c1 = mix ? ((p - 1) >> 1) * 16 : 0, c2 = mix ? (hf ^ 1) * 8 + ((p - 1) & 1) * 4 : chunk_of(p) * 4;
          uint32_t d = sm + (uint32_t)((WO_SLOTS >> (4 * p)) & 15) * SLOT_B;
          if (PRE & 2) asm volatile("" : "+r"(d), "+r"(c1), "+r"(c2));
          if ((0xFFE2 >> p) & 1) mbar_wait(p == 1 ? mb + B_EMPTY + 8 : sm + bar3(32) + o3(p - 5), p == 1);
          else if (WDT) delay(clk(), WDT);
          if (elect_one()) asm volatile("cp.async.bulk.tensor.4d.shared::cluster.global.mbarrier::complete_tx::bytes [%0], [%1, {0, %3, %4, %5}], [%2];"
                                        :: "r"(d), "l"(mix ? &tmM : &tmO), "r"(mb + B_FULL3 + 8 * p), "r"(c1), "r"(c2), "r"(c3 * 2) : "memory");
          if (p >= 10) PTS(7 + p);
        }
        if (fidx >= 0) {
#pragma unroll 1
          for (int i = 0; i < 4; i++) {
            mbar_wait(sm + bar3(32) + o3((DEV >> (4 * i)) & 15), 0);
            if (elect_one()) tma_3d(sm + ((D_SLOTS >> (4 * i)) & 15) * SLOT_B, &tmD, 0, fidx * 32, i * 4, mb + B_FFN + 8, EFF);
          }
        }
      } else if (wid == 11) {
        const uint2 w = ld_rlx2((const uint2*)(P.wr + c3 * 128) + lane);
        wait3(32);
        sts1(sm + OFF_LNP + (lane & 1) * 128 + (lane >> 1) * 4, w.x); sts1(sm + OFF_LNP + (lane & 1) * 128 + 64 + (lane >> 1) * 4, w.y);
        if (lane < 16) sts1(sm + OFF_LNP + 256 + lane * 4, 0x3F803F80u);
        const uint32_t tag = lds1(mb + B_SW + 4) & 255;
        uint4 k;
        for (int it = 0;; it++) {
          k = ld_rlx4((const uint4*)&G.pred[rb * 256 + hf * 64 + r2 * 128] + c16);
          k.x ^= tag; k.y ^= tag; k.z ^= tag; k.w ^= tag;
          if (!__any_sync(~0u, (k.x | k.y | k.z | k.w) & 255)) break;
          SPINCHK(it, 13);
        }
        const uint2 ahead = top2(k.x | (lane * 4), k.y | (lane * 4 + 1), k.z | (lane * 4 + 2), k.w | (lane * 4 + 3));
        if (lane == 0) sts2f(sm + OFF_MSC + 8, __uint_as_float((ahead.x & 127) ^ NOSPEC), __uint_as_float((ahead.y & 127) ^ NOSPEC));
        __syncwarp();
        if (lane == 0) mbar_arrive(mb + B_FULL3 + 8 * 15);
        if (fidx >= 0) {
#pragma unroll 1
          for (int j = 0; j < 8; j++) {
            mbar_wait(sm + bar3(32) + o3(PD0 + j), 0);
            if (elect_one()) tma_2d(sm + OFF_COLSUM, &tmPD, 0, fidx * 256 + j * 32, mb + B_FFN, false);
          }
        }
      } else if (fidx >= 0) {
        wait3(60);
        if (elect_one()) mbar_expect_tx(mb + B_FULL, 65536);
#pragma unroll 1
        for (int h = 0; h < 2; h++) {
          const int up = h ^ hf ^ 1;
          mbar_wait(mb + B_EMPTY + 16 - 16 * h, 1);
#pragma unroll
          for (int i = 0; i < 4; i++) {
            const int f = (0x5140 >> (4 * i)) & 15;
            if (elect_one()) tma_2d(sm + ((GU_SLOTS >> (4 * f)) & 15) * SLOT_B + up * 8192, up ? &tmU : &tmG, fidx * 32, f * 128, mb + B_FULL, EFF);
            if (i < 3) delay(clk(), FDT);
          }
          PTS(23 + h);
        }
#pragma unroll 1
        for (int i = 0; i < 4; i++) {
          const int f = (0x7362 >> (4 * i)) & 15;
          const uint32_t d = sm + ((GU_SLOTS >> (4 * f)) & 15) * SLOT_B;
          mbar_wait(sm + bar3(32) + o3((GEV >> (4 * i)) & 15), 0);
          if (elect_one()) { tma_2d(d, &tmG, fidx * 32, f * 128, mb + B_FFN, EFF); tma_2d(d + 8192, &tmU, fidx * 32, f * 128, mb + B_FFN, EFF); }
          PTS(27 + i);
        }
      }
    }
    const float sw = __uint_as_float(lds1(mb + B_SW));
    const int rr = lane >> 4, row00 = rb * 256 + hf * 64;
    uint2 pick;
    if (wid == 8) {
      wait3(61);
      delay(clk(), SDELAY);
      uint4 v;
      int id;
      for (int it = 0;; it++) {
        v = ld_rlx4(&G.cst[jp * 32 + lane]);
        id = __float2int_rn(__uint_as_float(v.w));
        if (!__any_sync(~0u, (id & 15) != 8)) break;
        SPINCHK(it, 14);
      }
      float2 pr;
      const uint32_t k = route(v, sw, id >> 4, pr);
      pick.x = __reduce_max_sync(~0u, k); pick.y = __reduce_max_sync(~0u, k == pick.x ? 0 : k);
      if (k == pick.x || k == pick.y) sts4(sm + OFF_MSC + 16 + (k == pick.y) * 16, k, lane, __float_as_uint(pr.x), __float_as_uint(pr.y));
      __syncwarp();
      if (lane == 0) { mbar_arrive(mb + B_SEL); PTS(16); }
    } else if (wid == 9) {
      wait3(61);
      delay(clk(), LDELAY);
      uint4 v[4];
      for (int it = 0;; it++) {
#pragma unroll
        for (int i = 0; i < 4; i++) v[i] = ld_rlx4(&G.st2[row00 + (i >> 1) * 128 + (i & 1) * 32 + lane]);
        if (!__any_sync(~0u, (v[0].w & v[1].w & v[2].w & v[3].w) != 0x41000000u)) break;
        SPINCHK(it, 6);
      }
      uint32_t k[4];
#pragma unroll
      for (int i = 0; i < 4; i++) {
        float2 pr;
        k[i] = route(v[i], sw, row00 + (i >> 1) * 128 + (i & 1) * 32 + lane, pr);
        const float nm = __uint_as_float(v[i].x) * (-1.f / D_);
        sts2f(sm + OFF_LNP + (i * 32 + lane) * 8, __uint_as_float(pack2(pr.x, pr.x)), __uint_as_float(pack2(nm, nm)));
      }
      const uint2 m = top2(k[0], k[1], k[2], k[3]);
      if (lane == 0) { st_rlx2(&G.cand[c3 * 32 + (rb * 2 + hf) * 2], m.x, m.y); sts2f(sm + OFF_MSC + 0, __uint_as_float(m.x), __uint_as_float(m.y)); }
      wait3(62);
      __syncwarp();
      if (lane == 0) { mbar_arrive(mb + B_OUT); PTS(12); }
      const int ca = 2047 - (((lane & 4) ? m.y : m.x) & 2047), ta = ((ca >> 1) & 64) + (ca & 63);
      uint32_t h0, h1, h2, h3;
      ldsm4_o<0>(sm + HST + ta * 256 + ((((lane & 3) * 4 + (lane >> 3)) ^ (ta & 7)) << 4), h0, h1, h2, h3);
      st_rlx4(&G.hsel[(32 + (rb * 2 + hf) * 2 + rr) * 128 + c3 * 16 + (lane & 15)], make_uint4(h0, h1, h2, h3));
    }
    mbar_wait(mb + B_OUT, 0);
    const float2 cf = lds2f(sm + OFF_MSC + 0);
    const int ca0 = ~__float_as_int(cf.x), ca1 = ~__float_as_int(cf.y), cand0 = ((ca0 >> 1) & 64) + (ca0 & 63), cand1 = ((ca1 >> 1) & 64) + (ca1 & 63);
    auto norm = [](const uint4& v, const float2& pr) {
      const uint32_t r = __float_as_uint(pr.x), m = __float_as_uint(pr.y);
      return make_uint4(hfma2(hadd2(v.x, m), r, v.x), hfma2(hadd2(v.y, m), r, v.y), hfma2(hadd2(v.z, m), r, v.z), hfma2(hadd2(v.w, m), r, v.w));
    };
    uint4* const og = (uint4*)(P.out + row00 * D_ + c3 * 128) + (lane & 15);
    if (wid == 8) {
      delay(clk(), CDELAY);
      uint32_t k;
      for (int it = 0;; it++) { k = ld_rlx(&G.cand[c3 * 32 + lane]); if (!__any_sync(~0u, k == SENT)) break; SPINCHK(it, 12); }
      const uint32_t m1 = __reduce_max_sync(~0u, k), m2 = __reduce_max_sync(~0u, k == m1 ? 0 : k);
      const uint32_t miss = ((m1 ^ pick.x) | (m2 ^ pick.y)) & 2047;
      if (miss && (k == m1 || k == m2)) {
        float2 pr;
        route(ld_rlx4(&G.st2[2047 - (k & 2047)]), sw, 0, pr);
        sts4(sm + OFF_MSC + 48 + (k == m2) * 16, k, 32 + lane, __float_as_uint(pr.x), __float_as_uint(pr.y));
      }
      if (lane == 0) sts1(sm + OFF_MSC + 80, miss);
      __syncwarp();
      if (lane == 0) { mbar_arrive(mb + B_SEL2); PTS(13); }
      if (lane == 0 && b == 0) G.epoch = lds1(mb + B_SW + 4);
      const uint32_t kc = __float_as_uint(rr ? cf.y : cf.x);
      const int c = rr ? cand1 : cand0;
      if (kc != m1 && kc != m2) og[(c + (c & 64)) * 128] = norm(lds4(sm + HST + c * 256 + (((lane & 15) ^ (c & 7)) << 4)), lds2f(sm + OFF_LNP + c * 8));
    }
#pragma unroll 1
    for (int t0 = wid == 8 ? 120 : (11 - wid) * 8; t0 < (wid == 8 ? 128 : 120) * !NOOUT; t0 += 24) {
      uint4 v[4];
      float2 pr[4];
      const uint32_t ad = sm + HST + t0 * 256 + lane * 16;
      static_for<0, 4>([&](auto ic) { constexpr int i = decltype(ic)::value; v[i] = lds4_o<i * 512>(ad ^ (rr << 4) ^ (i << 5)); pr[i] = lds2f_o<i * 16>(sm + OFF_LNP + (t0 + rr) * 8); });
#pragma unroll
      for (int i = 0; i < 4; i++) v[i] = norm(v[i], pr[i]);
      if (t0 >= OHOLD) wait3(63);
#pragma unroll
      for (int i = 0; i < 4; i++) {
        const int tr = t0 + rr + 2 * i;
        if (tr != cand0 && tr != cand1) {
          if (OUTEF) asm volatile("st.global.L2::cache_hint.v4.u32 [%0], {%1,%2,%3,%4}, %5;" :: "l"(og + (tr + (tr & 64)) * 128), "r"(v[i].x), "r"(v[i].y), "r"(v[i].z), "r"(v[i].w), "l"(l2_stream()) : "memory");
          else og[(tr + (tr & 64)) * 128] = v[i];
        }
      }
    }
    if (wid == 11 && lane == 0) PTS(31);
  } else {
    asm volatile("setmaxnreg.inc.sync.aligned.u32 224;");
    const int t128 = tid & 127, warp = wid & 3, g = lane >> 2, t = lane & 3;
    const int mb3 = rb * 4 + wg * 2 + hf;
    float acc[64];
    uint4 abuf[3][4];
    uint32_t to;
    int tid2;
    {
      float acc0[96], acc1[96];
#pragma unroll
      for (int i = 0; i < 96; i++) { asm volatile("" : "=f"(acc0[i])); asm volatile("" : "=f"(acc1[i])); }
      const uint32_t xo0 = dlo(sb, 16) + hf * 512, xo1 = dlo(sb, 16) + (hf ^ 1) * 512;
      const uint32_t eb0 = (t128 << 24) + bars + B_EMPTY;
#pragma unroll 1
      for (int kb = 0; kb < 12; kb++) {
        const int s = kb & 3;
        mbar_wait(mb + B_FULL + 8 * s, (kb >> 2) & 1);
        if (LOCK) bar_sync(13, 256);
        if (kb == 0) TS(1);
        const uint32_t xs = xoff(s, wg) >> 4, ws = dlo(sb + woff(s), WSTR);
        pin(acc0); pin(acc1);
        wg_fence();
#pragma unroll
        for (int k = 0; k < 4; k++) {
          const uint64_t db = dsc<1024, 1>(ws + k * 128);
          const int sd = k == 0 ? kb : 1;
          wgmma_n192_ss<0, 1, 0>(acc0, dsc<1024, 1>(xs + xo0 + k * 2), db, sd);
          wgmma_n192_ss<0, 1, 0>(acc1, dsc<1024, 1>(xs + xo1 + k * 2), db, sd);
          if (k == RELK || k == 3) wg_commit();
          if (k == RELK) {
            wg_wait<1>();
            if (kb > 0 && t128 < 2) mbar_arrive_rem(eb0 + 8 * ((kb - 1) & 3));
          }
        }
        pin(acc0); pin(acc1);
      }
      float qa0[32], qa1[32], kv0[64], kv1[64];
#pragma unroll
      for (int i = 0; i < 96; i++) { if (i < 32) { qa0[i] = acc0[i]; qa1[i] = acc1[i]; } else { kv0[i - 32] = acc0[i]; kv1[i - 32] = acc1[i]; } }
      uint2 st[2][2];
      uint4 am;
      auto center = [&](float (&q)[32], float (&kv)[64], const uint2 (&v)[2]) {
        const uint32_t n0 = v[0].x & (t == 0 ? ~255u : 0u), n1 = v[1].x & (t == 0 ? ~255u : 0u);
        am = make_uint4(__byte_perm(n0, 0, 0x3232), __byte_perm(n1, 0, 0x3232),
                        __byte_perm(__float_as_uint(__uint_as_float(n0) - bf_hi(n0)), 0, 0x3232), __byte_perm(__float_as_uint(__uint_as_float(n1) - bf_hi(n1)), 0, 0x3232));
        wg_fence();
        wgmma_n64_rs<1, 0>(q, am.x, am.y, am.z, am.w, dsc<32, 0>(dlo(sb + OFF_COLSUM, 0)), 1);
        wgmma_n128_rs<1, 0>(kv, am.x, am.y, am.z, am.w, dsc<32, 0>(dlo(sb + OFF_COLSUM + 256, 0)), 1);
      };
      auto load_st = [&]() {
        mbar_wait(mb + B_AUX, 0);
#pragma unroll
        for (int i = 0; i < 4; i++) st[i >> 1][i & 1] = ld_rlx2((const uint2*)G.st1 + ((rb * 4 + wg * 2 + ((i >> 1) ^ hf)) * 2 + (warp >> 1)) * 96 + (warp & 1) * 16 + (i & 1) * 8 + g);
      };
      if (!wg) {
        wg_wait<0>();
        if (t128 < 2) mbar_arrive_rem(eb0 + 24);
        load_st();
#pragma unroll 1
        for (int s = 0; s < (B6E < 3 ? 3 : 4); s++) mbar_wait(mb + B_FULL + 8 * s, 1);
        bar_sync(6, 256);
      }
      static_for<0, 4>([&](auto sc) {
        constexpr int s = decltype(sc)::value;
        if (wg || (B6E < 3 && s == 3)) mbar_wait(mb + B_FULL + 8 * s, 1);
        const uint32_t xs = (wg ? xoff(s, 1) : xoff(s, 0)) >> 4, ws = dlo(sb + woff(s) + WSTR, WSTR);
        pin(kv0); pin(kv1); pin(qa0); pin(qa1);
        wg_fence();
#pragma unroll
        for (int k = 0; k < 4; k++) {
          const uint64_t db = dsc<1024, 1>(ws + k * 128);
          wgmma_n128_ss<0, 1, 0>(kv0, dsc<1024, 1>(xs + xo0 + k * 2), db, 1);
          wgmma_n128_ss<0, 1, 0>(kv1, dsc<1024, 1>(xs + xo1 + k * 2), db, 1);
          if (s == 0 && k == B6H - 1) { if (!wg) bar_sync(14, 256); wg_fence(); }
          if (k == 3 || (k == 2 && s == 0)) wg_commit();
          if (k == (s ? 3 : 2) && s < 3) {
            wg_wait<1>();
            if (s == 0) { if (wg && t128 < 2) mbar_arrive_rem(eb0 + 24); }
            else if (!wg) bar_arrive(8 + s, 256);
          }
        }
        if (s == B6E && wg) bar_arrive(6, 256);
        if (s == 3 && B6H && wg) bar_arrive(14, 256);
        if (s == STLD && wg) load_st();
      });
      if (CUTS & 2) {
        cut<6>(zero);
#pragma unroll
        for (int i = 0; i < 4; i++) asm volatile("" : "+r"(st[i >> 1][i & 1].x), "+r"(st[i >> 1][i & 1].y) :: "memory");
      }
      center(qa0, kv0, st[0]);
      wg_commit();
      if (B6E > 3 && wg) bar_arrive(6, 256);
      float rs[2][2];
#pragma unroll
      for (int i = 0; i < 4; i++) rs[i >> 1][i & 1] = __uint_as_float(st[i >> 1][i & 1].y & ~255u);
      const uint32_t sad = sm + (wg ? 11 : 2) * SLOT_B + (warp * 16 + (lane & 15)) * 128 + (((lane >> 4) ^ (lane & 7)) << 4);
      wg_wait<0>();
      pin(kv0); pin(kv1); pin(qa0); pin(qa1); pin4(am);
      center(qa1, kv1, st[1]);
      wg_commit();
      if (wg) bar_arrive(11, 256);
      if (CUTS & 1) cut<2>(zero);
      TS(2);
      float rl[2];
      uint32_t r2[2];
      auto scales = [&](int m, uint32_t z) {
#pragma unroll
        for (int h = 0; h < 2; h++) { const float r = __uint_as_float(__float_as_uint(rs[m][h]) + z); r2[h] = pack2(r, r); rl[h] = r * 1.4426950408889634f; }
      };
      auto phi8 = [&](const float* a) {
        return make_uint4(phi2(a[0], a[1], r2[0], rl[0]), phi2(a[2], a[3], r2[1], rl[1]), phi2(a[4], a[5], r2[0], rl[0]), phi2(a[6], a[7], r2[1], rl[1]));
      };
      auto stage = [&](float (&a)[64], auto mc) {
        constexpr int m = decltype(mc)::value;
        uint4 r[4];
        scales(m, 0);
#pragma unroll
        for (int j = 0; j < 4; j++) r[j] = phi8(a + j * 8);
        if (m == 0 || wg) bar_sync(wg ? 9 + m : 11, 256 + (r[SBAR].x & zero));
#pragma unroll
        for (int j = 0; j < 4; j++) {
          const int v = 32 + j * 8;
          stsm4_o<WSTR + m * 8192>(sad ^ (j << 5), hmul2(pack2(a[v], a[v + 1]), r2[0]), hmul2(pack2(a[v + 2], a[v + 3]), r2[1]),
                                                   hmul2(pack2(a[v + 4], a[v + 5]), r2[0]), hmul2(pack2(a[v + 6], a[v + 7]), r2[1]));
        }
#pragma unroll
        for (int j = 0; j < 4; j++) stsm4_o<m * 8192>(sad ^ (j << 5), r[j].x, r[j].y, r[j].z, r[j].w);
      };
      stage(kv0, std::integral_constant<int, 0>{});
      wg_wait<0>();
      pin(kv1); pin(qa1); pin4(am);
      stage(kv1, std::integral_constant<int, 1>{});
      fence_async_smem();
      TS(3);
      uint32_t xr[8][4];
      auto load_xr = [&]() {
        const uint32_t xa = sm + hf * 8192 + (warp * 16 + (lane & 15)) * 128 + (((lane >> 4) ^ (lane & 7)) << 4);
#pragma unroll
        for (int q = 0; q < 8; q++) ldsm4_o<0>((xa ^ ((q & 3) << 5)) + xoff(rank * 2 + (q >> 2), wg), xr[q][0], xr[q][1], xr[q][2], xr[q][3]);
      };
      if (!wg) { bar_arrive(4, 256); load_xr(); }
      else {
        float ka[36];
#pragma unroll
        for (int i = 0; i < 36; i++) ka[i] = 0.f;
        auto kv_mma = [&](auto ic) {
          constexpr int i = decltype(ic)::value;
          constexpr uint32_t o = sb + (i < 8 ? 11 : 2) * SLOT_B + (i & 7) * 2048;
          wgmma_n72_ss<1, 1, 0>(ka, dsc<1024, 1>(dlo(o, 8192)), dsc<1024, 1>(dlo(o + WSTR, sb + OFF_STATS - o - WSTR)), i);
        };
        mbar_wait(mb + B_LATE, 0);
        bar_sync(3, 128);
        wg_fence();
        static_for<0, 8>(kv_mma);
        wg_commit();
        uint4* dst = &G.kvp[cg * 2304 + rb * 32];
        if (CUTS & 4) cut<3>(zero);
        load_xr();
        bar_sync(4, 256);
        static_for<8, 16>(kv_mma);
        wg_commit();
        if (QHOLD == 1) bar_arrive(8, 256);
        wg_wait<0>();
        pin(ka);
        if (QHOLD == 2) bar_arrive(8, 256);
        TS(4);
        if (warp < 2) {
          st_rlx4(dst + warp * 512 + lane, make_uint4(pack2(ka[0], ka[1]), pack2(ka[4], ka[5]), pack2(ka[8], ka[9]), pack2(ka[12], ka[13])));
          st_rlx4(dst + warp * 512 + 256 + lane, make_uint4(pack2(ka[2], ka[3]), pack2(ka[6], ka[7]), pack2(ka[10], ka[11]), pack2(ka[14], ka[15])));
        } else {
          st_rlx4(dst + warp * 512 + lane, make_uint4(pack2(ka[16], ka[17]), pack2(ka[20], ka[21]), pack2(ka[24], ka[25]), pack2(ka[28], ka[29])));
          st_rlx4(dst + warp * 512 + 256 + lane, make_uint4(pack2(ka[18], ka[19]), pack2(ka[22], ka[23]), pack2(ka[26], ka[27]), pack2(ka[30], ka[31])));
        }
        st_rlx((uint32_t*)(dst + 2048) + t128, pack2(ka[32], ka[34]));
        if (QHOLD == 3) bar_arrive(8, 256);
        if (t128 == 0) mbar_arrive(sm + bar3(60));
      }
      TS(5);
      uint32_t pq[16], pq0[16];
      auto q_mma = [&](float (&q)[32], uint32_t xo, int s0, int s1) {
#pragma unroll 1
        for (int s = s0; s < s1; s++) {
          const uint32_t xs = (xoff(s, wg) >> 4) + xo, ws = dlo(sb + woff(s), 8192);
          pin(q);
          wg_fence();
#pragma unroll
          for (int k = 0; k < 4; k++) wgmma_n64_ss<0, 1, 0>(q, dsc<1024, 1>(xs + k * 2), dsc<1024, 1>(ws + k * 128), 1);
          wg_commit();
        }
      };
      auto q_phi = [&](float (&q)[32], int m, uint32_t (&pq)[16], int lo, int hi) {
        scales(m, zero);
#pragma unroll
        for (int j = lo; j < hi; j++) { const uint4 r = phi8(q + j * 8); pq[j * 4] = r.x; pq[j * 4 + 1] = r.y; pq[j * 4 + 2] = r.z; pq[j * 4 + 3] = r.w; }
      };
      auto o_of = [&](uint32_t (&pq)[16], uint4 (&o)[4], uint4* first, bool pub) {
        float oa[2][20];
#pragma unroll
        for (int i = 0; i < 40; i++) oa[i / 20][i % 20] = 0.f;
        wg_fence();
#pragma unroll
        for (int ks = 0; ks < 4; ks++) {
          wgmma_n40_rs<1, 0>(oa[ks >> 1], pq[ks * 4], pq[ks * 4 + 1], pq[ks * 4 + 2], pq[ks * 4 + 3], dsc<1024, 1>(dlo(sb + OFF_KVB + ks * 2048, 8192)), ks & 1);
          if (ks & 1) wg_commit();
        }
#pragma unroll
        for (int h = 0; h < 2; h++) {
          if (h) wg_wait<0>(); else wg_wait<1>();
          pin(oa[h]);
          const float (&d)[20] = oa[h];
          const float i0 = rcp(d[16] + 1e-6f), i1 = rcp(d[18] + 1e-6f);
#pragma unroll
          for (int k2 = 0; k2 < 2; k2++) {
            o[h * 2 + k2] = make_uint4(pack2(d[k2 * 8] * i0, d[k2 * 8 + 1] * i0), pack2(d[k2 * 8 + 2] * i1, d[k2 * 8 + 3] * i1),
                                       pack2(d[k2 * 8 + 4] * i0, d[k2 * 8 + 5] * i0), pack2(d[k2 * 8 + 6] * i1, d[k2 * 8 + 7] * i1));
            if (pub && !h) st_rlx4(first + (h * 2 + k2) * 1024, o[h * 2 + k2]);
          }
        }
#pragma unroll
        for (int i = 0; i < 16; i++) asm volatile("" : "+r"(pq[i]) :: "memory");
      };
      bar_sync(wg ? 7 : 8, 256);
      TS(12);
      q_mma(qa1, xo1, 0, 4);
      if (wg) {
        if (QX) {
          pin(qa0);
          wg_fence();
#pragma unroll
          for (int k = 0; k < 4 * QX; k++) wgmma_n64_ss<0, 1, 0>(qa0, dsc<1024, 1>((xoff(k >> 2, 1) >> 4) + xo0 + (k & 3) * 2), dsc<1024, 1>(dlo(sb + woff(k >> 2), 8192) + (k & 3) * 128), 1);
          wg_commit();
        }
        bar_arrive(8, 256);
        wg_wait<QX ? 1 : 0>();
      }
      else { bar_arrive(7, 256); wg_wait<0>(); }
      TS(13);
      if (tid == 0) mbar_arrive(mb + B_EMPTY + 16);
      cut<5>(zero);
      pin(qa1);
      q_phi(qa1, 1, pq, 0, 4);
      tid2 = __shfl_sync(~0u, tid, lane);
      uint32_t done = 0;
#pragma unroll
      for (int j = 0; j < 8; j++) done |= pq[2 * j] | pq[2 * j + 1] | xr[j][3];
      bar_sync(wg ? 7 : 8, 256 + (done & zero));
      TS(9);
      q_mma(qa0, xo0, wg * QX, 4);
      if (!wg) bar_arrive(7, 256);
      wg_wait<0>();
      pin(qa0);
      if (t128 == 0) mbar_arrive(mb + B_EMPTY + 8 * wg);
      TS(6);
#pragma unroll
      for (int i = 0; i < 16; i++) pq0[i] = 0;
#pragma unroll 1
      for (int r = 0;; r++) {
      if (ASYM && r == wg) { pin(qa0); q_phi(qa0, 0, pq0, 0, ASYM); }
      if (r) break;
      {
        uint4 a, v[8];
        uint32_t z[8], zs;
        const int blk = warp * 2 + wg;
        mbar_wait(mb + B_KVL, 0);
        static_for<0, 8>([&](auto ic) { constexpr int i = decltype(ic)::value; v[i] = lds4_o<sb + 11 * SLOT_B + i * 512>(own + (blk + (blk & 4)) * 4096 + lane * 16); });
#pragma unroll
        for (int i = 0; i < 8; i++) z[i] = lds1(sm + 2 * SLOT_B + i * 512 + t128 * 4);
#pragma unroll 1
        for (int it = 0;; it++) {
          zs = hadd2(hadd2(hadd2(z[0], z[1]), hadd2(z[2], z[3])), hadd2(hadd2(z[4], z[5]), hadd2(z[6], z[7])));
          a = hadd8(hadd8(hadd8(v[0], v[1]), hadd8(v[2], v[3])), hadd8(hadd8(v[4], v[5]), hadd8(v[6], v[7])));
          TSV(20, it + 1);
          if (!__any_sync(~0u, hnan(hadd2(hadd2(hadd2(a.x, a.y), hadd2(a.z, a.w)), zs)))) break;
          uint32_t mm = 0;
#pragma unroll
          for (int i = 0; i < 8; i++) mm = max4(max(mm, z[i]), v[i]);
          if (!__any_sync(~0u, mm == SENT)) break;
#pragma unroll
          for (int i = 0; i < 8; i++) { v[i] = ld_rlx4(&G.kvp[cg * 2304 + blk * 256 + i * 32 + lane]); z[i] = ld_rlx((const uint32_t*)&G.kvp[cg * 2304 + 2048 + i * 32] + t128); }
          SPINCHK(it, 4);
        }
        TS(23);
        const uint32_t kb0 = sm + OFF_KVB + blk * 1024 + (lane & 7) * 128;
        stsm4(kb0 + (((lane >> 3) ^ (lane & 7)) << 4), a.x, a.y, a.z, a.w);
        asm volatile("stmatrix.sync.aligned.m8n8.x1.shared.b16 [%0], {%1};" :: "r"(kb0 + ((4 ^ (lane & 7)) << 4)), "r"(zs >> (16 * wg)) : "memory");
        fence_async_smem();
        bar_sync(12, 256);
      }
      TS(7);
      if (t128 == 0) mbar_arrive_rem((wg << 24) + sb + bar3(48));
      o_of(pq, abuf[1], &G.obuf[((mb3 ^ 1) * 64 + hf * 32 + c3) * 128 + (tid2 & 127)], true);
      to = clk();
      TS(29);
      }
      if (!ASYM) cut<4>(zero);
      pin(qa0);
      q_phi(qa0, 0, pq0, ASYM, 4);
      o_of(pq0, abuf[0], nullptr, false);
#pragma unroll
      for (int q = 0; q < 32; q++) { asm volatile("" : "+r"(xr[q >> 2][q & 3])); acc[q * 2] = bf_lo(xr[q >> 2][q & 3]); acc[q * 2 + 1] = bf_hi(xr[q >> 2][q & 3]); }
      pin(acc);
    }
    {
    const int t128 = tid2 & 127, lane = tid2 & 31, g = lane >> 2, t = lane & 3;
    TS(8);
    uint32_t wa[32][4];
    auto load_gu = [&](int f, int lo = 0, int hi = 8) {
      const uint32_t ad = own + ((lane >> 3) & 1) * 8192 + ((lane >> 4) * 8 + (lane & 7)) * 64 + ((warp ^ ((lane >> 1) & 3)) << 4) + ((GU_SLOTS >> (16 * wg + 4 * f)) & 15) * SLOT_B;
      static_for<0, 8>([&](auto ic) { constexpr int i = decltype(ic)::value; if (i >= lo && i < hi) ldsm4t_o<sb + i * 1024>(ad, wa[f * 8 + i]); });
    };
    {
      const uint32_t la = own + wg * 8192 + t128 * 16, fa = sm + wg * 256;
      int pv = tid2 & zero;
      auto second = [&]() {
        delay(to, BDELAY);
#pragma unroll
        for (int k = 2; k < 4; k++) st_rlx4(&G.obuf[((mb3 ^ 1) * 64 + hf * 32 + c3) * 128 + t128 + k * 1024], abuf[1][k]);
      };
      auto own_rows = [&](int at) {
#pragma unroll
        for (int k = 0; k < 4; k++) if (((OPOS >> (4 * k)) & 15) == at) st_rlx4(&G.obuf[(mb3 * 64 + cg * 4 + k) * 128 + t128], abuf[0][k]);
      };
      auto step = [&](const int p, auto jc) {
        constexpr int j = decltype(jc)::value;
        uint4 (&a)[4] = abuf[j == 3 ? 0 : (j + 1) % 3];
        uint4 (&n)[4] = abuf[j == 3 ? 1 : (j + 2) % 3];
        auto fetch = [&]() {
          const uint32_t ra = la + ((p + 1) & 3) * SLOT_B;
          mbar_wait(fa + bar3(0) + o3(p + 1), 0);
          n[0] = lds4_o<sb + 10 * SLOT_B>(ra); n[1] = lds4_o<sb + 10 * SLOT_B + 2048>(ra); n[2] = lds4_o<sb + 10 * SLOT_B + 4096>(ra); n[3] = lds4_o<sb + 10 * SLOT_B + 6144>(ra);
        };
        const bool early = j == 0 ? p > 1 : j == 1 ? true : j == 2 ? p < 15 : false;
        const uint32_t bs = dlo(sb, 8192) + (uint32_t)((WO_SLOTS >> (4 * p)) & 15) * (SLOT_B >> 4);
        if (early) fetch();
        if (p == 1) TS(28);
        pin(acc);
        wg_fence();
#pragma unroll
        for (int k = 0; k < 4; k++) {
          wgmma_n128_rs<1, 0>(acc, a[k].x, a[k].y, a[k].z, a[k].w, dsc<1024, 1>(bs + k * 128), 1);
          if (k == 0) { if (j != 2 || p < 15) mbar_wait(mb + B_FULL3 + 8 * p + 8, 0); wg_fence(); }
        }
        wg_commit();
        if (j == 3) {
#pragma unroll
          for (int i = 0; i < 4; i++) { abuf[2][i] = make_uint4(zero, zero, zero, zero); pin4(abuf[2][i]); }
          if (GUP == 0) { if (fidx >= 0) mbar_wait(mb + B_FULL, 0); load_gu(0); }
          if (GUP < 2) load_gu(1);
          if (B2POS == 1) second();
          own_rows(0);
          TS(24);
          fetch();
          TS(27);
        } else if (j == 0 && p == 1) { own_rows(2); fetch(); own_rows(3); }
        pv++;
        if (__any_sync(~0u, max(max4(max4(0, n[0]), n[1]), max4(max4(0, n[2]), n[3])) == SENT)) {
          const uint4* q = &G.obuf[(mb3 * 64 + chunk_of(pv) * 4) * 128 + t128];
#pragma unroll 1
          for (int it = 0;; it++) {
#pragma unroll
            for (int i = 0; i < 4; i++) n[i] = ld_rlx4(q + i * 128);
            TSV(21, _ts | 1 << pv);
            if (!__any_sync(~0u, max(max4(max4(0, n[0]), n[1]), max4(max4(0, n[2]), n[3])) == SENT)) break;
            SPINCHK(it, 5);
          }
        }
        if (lane == 0 && p < 11) mbar_arrive_rem((wg << 24) + sb + bar3(48) + o3(p + 1));
        wg_wait<1>();
        pin(acc);
        if (j < 3) {
#pragma unroll
          for (int i = 0; i < 4; i++) pin4(abuf[j][i]);
        }
        if (j == 3) own_rows(1); else if (j == 0 && p == 1) own_rows(4);
        if (lane == 0) mbar_arrive(sm + bar3(32) + o3(p));
      };
      if (B2POS == 0) second();
      if (GUP > 0) { if (fidx >= 0) mbar_wait(mb + B_FULL, 0); load_gu(0); }
      if (GUP == 2) load_gu(1);
      mbar_wait(mb + B_FULL3, 0);
      step(0, std::integral_constant<int, 3>{});
#pragma unroll 1
      for (int pp = 1; pp < 16; pp += 3) static_for<0, 3>([&](auto jc) { step(pp + decltype(jc)::value, jc); });
    }
    uint4 wb[4];
#pragma unroll
    for (int i = 0; i < 4; i++) wb[i] = lds4(sm + OFF_LNP + ((g & 1) ? t * 64 : 256) + i * 16);
    const float2 ah = lds2f(sm + OFF_MSC + 8);
    const int ta = __float_as_int((lane & 8) ? ah.y : ah.x);
    int sl = (ta & 7) * 4 + ((ta >> 3) & 1), son = lane < 16 && (ta >> 4) == wid;
    float sid = c3 ? 1.f : (float)((mb3 * 64 + (ta & 63)) * 16 + 1);
    uint4 *sp = &G.cst[(lane & 7) * 32 + (rb * 2 + hf) * 2 + ((lane >> 3) & 1)], *sq = &G.st2[mb3 * 64 + warp * 16 + (t & 1) * 8 + g];
    asm volatile("" : "+r"(sl), "+r"(son), "+f"(sid), "+l"(sp), "+l"(sq) :: "memory");
    if (T4) cut<7>(zero);
    wg_wait<0>();
    pin(acc);
#pragma unroll
    for (int i = 0; i < 4; i++) pin4(abuf[0][i]);
    TS(10);
    const uint32_t msc = sm + OFF_MSC;
    uint32_t hp[8][4];
    {
      float se[2][4], q[4] = {0.f, 0.f, 0.f, 0.f};
#pragma unroll
      for (int i = 0; i < 8; i++) se[i >> 2][i & 3] = 0.f;
#pragma unroll
      for (int j = 0; j < 8; j++) {
#pragma unroll
        for (int i = 0; i < 4; i++) { const float a = acc[j * 8 + i * 2], c = acc[j * 8 + i * 2 + 1]; hp[j][i] = pack2(a, c); q[i] = fmaf(a, a, fmaf(c, c, q[i])); }
        mma16816(se[j & 1], hp[j], (j & 1) ? wb[j >> 1].z : wb[j >> 1].x, (j & 1) ? wb[j >> 1].w : wb[j >> 1].y);
      }
      const bool od = t & 1;
      const float q0 = q[0] + q[2], q1 = q[1] + q[3];
      float qq = (od ? q1 : q0) + __shfl_xor_sync(~0u, od ? q0 : q1, 1);
      qq += __shfl_xor_sync(~0u, qq, 2);
      const float ss = od ? se[0][2] + se[1][2] : se[0][0] + se[1][0], ee = od ? se[0][3] + se[1][3] : se[0][1] + se[1][1];
      red4(son, sp, __shfl_sync(~0u, ss, sl), __shfl_sync(~0u, qq, sl), __shfl_sync(~0u, ee, sl), sid);
      red4(t < 2, sq, ss, qq, ee, 1.f);
#pragma unroll 1
      for (int c = 0; c < 2; c++) {
        const int tr = __float_as_int(c ? ah.y : ah.x);
        if ((tr >> 4) == wid && g == (tr & 7)) {
#pragma unroll
          for (int i = 0; i < 4; i++)
            st_rlx4(&G.hsel[((rb * 2 + hf) * 2 + c) * 128 + c3 * 16 + i * 4 + t], (tr & 8) ? make_uint4(hp[2 * i][1], hp[2 * i][3], hp[2 * i + 1][1], hp[2 * i + 1][3])
                                                                                           : make_uint4(hp[2 * i][0], hp[2 * i][2], hp[2 * i + 1][0], hp[2 * i + 1][2]));
        }
      }
      if (lane == 0) mbar_arrive(sm + bar3(61));
      TS(11);
    }
    uint32_t wd[8][2][4];
    const uint32_t da = sm + ((D_SLOTS >> (2 * (wid & 6))) & 15) * SLOT_B + (wid & 1) * 8192 + ((lane >> 4) * 8 + (lane & 7)) * 128 + ((((lane >> 3) & 1) ^ (lane & 7)) << 4);
    int pass = 0;
    if (!GUPOS) { if (fidx >= 0) mbar_wait(mb + B_FFN, 1); load_gu(2); load_gu(3); }
    {
      bar_sync(1, 256);
      const uint32_t ha = sm + HST + wid * 4096 + (lane & 15) * 256 + (((lane >> 4) ^ (lane & 7)) << 4);
      static_for<0, 8>([&](auto jc) { constexpr int j = decltype(jc)::value; stsm4_o<(j >> 2) * 128>(ha ^ ((j & 3) << 5), hp[j][0], hp[j][1], hp[j][2], hp[j][3]); });
      asm volatile("fence.acq_rel.cta;" ::: "memory");
      __syncwarp();
      if (lane == 0) mbar_arrive(sm + bar3(62));
    }
    auto load_d1 = [&]() {
      if (fidx >= 0) mbar_wait(mb + B_FFN + 8, 0);
      static_for<0, 8>([&](auto ic) { constexpr int i = decltype(ic)::value; ldsm4t_o<(i & 1) * 2048>(da ^ ((i >> 1) << 5), wd[i >> 1][i & 1]); });
    };
    if (GUPOS) { if (fidx >= 0) mbar_wait(mb + B_FFN, 1); load_gu(2); load_gu(3); }
    if (!D1POS) load_d1();
#pragma unroll 1
    for (;; pass++) {
      TS(15);
      mbar_wait(mb + B_SEL, 0);
      const uint4 sx = lds4(msc + 16 + pass * 32 + (lane & 16));
      TS(26);
      const uint4* xp = &G.hsel[sx.y * 128 + wid * 16 + (lane & 15)];
      uint4 xv = ld_rlx4(xp);
      if (D1POS == 1) load_d1();
#pragma unroll 1
      for (int it = 0; __any_sync(~0u, max4(0, xv) == SENT); it++) { xv = ld_rlx4(xp); SPINCHK(it, 7); }
      const float f = __uint_as_float(sx.z), n = __uint_as_float(sx.w);
      sts4(sm + OFF_XS + wid * 512 + ((lane & 12) * 2 + (lane >> 4) * 4 + t) * 16, pack2(fmaf(bf_lo(xv.x), f, n), fmaf(bf_hi(xv.x), f, n)), pack2(fmaf(bf_lo(xv.y), f, n), fmaf(bf_hi(xv.y), f, n)),
           pack2(fmaf(bf_lo(xv.z), f, n), fmaf(bf_hi(xv.z), f, n)), pack2(fmaf(bf_lo(xv.w), f, n), fmaf(bf_hi(xv.w), f, n)));
      if (wid == rb && (g & 3) == (cg >> 2)) sts4(msc + 96 + (lane >> 4) * 16 + t * 32, xv.x, xv.y, xv.z, xv.w);
      bar_sync(2 + wg, 128);
      TS(14);
      float gu[4][4];
#pragma unroll
      for (int i = 0; i < 16; i++) gu[i >> 2][i & 3] = 0.f;
      uint4 xb[4];
      static_for<0, 4>([&](auto ic) { constexpr int i = decltype(ic)::value; xb[i] = lds4_o<sb + OFF_XS + i * 128>(own + wg * 2048 + (lane >> 3) * 512 + (lane & 7) * 16); });
      if (D1POS == 2) load_d1();
#pragma unroll
      for (int i = 0; i < 16; i++) {
        const int ks = i & 7;
#pragma unroll
        for (int j = i < 8 ? 2 : 0; j < (i < 8 ? 4 : 2); j++) mma16816(gu[j], wa[j * 8 + ks], (ks & 1) ? xb[ks >> 1].z : xb[ks >> 1].x, (ks & 1) ? xb[ks >> 1].w : xb[ks >> 1].y);
        if (i == D2I) {
          if (D1POS == 3) load_d1();
          const uint32_t dd = da | ((__float_as_uint(gu[2][0]) | __float_as_uint(gu[3][0])) & zero);
          static_for<0, 8>([&](auto jc) { constexpr int j = decltype(jc)::value; ldsm4t_o<4096 + (j & 1) * 2048>(dd ^ ((j >> 1) << 5), wd[4 + (j >> 1)][j & 1]); });
          if (T1) cut<8>(zero);
#pragma unroll
          for (int j = 0; j < 4; j++) { pin(gu[j]); pin4(xb[j]); }
        }
      }
      {
        float o[4];
#pragma unroll
        for (int j = 0; j < 4; j++) o[j] = t == 0 ? gu[0][j] : t == 1 ? gu[1][j] : t == 2 ? gu[2][j] : gu[3][j];
        const float e0 = ((t & 2) ? o[2] : o[0]) + __shfl_xor_sync(~0u, (t & 2) ? o[0] : o[2], 2), e1 = ((t & 2) ? o[3] : o[1]) + __shfl_xor_sync(~0u, (t & 2) ? o[1] : o[3], 2);
        sts1(sm + OFF_XS + 4096 + tid2 * 4, __float_as_uint(((t & 1) ? e1 : e0) + __shfl_xor_sync(~0u, (t & 1) ? e0 : e1, 1)));
      }
      TS(25);
      mbar_wait(mb + B_SEL2, 0);
      const uint32_t miss = lds1(msc + 80);
      bar_sync(1, 256);
      if (pass || !miss) break;
      load_gu(2); load_gu(3);
    }
    {
      const uint4 p0 = lds4_o<sb + OFF_XS + 4096>(own + lane * 16), p1 = lds4_o<sb + OFF_XS + 4608>(own + lane * 16);
      const float g0 = __uint_as_float(p0.x) + __uint_as_float(p1.x), g1 = __uint_as_float(p0.y) + __uint_as_float(p1.y);
      const float u0 = __uint_as_float(p0.z) + __uint_as_float(p1.z), u1 = __uint_as_float(p0.w) + __uint_as_float(p1.w);
      const uint32_t act = pack2(g0 * rcp(1.f + ex2(-1.4426950408889634f * g0)) * u0, g1 * rcp(1.f + ex2(-1.4426950408889634f * g1)) * u1);
      uint32_t bq[4];
#pragma unroll
      for (int i = 0; i < 4; i++) {
        const uint32_t lo = __shfl_sync(~0u, act, i * 8 + 2 * t), hi = __shfl_sync(~0u, act, i * 8 + 2 * t + 1);
        bq[i] = __byte_perm(lo, hi, (g & 1) ? 0x7632 : 0x5410);
      }
      TS(16);
      float ya[8][4];
#pragma unroll
      for (int i = 0; i < 8; i++) { ya[i][0] = 0.f; ya[i][1] = 0.f; ya[i][2] = 0.f; ya[i][3] = 0.f; }
#pragma unroll
      for (int ks = 0; ks < 2; ks++)
#pragma unroll
        for (int i = 0; i < 8; i++) mma16816(ya[i], wd[i][ks], bq[ks * 2], bq[ks * 2 + 1]);
    if (fidx >= 0) {
      uint2* const yp = (uint2*)&G.ybuf[((wid * 16 + t * 2) * NFFN + fidx) * 4] + g;
#pragma unroll
      for (int h = 0; h < 2; h++) {
        float o[4];
#pragma unroll
        for (int j = 0; j < 4; j++) o[j] = t == 0 ? ya[h * 4][j] : t == 1 ? ya[h * 4 + 1][j] : t == 2 ? ya[h * 4 + 2][j] : ya[h * 4 + 3][j];
        st_rlx2(yp + h * (8 * NFFN * 8), __float_as_uint(o[0]), __float_as_uint(o[1]));
        st_rlx2(yp + h * (8 * NFFN * 8) + NFFN * 8, __float_as_uint(o[2]), __float_as_uint(o[3]));
      }
    }
    }
    const uint32_t ty = clk();
    TS(17);
    if (wid < 7) {
      const uint4* const yq = &G.ybuf[b * NFFN * 4 + wid * 64 + lane];
      const uint4 sel = lds4(msc + 16 + pass * 32 + (lane & 1) * 16);
      const uint32_t fh = lds1(msc + 96 + (lane & 1) * 16 + (g & 3) * 32 + (cg & 3) * 4);
      const float r = __uint_as_float(sel.x ^ (~(uint32_t)((int)sel.x >> 31) | 0x80000000u));
      float sg = rcp(1.f + ex2(-1.4426950408889634f * r)), base = fmaf((lane & 2) ? bf_hi(fh) : bf_lo(fh), 1.f + __uint_as_float(sel.z), __uint_as_float(sel.w));
      __nv_bfloat16* op = P.out + (size_t)(2047 - (sel.x & 2047)) * D_ + b * 8 + ((lane >> 1) & 7);
      asm volatile("" : "+f"(sg), "+f"(base), "+l"(op) :: "memory");
      delay(ty | (__float_as_uint(sg) & zero), YDELAY);
      uint4 v0, v1;
#pragma unroll 1
      for (int it = 0;; it++) {
        v0 = ld_rlx4(yq); v1 = ld_rlx4(yq + 32);
        TSV(22, it + 1);
        if (!__any_sync(~0u, max(max4(0, v0), max4(0, v1)) == SENT)) break;
        SPINCHK(it, 8);
      }
      if (lane == 0) mbar_arrive(sm + bar3(63));
      TS(18);
      float y0 = __uint_as_float(v0.x) + __uint_as_float(v1.x), y1 = __uint_as_float(v0.y) + __uint_as_float(v1.y);
      float y2 = __uint_as_float(v0.z) + __uint_as_float(v1.z), y3 = __uint_as_float(v0.w) + __uint_as_float(v1.w);
      float z0 = ((lane & 16) ? y2 : y0) + __shfl_xor_sync(~0u, (lane & 16) ? y0 : y2, 16), z1 = ((lane & 16) ? y3 : y1) + __shfl_xor_sync(~0u, (lane & 16) ? y1 : y3, 16);
      z0 = ((lane & 8) ? z1 : z0) + __shfl_xor_sync(~0u, (lane & 8) ? z0 : z1, 8);
      z0 += __shfl_xor_sync(~0u, z0, 4);
      const uint32_t yx = sm + OFF_COLSUM;
      if (!(lane & 4)) sts1(yx + (t * 4 + (lane >> 3)) * 32 + wid * 4, __float_as_uint(z0));
      if (wid) bar_arrive(1, 224);
      else {
        bar_sync(1, 224);
        const uint4 a = lds4(yx + (lane & 15) * 32), c = lds4(yx + (lane & 15) * 32 + 16);
        const float y = ((__uint_as_float(a.x) + __uint_as_float(a.y)) + (__uint_as_float(a.z) + __uint_as_float(a.w))) + ((__uint_as_float(c.x) + __uint_as_float(c.y)) + __uint_as_float(c.z));
        if (lane < 16) *op = __float2bfloat16(fmaf(y, sg, base));
      }
    }
    }
    TS(19); TSG(31);
    if (warp == 0) TS_DUMP(wg);
  }
}

typedef CUresult (*EncodeFn)(CUtensorMap*, CUtensorMapDataType, cuuint32_t, void*, const cuuint64_t*, const cuuint64_t*, const cuuint32_t*,
                             const cuuint32_t*, CUtensorMapInterleave, CUtensorMapSwizzle, CUtensorMapL2promotion, CUtensorMapFloatOOBfill);
void make_map(EncodeFn enc, CUtensorMap* m, const void* p, uint64_t cols, uint64_t rows, uint64_t d0, uint32_t b0, uint32_t b1, uint32_t b2, CUtensorMapSwizzle sw,
              CUtensorMapL2promotion promo = CU_TENSOR_MAP_L2_PROMOTION_L2_128B) {
  cuuint64_t dims[3] = {d0, rows, cols / d0}, str[2] = {cols * 2, d0 * 2};
  cuuint32_t box[3] = {b0, b1, b2}, es[3] = {1, 1, 1};
  enc(m, CU_TENSOR_MAP_DATA_TYPE_BFLOAT16, b2 ? 3 : 2, const_cast<void*>(p), dims, str, box, es, CU_TENSOR_MAP_INTERLEAVE_NONE, sw,
      promo, CU_TENSOR_MAP_FLOAT_OOB_FILL_NONE);
}

}

extern "C" void kernel_launch(void* const* d_in, const int* in_sizes, int n_in, void* d_out, int out_size) {
  (void)in_sizes; (void)n_in; (void)out_size;
  Ptrs P;
  P.x = (const __nv_bfloat16*)d_in[0]; P.wqkv = (const __nv_bfloat16*)d_in[1]; P.wo = (const __nv_bfloat16*)d_in[2];
  P.wr = (const __nv_bfloat16*)d_in[4]; P.wg = (const __nv_bfloat16*)d_in[5]; P.wu = (const __nv_bfloat16*)d_in[6];
  P.wd = (const __nv_bfloat16*)d_in[7]; P.out = (__nv_bfloat16*)d_out;
  void* fn = nullptr;
  cudaDriverEntryPointQueryResult q;
  cudaGetDriverEntryPoint("cuTensorMapEncodeTiled", &fn, cudaEnableDefault, &q);
  EncodeFn enc = (EncodeFn)fn;
  CUtensorMap tmX, tmW, tmO, tmG, tmU, tmD, tmM, tmPG, tmPU, tmPD;
  make_map(enc, &tmX, P.x, D_, S_, D_, 64, 128, 0, CU_TENSOR_MAP_SWIZZLE_128B);
  make_map(enc, &tmW, P.wqkv, 3 * D_, D_, 3 * D_, 64, 64, 0, CU_TENSOR_MAP_SWIZZLE_128B);
  make_map(enc, &tmG, P.wg, F_, D_, F_, 32, 128, 0, CU_TENSOR_MAP_SWIZZLE_64B);
  make_map(enc, &tmU, P.wu, F_, D_, F_, 32, 128, 0, CU_TENSOR_MAP_SWIZZLE_64B);
  make_map(enc, &tmD, P.wd, D_, F_, 64, 64, 32, 4, CU_TENSOR_MAP_SWIZZLE_128B);
  make_map(enc, &tmPG, P.wg, F_, D_, F_, 8, 32, 0, CU_TENSOR_MAP_SWIZZLE_NONE);
  make_map(enc, &tmPU, P.wu, F_, D_, F_, 8, 32, 0, CU_TENSOR_MAP_SWIZZLE_NONE);
  make_map(enc, &tmPD, P.wd, 128, F_ * 8, 128, 8, 32, 0, CU_TENSOR_MAP_SWIZZLE_NONE, CU_TENSOR_MAP_L2_PROMOTION_L2_256B);
  for (int m = 0; m < 2; m++) {
    cuuint64_t dims[4] = {64, m ? 64u : 16u, m ? 16u : 64u, 16}, str[3] = {2 * D_, (m ? 128u : 32u) * D_, 128};
    cuuint32_t box[4] = {64, 16, 4, 2}, es[4] = {1, 1, 1, 1};
    enc(m ? &tmM : &tmO, CU_TENSOR_MAP_DATA_TYPE_BFLOAT16, 4, const_cast<__nv_bfloat16*>(P.wo), dims, str, box, es, CU_TENSOR_MAP_INTERLEAVE_NONE,
        CU_TENSOR_MAP_SWIZZLE_128B, CU_TENSOR_MAP_L2_PROMOTION_L2_128B, CU_TENSOR_MAP_FLOAT_OOB_FILL_NONE);
  }
  cudaFuncSetAttribute(fused_kernel, cudaFuncAttributeMaxDynamicSharedMemorySize, SMEM_BYTES);
  fused_kernel<<<NCTA, 384, SMEM_BYTES>>>(P, tmX, tmW, tmO, tmG, tmU, tmD, tmM, tmPG, tmPU, tmPD);
}
```
